```python
import torch

def _softmax(x, axis=-1):
    return torch.softmax(x, dim=axis)

def _gelu(x):
    return torch.nn.functional.gelu(x, approximate='tanh')

def _silu(x):
    return torch.nn.functional.silu(x)

def _sigmoid(x):
    return torch.sigmoid(x)

def _layernorm(x, axis=-1, eps=1e-05):
    m = x.mean(dim=axis, keepdim=True)
    v = x.var(dim=axis, keepdim=True, unbiased=False)
    return (x - m) / torch.sqrt(v + eps)

def _scatter_add(tgt, idx, src, axis=0):
    return tgt.clone().index_add_(axis, idx, src)

def _segment_sum(src, seg, n):
    out = torch.zeros((n,) + src.shape[1:], dtype=src.dtype)
    return out.index_add_(0, seg, src)

def _pad(x, pw):
    flat = tuple((v for pair in reversed(pw) for v in pair))
    return torch.nn.functional.pad(x, flat)
kernel_name = 'adaLN_cond__ssm_conv_h3__glu_gated_swiglu__prompt'

def setup_inputs():

    _w = lambda a: (lambda t: t.to(torch.bfloat16) if t.is_floating_point() else t)(torch.as_tensor(a))

    def _A_setup():
        B, S, D = (1, 2048, 640)
        ks = 4
        return {'q': _w((lambda *s: torch.randn(*s, dtype=torch.bfloat16) * 0.05)(B, S, D)), 'k': _w((lambda *s: torch.randn(*s, dtype=torch.bfloat16) * 0.8)(B, S, D)), 'v': _w((lambda *s: torch.randn(*s, dtype=torch.bfloat16) * 0.8)(B, S, D)), 'shift_k': _w((lambda *s: torch.randn(*s, dtype=torch.bfloat16) * 0.8)(D, ks) * 0.5), 'ssm_k': _w((lambda *s: torch.randn(*s, dtype=torch.bfloat16) * 0.8)(D, S) * (1.0 / S ** 0.5)), 'ssm_D': _w((lambda *s: torch.randn(*s, dtype=torch.bfloat16) * 0.8)(D))}
    _A_in = _A_setup()

    def _B_setup():
        B, S, D, F = (1, 2048, 640, 1536)
        return {'x': _w((lambda *s: torch.randn(*s, dtype=torch.bfloat16) * 0.05)(B, S, D)), 'w1': _w((lambda *s: torch.randn(*s, dtype=torch.bfloat16) * 0.8)(D, F) * (2.0 / D) ** 0.5), 'w3': _w((lambda *s: torch.randn(*s, dtype=torch.bfloat16) * 0.8)(D, F) * (2.0 / D) ** 0.5), 'w2': _w((lambda *s: torch.randn(*s, dtype=torch.bfloat16) * 0.8)(F, D) * (2.0 / F) ** 0.5)}
    _B_in = _B_setup()
    return {'A_q': _A_in['q'], 'A_k': _A_in['k'], 'A_v': _A_in['v'], 'A_shift_k': _A_in['shift_k'], 'A_ssm_k': _A_in['ssm_k'], 'A_ssm_D': _A_in['ssm_D'], 'B_x': _B_in['x'], 'B_w1': _B_in['w1'], 'B_w3': _B_in['w3'], 'B_w2': _B_in['w2'], 'c': _w((lambda *s: torch.randn(*s, dtype=torch.bfloat16) * 0.2)(1, 640) * 8.0), 'w_mod': _w((lambda *s: torch.randn(*s, dtype=torch.bfloat16) * 0.2)(640, 6 * 640) * 640 ** (-0.5) * 8.0)}

def reference(A_q, A_k, A_v, A_shift_k, A_ssm_k, A_ssm_D, B_x, B_w1, B_w3, B_w2, c, w_mod):

    def _A_ref(q, k, v, shift_k, ssm_k, ssm_D):
        B, S, D = q.shape
        ks = shift_k.shape[-1]
        k_pad = _pad(k, ((0, 0), (ks - 1, 0), (0, 0)))
        k_shift = torch.zeros_like(k)
        for t in range(ks):
            k_shift = k_shift + k_pad[:, t:t + S, :] * shift_k[:, ks - 1 - t][None, None, :]
        kv = k_shift * v
        L = 2 * S
        kv_pad = _pad(kv, ((0, 0), (0, S), (0, 0)))
        kf_pad = _pad(ssm_k, ((0, 0), (0, S)))
        kv_f = (lambda x, axes=(-2, -1): torch.fft.rfft2(x.float(), dim=axes))(kv_pad[:, None, :, :], axes=(1, 2))
        kf_f = (lambda x, axes=(-2, -1): torch.fft.rfft2(x.float(), dim=axes))(kf_pad[:, None, :], axes=(1, 2))
        kf_f = (lambda x, *d: x.permute(*d))(kf_f, 1, 2, 0)
        y_f = kv_f * kf_f[None, :, :, :]
        y = (lambda x, s, axes=(-2, -1): torch.fft.irfft2(x, s=s, dim=axes).to(torch.bfloat16))(y_f, (1, L), axes=(1, 2))[:, 0, :S, :]
        y = y + kv * ssm_D[None, None, :]
        return q * y

    def _B_ref(x, w1, w3, w2):
        gate = torch.einsum('bsd,df->bsf', x, w1)
        up = torch.einsum('bsd,df->bsf', x, w3)
        h = _silu(gate) * up
        out = torch.einsum('bsf,fd->bsd', h, w2)
        return out
    x = A_q
    mod = (_silu(c) @ w_mod).reshape(c.shape[0], 6, 1, -1)
    sa, ca, ga, sb, cb, gb = (mod[:, 0].clone(), mod[:, 1].clone(), mod[:, 2].clone(), mod[:, 3].clone(), mod[:, 4].clone(), mod[:, 5].clone())
    h = _layernorm(x, axis=-1) * (1 + ca) + sa
    x = x + ga * _A_ref(h, A_k, A_v, A_shift_k, A_ssm_k, A_ssm_D)
    h = _layernorm(x, axis=-1) * (1 + cb) + sb
    x = x + gb * _B_ref(h, B_w1, B_w3, B_w2)
    return x
```

```cpp
#include <cuda_runtime.h>
#include <cuda.h>
#include <cuda_bf16.h>
#include <stdint.h>
#include <stdlib.h>
#include <string.h>

#define M1W
#define ORDER "k1v1f0q0q1q2q3q4k2v2f1k3v3f2k4v4f3w0f4"
#define WIN 16
#define EARLY 0
typedef __nv_bfloat16 bf16;
constexpr int S_ = 2048, D_ = 640, F_ = 1536;

struct Scratch {
  uint32_t st1[2][1024];
  uint32_t st2[32][4][128];
  uint32_t modc[128][5][32];
  uint2 modv[3][D_];
  uint32_t uv[8][3072];
  unsigned hint[9][8][32];
  unsigned xsh[5][8][32], hhf[256 * 8], key[256];
  uint4 xr[D_ * 256];
  uint4 qt[D_ * 256];
  uint4 xs[D_ * 256];
  uint4 x1[2][D_ * 256];
  uint4 hh[32 * 8 * 1536];
};
__device__ __align__(1024) Scratch g_s;

__device__ __forceinline__ uint32_t smem_u32(const void* p) { return (uint32_t)__cvta_generic_to_shared(p); }
__device__ __forceinline__ void mbar_expect_tx(uint32_t b, uint32_t n) { asm volatile("mbarrier.arrive.expect_tx.shared::cta.b64 _, [%0], %1;" ::"r"(b), "r"(n) : "memory"); }
__device__ __forceinline__ void mbar_arrive(uint32_t b) { asm volatile("mbarrier.arrive.shared::cta.b64 _, [%0];" ::"r"(b) : "memory"); }
__device__ __forceinline__ void mbar_arrive2(uint32_t b) { asm volatile("mbarrier.arrive.shared::cta.b64 _, [%0], 2;" ::"r"(b) : "memory"); }
__device__ __forceinline__ uint32_t mapa(uint32_t a, uint32_t cta) { uint32_t r; asm volatile("mapa.shared::cluster.u32 %0, %1, %2;" : "=r"(r) : "r"(a), "r"(cta)); return r; }
__device__ __forceinline__ void mbar_arrive_remote(uint32_t rb) { asm volatile("mbarrier.arrive.shared::cluster.b64 _, [%0];" ::"r"(rb) : "memory"); }
constexpr int SPIN_LIMIT = 1 << 16;
template <int N> __device__ __forceinline__ void mbar_init(uint32_t b, uint32_t count) {
#pragma unroll
  for (int i = 0; i < N; i++) asm volatile("mbarrier.init.shared::cta.b64 [%0], %1;" ::"r"(b + 8 * i), "r"(count) : "memory");
}
__device__ __forceinline__ bool elect() { uint32_t p; asm volatile("{.reg .pred q; elect.sync _|q, 0xffffffff; selp.u32 %0, 1, 0, q;}" : "=r"(p)); return p; }
__device__ __forceinline__ void arrive1(uint32_t b) { __syncwarp(); if (elect()) mbar_arrive(b); }
__device__ __forceinline__ bool mbar_test(uint32_t b) {
  uint32_t ok;
  asm volatile("{.reg .pred p; mbarrier.test_wait.parity.shared::cta.b64 p, [%1], 0; selp.u32 %0,1,0,p;}" : "=r"(ok) : "r"(b) : "memory");
  return ok;
}
#define WAIT_LOOP(sem) "{.reg .pred p; mov.u32 %0, 0; W: mbarrier.try_wait.parity" sem ".shared::cta.b64 p, [%1], %2; @p bra.uni D; add.u32 %0, %0, 1; setp.lt.u32 p, %0, %3; @p bra.uni W; D:}"
__device__ __forceinline__ void mbar_wait(uint32_t b, uint32_t ph = 0) {
  int it;
  asm volatile(WAIT_LOOP("") : "=&r"(it) : "r"(b), "r"(ph), "n"(SPIN_LIMIT) : "memory");
}
__device__ __forceinline__ void mbar_wait_cluster(uint32_t b, uint32_t ph = 0) {
  int it;
  asm volatile(WAIT_LOOP(".acquire.cluster") : "=&r"(it) : "r"(b), "r"(ph), "n"(SPIN_LIMIT) : "memory");
}
__device__ __forceinline__ void wait_clock(uint32_t t) {
  asm volatile("{.reg .pred p; .reg .s32 d; W: mov.u32 d, %%clock; sub.s32 d, d, %0; setp.lt.s32 p, d, 0; @p bra.uni W;}" ::"r"(t) : "memory");
}
__device__ __forceinline__ void tma2d(uint32_t dst, const CUtensorMap* m, int c0, int c1, uint32_t bar) {
  asm volatile("cp.async.bulk.tensor.2d.shared::cluster.global.mbarrier::complete_tx::bytes [%0], [%1, {%3,%4}], [%2];" ::"r"(dst), "l"(m), "r"(bar), "r"(c0), "r"(c1) : "memory");
}
__device__ __forceinline__ void tma3d(uint32_t dst, const CUtensorMap* m, int c0, int c1, int c2, uint32_t bar) {
  asm volatile("cp.async.bulk.tensor.3d.shared::cluster.global.mbarrier::complete_tx::bytes [%0], [%1, {%3,%4,%5}], [%2];" ::"r"(dst), "l"(m), "r"(bar), "r"(c0), "r"(c1), "r"(c2) : "memory");
}
__device__ __forceinline__ void tma5d(uint32_t dst, const CUtensorMap* m, int c0, int c4, uint32_t bar) {
  asm volatile("cp.async.bulk.tensor.5d.shared::cluster.global.mbarrier::complete_tx::bytes [%0], [%1, {%4,%3,%3,%3,%5}], [%2];" ::"r"(dst), "l"(m), "r"(bar), "r"(0), "r"(c0), "r"(c4) : "memory");
}
__device__ __forceinline__ void tma2d_store(const CUtensorMap* m, int c0, int c1, uint32_t src) {
  asm volatile("cp.async.bulk.tensor.2d.global.shared::cta.bulk_group [%0, {%2,%3}], [%1];" ::"l"(m), "r"(src), "r"(c0), "r"(c1) : "memory");
}
__device__ __forceinline__ void bulk_load(uint32_t dst, const void* src, uint32_t bytes, uint32_t bar) {
  asm volatile("cp.async.bulk.shared::cluster.global.mbarrier::complete_tx::bytes [%0], [%1], %2, [%3];" ::"r"(dst), "l"(src), "r"(bytes), "r"(bar) : "memory");
}
__device__ __forceinline__ void prefetch_map(const CUtensorMap* m) { asm volatile("prefetch.tensormap [%0];" ::"l"(m) : "memory"); }
__device__ __forceinline__ void bulk_commit() { asm volatile("cp.async.bulk.commit_group;" ::: "memory"); }
__device__ __forceinline__ void bulk_wait_read() { asm volatile("cp.async.bulk.wait_group.read 0;" ::: "memory"); }
__device__ __forceinline__ void fence_async_smem() { asm volatile("fence.proxy.async.shared::cta;" ::: "memory"); }
__device__ __forceinline__ void fence_async_all() { asm volatile("fence.proxy.async.global;" ::: "memory"); }
__device__ __forceinline__ void named_bar(int id, int n) { asm volatile("bar.sync %0, %1;" ::"r"(id), "r"(n) : "memory"); }
__device__ __forceinline__ bool bar_all(int id, bool v) {
  uint32_t r;
  asm volatile("{.reg .pred p, q; setp.ne.u32 p, %2, 0; bar.red.and.pred q, %1, 128, p; selp.u32 %0, 1, 0, q;}" : "=r"(r) : "r"(id), "r"((uint32_t)v) : "memory");
  return __all_sync(~0u, r);
}
__device__ __forceinline__ void cluster_wait() { asm volatile("barrier.cluster.wait.aligned;" ::: "memory"); }
__device__ __forceinline__ void wg_fence() { asm volatile("wgmma.fence.sync.aligned;" ::: "memory"); }
__device__ __forceinline__ void wg_commit() { asm volatile("wgmma.commit_group.sync.aligned;" ::: "memory"); }
template <int N> __device__ __forceinline__ void wg_wait() { asm volatile("wgmma.wait_group.sync.aligned %0;" ::"n"(N) : "memory"); }
template <int N> __device__ __forceinline__ void fence_regs(float (&a)[N]) {
#pragma unroll
  for (int i = 0; i < N; i++) asm volatile("" : "+f"(a[i])::"memory");
}
__device__ __forceinline__ uint64_t mkdesc(uint32_t addr, uint32_t lbo, uint32_t sbo, uint32_t swz) {
  uint32_t lo = (addr >> 4) | ((lbo >> 4) << 16), hi = (sbo >> 4) | (swz << 30);
  return ((uint64_t)hi << 32) | lo;
}
__device__ __forceinline__ void stmatrix_x4(uint32_t a, uint32_t r0, uint32_t r1, uint32_t r2, uint32_t r3) {
  asm volatile("stmatrix.sync.aligned.m8n8.x4.shared.b16 [%0], {%1,%2,%3,%4};" ::"r"(a), "r"(r0), "r"(r1), "r"(r2), "r"(r3) : "memory");
}
__device__ __forceinline__ void stmatrix_x4_t(uint32_t a, uint32_t r0, uint32_t r1, uint32_t r2, uint32_t r3) {
  asm volatile("stmatrix.sync.aligned.m8n8.x4.trans.shared.b16 [%0], {%1,%2,%3,%4};" ::"r"(a), "r"(r0), "r"(r1), "r"(r2), "r"(r3) : "memory");
}
__device__ __forceinline__ void ldmatrix_x4_t(uint32_t* r, uint32_t a) {
  asm volatile("ldmatrix.sync.aligned.m8n8.x4.trans.shared.b16 {%0,%1,%2,%3}, [%4];" : "=r"(r[0]), "=r"(r[1]), "=r"(r[2]), "=r"(r[3]) : "r"(a) : "memory");
}
__device__ __forceinline__ uint32_t lds32(uint32_t a) { uint32_t v; asm volatile("ld.shared.b32 %0, [%1];" : "=r"(v) : "r"(a) : "memory"); return v; }
__device__ __forceinline__ uint2 lds64(uint32_t a) { uint2 v; asm volatile("ld.shared.v2.b32 {%0,%1}, [%2];" : "=r"(v.x), "=r"(v.y) : "r"(a) : "memory"); return v; }
__device__ __forceinline__ uint4 lds128(uint32_t a) { uint4 v; asm volatile("ld.shared.v4.b32 {%0,%1,%2,%3}, [%4];" : "=r"(v.x), "=r"(v.y), "=r"(v.z), "=r"(v.w) : "r"(a) : "memory"); return v; }
__device__ __forceinline__ void sts32(uint32_t a, uint32_t v) { asm volatile("st.shared.b32 [%0], %1;" ::"r"(a), "r"(v) : "memory"); }
__device__ __forceinline__ void sts64(uint32_t a, uint32_t x, uint32_t y) { asm volatile("st.shared.v2.b32 [%0], {%1,%2};" ::"r"(a), "r"(x), "r"(y) : "memory"); }
__device__ __forceinline__ void sts128(uint32_t a, uint32_t x, uint32_t y, uint32_t z, uint32_t w) { asm volatile("st.shared.v4.b32 [%0], {%1,%2,%3,%4};" ::"r"(a), "r"(x), "r"(y), "r"(z), "r"(w) : "memory"); }
__device__ __forceinline__ uint4 ld_relaxed128(const void* p) { uint4 v; asm volatile("ld.relaxed.gpu.global.v4.u32 {%0,%1,%2,%3}, [%4];" : "=r"(v.x), "=r"(v.y), "=r"(v.z), "=r"(v.w) : "l"(p) : "memory"); return v; }
__device__ __forceinline__ uint2 ld_relaxed64(const void* p) { uint2 v; asm volatile("ld.relaxed.gpu.global.v2.u32 {%0,%1}, [%2];" : "=r"(v.x), "=r"(v.y) : "l"(p) : "memory"); return v; }
__device__ __forceinline__ uint32_t ld_relaxed32(const void* p) { uint32_t v; asm volatile("ld.relaxed.gpu.global.u32 %0, [%1];" : "=r"(v) : "l"(p) : "memory"); return v; }
__device__ __forceinline__ void st_relaxed128(void* p, uint32_t x, uint32_t y, uint32_t z, uint32_t w) { asm volatile("st.relaxed.gpu.global.v4.u32 [%0], {%1,%2,%3,%4};" ::"l"(p), "r"(x), "r"(y), "r"(z), "r"(w) : "memory"); }
__device__ __forceinline__ void st_relaxed32(void* p, uint32_t x) { asm volatile("st.relaxed.gpu.global.u32 [%0], %1;" ::"l"(p), "r"(x) : "memory"); }
__device__ __forceinline__ void red_hint(unsigned* p) { asm volatile("red.relaxed.gpu.global.add.u32 [%0], 1;" ::"l"(p) : "memory"); }
__device__ __forceinline__ void publish(uint32_t* p, uint32_t x) { asm volatile("{.reg .b32 t; atom.relaxed.gpu.global.exch.b32 t, [%0], %1;}" ::"l"(p), "r"(x) : "memory"); }
__device__ __forceinline__ uint32_t ldg32(const void* p) { uint32_t v; asm volatile("ld.global.nc.L1::no_allocate.b32 %0, [%1];" : "=r"(v) : "l"(p)); return v; }
__device__ __forceinline__ uint32_t pack_bf16(float lo, float hi) { uint32_t r; asm("cvt.rn.bf16x2.f32 %0, %1, %2;" : "=r"(r) : "f"(hi), "f"(lo)); return r; }
__device__ __forceinline__ float bf_lo(uint32_t v) { return __uint_as_float(v << 16); }
__device__ __forceinline__ float bf_hi(uint32_t v) { return __uint_as_float(v & 0xFFFF0000u); }
__device__ __forceinline__ uint32_t bmul2(uint32_t a, uint32_t b) { uint32_t r; asm("mul.rn.bf16x2 %0, %1, %2;" : "=r"(r) : "r"(a), "r"(b)); return r; }
__device__ __forceinline__ uint32_t badd2(uint32_t a, uint32_t b) { uint32_t r; asm("add.rn.bf16x2 %0, %1, %2;" : "=r"(r) : "r"(a), "r"(b)); return r; }
__device__ __forceinline__ uint32_t bfma2(uint32_t a, uint32_t b, uint32_t c) { uint32_t r; asm("fma.rn.bf16x2 %0, %1, %2, %3;" : "=r"(r) : "r"(a), "r"(b), "r"(c)); return r; }
__device__ __forceinline__ uint32_t set_tag(uint32_t x, uint32_t mask, uint32_t e) { uint32_t r; asm("lop3.b32 %0, %1, %2, %3, 0xB8;" : "=r"(r) : "r"(x), "r"(mask), "r"(e)); return r; }
__device__ __forceinline__ uint32_t opaque(uint32_t x) { asm volatile("" : "+r"(x)); return x; }
__device__ __forceinline__ float rbf(float x) { return __bfloat162float(__float2bfloat16(x)); }
__device__ __forceinline__ float silu_f(float x) {
  float e, r;
  asm("ex2.approx.ftz.f32 %0, %1;" : "=f"(e) : "f"(x * -1.4426950408889634f));
  asm("rcp.approx.ftz.f32 %0, %1;" : "=f"(r) : "f"(1.f + e));
  return x * r;
}
__device__ __forceinline__ float silu2(float g, float a, float b) {
  float t;
  asm("tanh.approx.f32 %0, %1;" : "=f"(t) : "f"(g * a));
  return fmaf(g * b, t, g * b);
}
__device__ __forceinline__ void pin(int off, uint32_t x) { asm volatile("{.reg .pred p; setp.lt.s32 p, %0, 0; @p st.shared.b32 [%0], %1;}" ::"r"(off), "r"(x) : "memory"); }
__device__ __forceinline__ void pin4(int off, const uint32_t* x) { asm volatile("{.reg .pred p; setp.lt.s32 p, %0, 0; @p st.shared.v4.b32 [%0], {%1,%2,%3,%4};}" ::"r"(off), "r"(x[0]), "r"(x[1]), "r"(x[2]), "r"(x[3]) : "memory"); }
__device__ __forceinline__ void split(int x, int n) { asm volatile("{.reg .pred p; setp.eq.s32 p, %0, %1; @p trap;}" ::"r"(x), "r"(~n) : "memory"); }
__device__ __forceinline__ void ln_final(float s, float q, float& m, float& sd) {
  m = s * (1.f / D_);
  asm("sqrt.approx.f32 %0, %1;" : "=f"(sd) : "f"(rbf(rbf(fmaxf(fmaf(-m, m, q * (1.f / D_)), 0.f)) + 1e-5f)));
  sd = rbf(sd);
}
__device__ __forceinline__ float rcpf(float x) { float r; asm("rcp.approx.f32 %0, %1;" : "=f"(r) : "f"(x)); return r; }

__device__ __forceinline__ void wg_rs16_0(float* d, const uint32_t* a, uint64_t db, int sc) {
  asm volatile("{.reg .pred p; setp.ne.b32 p, %13, 0; wgmma.mma_async.sync.aligned.m64n16k16.f32.bf16.bf16 {%0,%1,%2,%3,%4,%5,%6,%7}, {%8,%9,%10,%11}, %12, p, 1, 1, 0;}"
    : "+f"(d[0]),"+f"(d[1]),"+f"(d[2]),"+f"(d[3]),"+f"(d[4]),"+f"(d[5]),"+f"(d[6]),"+f"(d[7]) : "r"(a[0]),"r"(a[1]),"r"(a[2]),"r"(a[3]),"l"(db),"r"(sc));
}
__device__ __forceinline__ void wg_rs32_0(float* d, const uint32_t* a, uint64_t db, int sc) {
  asm volatile("{.reg .pred p; setp.ne.b32 p, %21, 0; wgmma.mma_async.sync.aligned.m64n32k16.f32.bf16.bf16 {%0,%1,%2,%3,%4,%5,%6,%7,%8,%9,%10,%11,%12,%13,%14,%15}, {%16,%17,%18,%19}, %20, p, 1, 1, 0;}"
    : "+f"(d[0]),"+f"(d[1]),"+f"(d[2]),"+f"(d[3]),"+f"(d[4]),"+f"(d[5]),"+f"(d[6]),"+f"(d[7]),"+f"(d[8]),"+f"(d[9]),"+f"(d[10]),"+f"(d[11]),"+f"(d[12]),"+f"(d[13]),"+f"(d[14]),"+f"(d[15]) : "r"(a[0]),"r"(a[1]),"r"(a[2]),"r"(a[3]),"l"(db),"r"(sc));
}
__device__ __forceinline__ void wg_rs48_0(float* d, const uint32_t* a, uint64_t db, int sc) {
  asm volatile("{.reg .pred p; setp.ne.b32 p, %29, 0; wgmma.mma_async.sync.aligned.m64n48k16.f32.bf16.bf16 {%0,%1,%2,%3,%4,%5,%6,%7,%8,%9,%10,%11,%12,%13,%14,%15,%16,%17,%18,%19,%20,%21,%22,%23}, {%24,%25,%26,%27}, %28, p, 1, 1, 0;}"
    : "+f"(d[0]),"+f"(d[1]),"+f"(d[2]),"+f"(d[3]),"+f"(d[4]),"+f"(d[5]),"+f"(d[6]),"+f"(d[7]),"+f"(d[8]),"+f"(d[9]),"+f"(d[10]),"+f"(d[11]),"+f"(d[12]),"+f"(d[13]),"+f"(d[14]),"+f"(d[15]),"+f"(d[16]),"+f"(d[17]),"+f"(d[18]),"+f"(d[19]),"+f"(d[20]),"+f"(d[21]),"+f"(d[22]),"+f"(d[23]) : "r"(a[0]),"r"(a[1]),"r"(a[2]),"r"(a[3]),"l"(db),"r"(sc));
}
__device__ __forceinline__ void wg_rs64_0(float* d, const uint32_t* a, uint64_t db, int sc) {
  asm volatile("{.reg .pred p; setp.ne.b32 p, %37, 0; wgmma.mma_async.sync.aligned.m64n64k16.f32.bf16.bf16 {%0,%1,%2,%3,%4,%5,%6,%7,%8,%9,%10,%11,%12,%13,%14,%15,%16,%17,%18,%19,%20,%21,%22,%23,%24,%25,%26,%27,%28,%29,%30,%31}, {%32,%33,%34,%35}, %36, p, 1, 1, 0;}"
    : "+f"(d[0]),"+f"(d[1]),"+f"(d[2]),"+f"(d[3]),"+f"(d[4]),"+f"(d[5]),"+f"(d[6]),"+f"(d[7]),"+f"(d[8]),"+f"(d[9]),"+f"(d[10]),"+f"(d[11]),"+f"(d[12]),"+f"(d[13]),"+f"(d[14]),"+f"(d[15]),"+f"(d[16]),"+f"(d[17]),"+f"(d[18]),"+f"(d[19]),"+f"(d[20]),"+f"(d[21]),"+f"(d[22]),"+f"(d[23]),"+f"(d[24]),"+f"(d[25]),"+f"(d[26]),"+f"(d[27]),"+f"(d[28]),"+f"(d[29]),"+f"(d[30]),"+f"(d[31]) : "r"(a[0]),"r"(a[1]),"r"(a[2]),"r"(a[3]),"l"(db),"r"(sc));
}
__device__ __forceinline__ void wg_rs80_0(float* d, const uint32_t* a, uint64_t db, int sc) {
  asm volatile("{.reg .pred p; setp.ne.b32 p, %45, 0; wgmma.mma_async.sync.aligned.m64n80k16.f32.bf16.bf16 {%0,%1,%2,%3,%4,%5,%6,%7,%8,%9,%10,%11,%12,%13,%14,%15,%16,%17,%18,%19,%20,%21,%22,%23,%24,%25,%26,%27,%28,%29,%30,%31,%32,%33,%34,%35,%36,%37,%38,%39}, {%40,%41,%42,%43}, %44, p, 1, 1, 0;}"
    : "+f"(d[0]),"+f"(d[1]),"+f"(d[2]),"+f"(d[3]),"+f"(d[4]),"+f"(d[5]),"+f"(d[6]),"+f"(d[7]),"+f"(d[8]),"+f"(d[9]),"+f"(d[10]),"+f"(d[11]),"+f"(d[12]),"+f"(d[13]),"+f"(d[14]),"+f"(d[15]),"+f"(d[16]),"+f"(d[17]),"+f"(d[18]),"+f"(d[19]),"+f"(d[20]),"+f"(d[21]),"+f"(d[22]),"+f"(d[23]),"+f"(d[24]),"+f"(d[25]),"+f"(d[26]),"+f"(d[27]),"+f"(d[28]),"+f"(d[29]),"+f"(d[30]),"+f"(d[31]),"+f"(d[32]),"+f"(d[33]),"+f"(d[34]),"+f"(d[35]),"+f"(d[36]),"+f"(d[37]),"+f"(d[38]),"+f"(d[39]) : "r"(a[0]),"r"(a[1]),"r"(a[2]),"r"(a[3]),"l"(db),"r"(sc));
}
__device__ __forceinline__ void wg_rs96_0(float* d, const uint32_t* a, uint64_t db, int sc) {
  asm volatile("{.reg .pred p; setp.ne.b32 p, %53, 0; wgmma.mma_async.sync.aligned.m64n96k16.f32.bf16.bf16 {%0,%1,%2,%3,%4,%5,%6,%7,%8,%9,%10,%11,%12,%13,%14,%15,%16,%17,%18,%19,%20,%21,%22,%23,%24,%25,%26,%27,%28,%29,%30,%31,%32,%33,%34,%35,%36,%37,%38,%39,%40,%41,%42,%43,%44,%45,%46,%47}, {%48,%49,%50,%51}, %52, p, 1, 1, 0;}"
    : "+f"(d[0]),"+f"(d[1]),"+f"(d[2]),"+f"(d[3]),"+f"(d[4]),"+f"(d[5]),"+f"(d[6]),"+f"(d[7]),"+f"(d[8]),"+f"(d[9]),"+f"(d[10]),"+f"(d[11]),"+f"(d[12]),"+f"(d[13]),"+f"(d[14]),"+f"(d[15]),"+f"(d[16]),"+f"(d[17]),"+f"(d[18]),"+f"(d[19]),"+f"(d[20]),"+f"(d[21]),"+f"(d[22]),"+f"(d[23]),"+f"(d[24]),"+f"(d[25]),"+f"(d[26]),"+f"(d[27]),"+f"(d[28]),"+f"(d[29]),"+f"(d[30]),"+f"(d[31]),"+f"(d[32]),"+f"(d[33]),"+f"(d[34]),"+f"(d[35]),"+f"(d[36]),"+f"(d[37]),"+f"(d[38]),"+f"(d[39]),"+f"(d[40]),"+f"(d[41]),"+f"(d[42]),"+f"(d[43]),"+f"(d[44]),"+f"(d[45]),"+f"(d[46]),"+f"(d[47]) : "r"(a[0]),"r"(a[1]),"r"(a[2]),"r"(a[3]),"l"(db),"r"(sc));
}
__device__ __forceinline__ void wg_rs112_0(float* d, const uint32_t* a, uint64_t db, int sc) {
  asm volatile("{.reg .pred p; setp.ne.b32 p, %61, 0; wgmma.mma_async.sync.aligned.m64n112k16.f32.bf16.bf16 {%0,%1,%2,%3,%4,%5,%6,%7,%8,%9,%10,%11,%12,%13,%14,%15,%16,%17,%18,%19,%20,%21,%22,%23,%24,%25,%26,%27,%28,%29,%30,%31,%32,%33,%34,%35,%36,%37,%38,%39,%40,%41,%42,%43,%44,%45,%46,%47,%48,%49,%50,%51,%52,%53,%54,%55}, {%56,%57,%58,%59}, %60, p, 1, 1, 0;}"
    : "+f"(d[0]),"+f"(d[1]),"+f"(d[2]),"+f"(d[3]),"+f"(d[4]),"+f"(d[5]),"+f"(d[6]),"+f"(d[7]),"+f"(d[8]),"+f"(d[9]),"+f"(d[10]),"+f"(d[11]),"+f"(d[12]),"+f"(d[13]),"+f"(d[14]),"+f"(d[15]),"+f"(d[16]),"+f"(d[17]),"+f"(d[18]),"+f"(d[19]),"+f"(d[20]),"+f"(d[21]),"+f"(d[22]),"+f"(d[23]),"+f"(d[24]),"+f"(d[25]),"+f"(d[26]),"+f"(d[27]),"+f"(d[28]),"+f"(d[29]),"+f"(d[30]),"+f"(d[31]),"+f"(d[32]),"+f"(d[33]),"+f"(d[34]),"+f"(d[35]),"+f"(d[36]),"+f"(d[37]),"+f"(d[38]),"+f"(d[39]),"+f"(d[40]),"+f"(d[41]),"+f"(d[42]),"+f"(d[43]),"+f"(d[44]),"+f"(d[45]),"+f"(d[46]),"+f"(d[47]),"+f"(d[48]),"+f"(d[49]),"+f"(d[50]),"+f"(d[51]),"+f"(d[52]),"+f"(d[53]),"+f"(d[54]),"+f"(d[55]) : "r"(a[0]),"r"(a[1]),"r"(a[2]),"r"(a[3]),"l"(db),"r"(sc));
}
__device__ __forceinline__ void wg_rs128_0(float* d, const uint32_t* a, uint64_t db, int sc) {
  asm volatile("{.reg .pred p; setp.ne.b32 p, %69, 0; wgmma.mma_async.sync.aligned.m64n128k16.f32.bf16.bf16 {%0,%1,%2,%3,%4,%5,%6,%7,%8,%9,%10,%11,%12,%13,%14,%15,%16,%17,%18,%19,%20,%21,%22,%23,%24,%25,%26,%27,%28,%29,%30,%31,%32,%33,%34,%35,%36,%37,%38,%39,%40,%41,%42,%43,%44,%45,%46,%47,%48,%49,%50,%51,%52,%53,%54,%55,%56,%57,%58,%59,%60,%61,%62,%63}, {%64,%65,%66,%67}, %68, p, 1, 1, 0;}"
    : "+f"(d[0]),"+f"(d[1]),"+f"(d[2]),"+f"(d[3]),"+f"(d[4]),"+f"(d[5]),"+f"(d[6]),"+f"(d[7]),"+f"(d[8]),"+f"(d[9]),"+f"(d[10]),"+f"(d[11]),"+f"(d[12]),"+f"(d[13]),"+f"(d[14]),"+f"(d[15]),"+f"(d[16]),"+f"(d[17]),"+f"(d[18]),"+f"(d[19]),"+f"(d[20]),"+f"(d[21]),"+f"(d[22]),"+f"(d[23]),"+f"(d[24]),"+f"(d[25]),"+f"(d[26]),"+f"(d[27]),"+f"(d[28]),"+f"(d[29]),"+f"(d[30]),"+f"(d[31]),"+f"(d[32]),"+f"(d[33]),"+f"(d[34]),"+f"(d[35]),"+f"(d[36]),"+f"(d[37]),"+f"(d[38]),"+f"(d[39]),"+f"(d[40]),"+f"(d[41]),"+f"(d[42]),"+f"(d[43]),"+f"(d[44]),"+f"(d[45]),"+f"(d[46]),"+f"(d[47]),"+f"(d[48]),"+f"(d[49]),"+f"(d[50]),"+f"(d[51]),"+f"(d[52]),"+f"(d[53]),"+f"(d[54]),"+f"(d[55]),"+f"(d[56]),"+f"(d[57]),"+f"(d[58]),"+f"(d[59]),"+f"(d[60]),"+f"(d[61]),"+f"(d[62]),"+f"(d[63]) : "r"(a[0]),"r"(a[1]),"r"(a[2]),"r"(a[3]),"l"(db),"r"(sc));
}
__device__ __forceinline__ void wg_rs144_0(float* d, const uint32_t* a, uint64_t db, int sc) {
  asm volatile("{.reg .pred p; setp.ne.b32 p, %77, 0; wgmma.mma_async.sync.aligned.m64n144k16.f32.bf16.bf16 {%0,%1,%2,%3,%4,%5,%6,%7,%8,%9,%10,%11,%12,%13,%14,%15,%16,%17,%18,%19,%20,%21,%22,%23,%24,%25,%26,%27,%28,%29,%30,%31,%32,%33,%34,%35,%36,%37,%38,%39,%40,%41,%42,%43,%44,%45,%46,%47,%48,%49,%50,%51,%52,%53,%54,%55,%56,%57,%58,%59,%60,%61,%62,%63,%64,%65,%66,%67,%68,%69,%70,%71}, {%72,%73,%74,%75}, %76, p, 1, 1, 0;}"
    : "+f"(d[0]),"+f"(d[1]),"+f"(d[2]),"+f"(d[3]),"+f"(d[4]),"+f"(d[5]),"+f"(d[6]),"+f"(d[7]),"+f"(d[8]),"+f"(d[9]),"+f"(d[10]),"+f"(d[11]),"+f"(d[12]),"+f"(d[13]),"+f"(d[14]),"+f"(d[15]),"+f"(d[16]),"+f"(d[17]),"+f"(d[18]),"+f"(d[19]),"+f"(d[20]),"+f"(d[21]),"+f"(d[22]),"+f"(d[23]),"+f"(d[24]),"+f"(d[25]),"+f"(d[26]),"+f"(d[27]),"+f"(d[28]),"+f"(d[29]),"+f"(d[30]),"+f"(d[31]),"+f"(d[32]),"+f"(d[33]),"+f"(d[34]),"+f"(d[35]),"+f"(d[36]),"+f"(d[37]),"+f"(d[38]),"+f"(d[39]),"+f"(d[40]),"+f"(d[41]),"+f"(d[42]),"+f"(d[43]),"+f"(d[44]),"+f"(d[45]),"+f"(d[46]),"+f"(d[47]),"+f"(d[48]),"+f"(d[49]),"+f"(d[50]),"+f"(d[51]),"+f"(d[52]),"+f"(d[53]),"+f"(d[54]),"+f"(d[55]),"+f"(d[56]),"+f"(d[57]),"+f"(d[58]),"+f"(d[59]),"+f"(d[60]),"+f"(d[61]),"+f"(d[62]),"+f"(d[63]),"+f"(d[64]),"+f"(d[65]),"+f"(d[66]),"+f"(d[67]),"+f"(d[68]),"+f"(d[69]),"+f"(d[70]),"+f"(d[71]) : "r"(a[0]),"r"(a[1]),"r"(a[2]),"r"(a[3]),"l"(db),"r"(sc));
}
__device__ __forceinline__ void wg_rs160_0(float* d, const uint32_t* a, uint64_t db, int sc) {
  asm volatile("{.reg .pred p; setp.ne.b32 p, %85, 0; wgmma.mma_async.sync.aligned.m64n160k16.f32.bf16.bf16 {%0,%1,%2,%3,%4,%5,%6,%7,%8,%9,%10,%11,%12,%13,%14,%15,%16,%17,%18,%19,%20,%21,%22,%23,%24,%25,%26,%27,%28,%29,%30,%31,%32,%33,%34,%35,%36,%37,%38,%39,%40,%41,%42,%43,%44,%45,%46,%47,%48,%49,%50,%51,%52,%53,%54,%55,%56,%57,%58,%59,%60,%61,%62,%63,%64,%65,%66,%67,%68,%69,%70,%71,%72,%73,%74,%75,%76,%77,%78,%79}, {%80,%81,%82,%83}, %84, p, 1, 1, 0;}"
    : "+f"(d[0]),"+f"(d[1]),"+f"(d[2]),"+f"(d[3]),"+f"(d[4]),"+f"(d[5]),"+f"(d[6]),"+f"(d[7]),"+f"(d[8]),"+f"(d[9]),"+f"(d[10]),"+f"(d[11]),"+f"(d[12]),"+f"(d[13]),"+f"(d[14]),"+f"(d[15]),"+f"(d[16]),"+f"(d[17]),"+f"(d[18]),"+f"(d[19]),"+f"(d[20]),"+f"(d[21]),"+f"(d[22]),"+f"(d[23]),"+f"(d[24]),"+f"(d[25]),"+f"(d[26]),"+f"(d[27]),"+f"(d[28]),"+f"(d[29]),"+f"(d[30]),"+f"(d[31]),"+f"(d[32]),"+f"(d[33]),"+f"(d[34]),"+f"(d[35]),"+f"(d[36]),"+f"(d[37]),"+f"(d[38]),"+f"(d[39]),"+f"(d[40]),"+f"(d[41]),"+f"(d[42]),"+f"(d[43]),"+f"(d[44]),"+f"(d[45]),"+f"(d[46]),"+f"(d[47]),"+f"(d[48]),"+f"(d[49]),"+f"(d[50]),"+f"(d[51]),"+f"(d[52]),"+f"(d[53]),"+f"(d[54]),"+f"(d[55]),"+f"(d[56]),"+f"(d[57]),"+f"(d[58]),"+f"(d[59]),"+f"(d[60]),"+f"(d[61]),"+f"(d[62]),"+f"(d[63]),"+f"(d[64]),"+f"(d[65]),"+f"(d[66]),"+f"(d[67]),"+f"(d[68]),"+f"(d[69]),"+f"(d[70]),"+f"(d[71]),"+f"(d[72]),"+f"(d[73]),"+f"(d[74]),"+f"(d[75]),"+f"(d[76]),"+f"(d[77]),"+f"(d[78]),"+f"(d[79]) : "r"(a[0]),"r"(a[1]),"r"(a[2]),"r"(a[3]),"l"(db),"r"(sc));
}
__device__ __forceinline__ void wg_rs176_0(float* d, const uint32_t* a, uint64_t db, int sc) {
  asm volatile("{.reg .pred p; setp.ne.b32 p, %93, 0; wgmma.mma_async.sync.aligned.m64n176k16.f32.bf16.bf16 {%0,%1,%2,%3,%4,%5,%6,%7,%8,%9,%10,%11,%12,%13,%14,%15,%16,%17,%18,%19,%20,%21,%22,%23,%24,%25,%26,%27,%28,%29,%30,%31,%32,%33,%34,%35,%36,%37,%38,%39,%40,%41,%42,%43,%44,%45,%46,%47,%48,%49,%50,%51,%52,%53,%54,%55,%56,%57,%58,%59,%60,%61,%62,%63,%64,%65,%66,%67,%68,%69,%70,%71,%72,%73,%74,%75,%76,%77,%78,%79,%80,%81,%82,%83,%84,%85,%86,%87}, {%88,%89,%90,%91}, %92, p, 1, 1, 0;}"
    : "+f"(d[0]),"+f"(d[1]),"+f"(d[2]),"+f"(d[3]),"+f"(d[4]),"+f"(d[5]),"+f"(d[6]),"+f"(d[7]),"+f"(d[8]),"+f"(d[9]),"+f"(d[10]),"+f"(d[11]),"+f"(d[12]),"+f"(d[13]),"+f"(d[14]),"+f"(d[15]),"+f"(d[16]),"+f"(d[17]),"+f"(d[18]),"+f"(d[19]),"+f"(d[20]),"+f"(d[21]),"+f"(d[22]),"+f"(d[23]),"+f"(d[24]),"+f"(d[25]),"+f"(d[26]),"+f"(d[27]),"+f"(d[28]),"+f"(d[29]),"+f"(d[30]),"+f"(d[31]),"+f"(d[32]),"+f"(d[33]),"+f"(d[34]),"+f"(d[35]),"+f"(d[36]),"+f"(d[37]),"+f"(d[38]),"+f"(d[39]),"+f"(d[40]),"+f"(d[41]),"+f"(d[42]),"+f"(d[43]),"+f"(d[44]),"+f"(d[45]),"+f"(d[46]),"+f"(d[47]),"+f"(d[48]),"+f"(d[49]),"+f"(d[50]),"+f"(d[51]),"+f"(d[52]),"+f"(d[53]),"+f"(d[54]),"+f"(d[55]),"+f"(d[56]),"+f"(d[57]),"+f"(d[58]),"+f"(d[59]),"+f"(d[60]),"+f"(d[61]),"+f"(d[62]),"+f"(d[63]),"+f"(d[64]),"+f"(d[65]),"+f"(d[66]),"+f"(d[67]),"+f"(d[68]),"+f"(d[69]),"+f"(d[70]),"+f"(d[71]),"+f"(d[72]),"+f"(d[73]),"+f"(d[74]),"+f"(d[75]),"+f"(d[76]),"+f"(d[77]),"+f"(d[78]),"+f"(d[79]),"+f"(d[80]),"+f"(d[81]),"+f"(d[82]),"+f"(d[83]),"+f"(d[84]),"+f"(d[85]),"+f"(d[86]),"+f"(d[87]) : "r"(a[0]),"r"(a[1]),"r"(a[2]),"r"(a[3]),"l"(db),"r"(sc));
}
__device__ __forceinline__ void wg_rs192_0(float* d, const uint32_t* a, uint64_t db, int sc) {
  asm volatile("{.reg .pred p; setp.ne.b32 p, %101, 0; wgmma.mma_async.sync.aligned.m64n192k16.f32.bf16.bf16 {%0,%1,%2,%3,%4,%5,%6,%7,%8,%9,%10,%11,%12,%13,%14,%15,%16,%17,%18,%19,%20,%21,%22,%23,%24,%25,%26,%27,%28,%29,%30,%31,%32,%33,%34,%35,%36,%37,%38,%39,%40,%41,%42,%43,%44,%45,%46,%47,%48,%49,%50,%51,%52,%53,%54,%55,%56,%57,%58,%59,%60,%61,%62,%63,%64,%65,%66,%67,%68,%69,%70,%71,%72,%73,%74,%75,%76,%77,%78,%79,%80,%81,%82,%83,%84,%85,%86,%87,%88,%89,%90,%91,%92,%93,%94,%95}, {%96,%97,%98,%99}, %100, p, 1, 1, 0;}"
    : "+f"(d[0]),"+f"(d[1]),"+f"(d[2]),"+f"(d[3]),"+f"(d[4]),"+f"(d[5]),"+f"(d[6]),"+f"(d[7]),"+f"(d[8]),"+f"(d[9]),"+f"(d[10]),"+f"(d[11]),"+f"(d[12]),"+f"(d[13]),"+f"(d[14]),"+f"(d[15]),"+f"(d[16]),"+f"(d[17]),"+f"(d[18]),"+f"(d[19]),"+f"(d[20]),"+f"(d[21]),"+f"(d[22]),"+f"(d[23]),"+f"(d[24]),"+f"(d[25]),"+f"(d[26]),"+f"(d[27]),"+f"(d[28]),"+f"(d[29]),"+f"(d[30]),"+f"(d[31]),"+f"(d[32]),"+f"(d[33]),"+f"(d[34]),"+f"(d[35]),"+f"(d[36]),"+f"(d[37]),"+f"(d[38]),"+f"(d[39]),"+f"(d[40]),"+f"(d[41]),"+f"(d[42]),"+f"(d[43]),"+f"(d[44]),"+f"(d[45]),"+f"(d[46]),"+f"(d[47]),"+f"(d[48]),"+f"(d[49]),"+f"(d[50]),"+f"(d[51]),"+f"(d[52]),"+f"(d[53]),"+f"(d[54]),"+f"(d[55]),"+f"(d[56]),"+f"(d[57]),"+f"(d[58]),"+f"(d[59]),"+f"(d[60]),"+f"(d[61]),"+f"(d[62]),"+f"(d[63]),"+f"(d[64]),"+f"(d[65]),"+f"(d[66]),"+f"(d[67]),"+f"(d[68]),"+f"(d[69]),"+f"(d[70]),"+f"(d[71]),"+f"(d[72]),"+f"(d[73]),"+f"(d[74]),"+f"(d[75]),"+f"(d[76]),"+f"(d[77]),"+f"(d[78]),"+f"(d[79]),"+f"(d[80]),"+f"(d[81]),"+f"(d[82]),"+f"(d[83]),"+f"(d[84]),"+f"(d[85]),"+f"(d[86]),"+f"(d[87]),"+f"(d[88]),"+f"(d[89]),"+f"(d[90]),"+f"(d[91]),"+f"(d[92]),"+f"(d[93]),"+f"(d[94]),"+f"(d[95]) : "r"(a[0]),"r"(a[1]),"r"(a[2]),"r"(a[3]),"l"(db),"r"(sc));
}
__device__ __forceinline__ void wg_ss192_11(float* d, uint64_t da, uint64_t db, int sc) {
  asm volatile("{.reg .pred p; setp.ne.b32 p, %98, 0; wgmma.mma_async.sync.aligned.m64n192k16.f32.bf16.bf16 {%0,%1,%2,%3,%4,%5,%6,%7,%8,%9,%10,%11,%12,%13,%14,%15,%16,%17,%18,%19,%20,%21,%22,%23,%24,%25,%26,%27,%28,%29,%30,%31,%32,%33,%34,%35,%36,%37,%38,%39,%40,%41,%42,%43,%44,%45,%46,%47,%48,%49,%50,%51,%52,%53,%54,%55,%56,%57,%58,%59,%60,%61,%62,%63,%64,%65,%66,%67,%68,%69,%70,%71,%72,%73,%74,%75,%76,%77,%78,%79,%80,%81,%82,%83,%84,%85,%86,%87,%88,%89,%90,%91,%92,%93,%94,%95}, %96, %97, p, 1, 1, 1, 1;}"
    : "+f"(d[0]),"+f"(d[1]),"+f"(d[2]),"+f"(d[3]),"+f"(d[4]),"+f"(d[5]),"+f"(d[6]),"+f"(d[7]),"+f"(d[8]),"+f"(d[9]),"+f"(d[10]),"+f"(d[11]),"+f"(d[12]),"+f"(d[13]),"+f"(d[14]),"+f"(d[15]),"+f"(d[16]),"+f"(d[17]),"+f"(d[18]),"+f"(d[19]),"+f"(d[20]),"+f"(d[21]),"+f"(d[22]),"+f"(d[23]),"+f"(d[24]),"+f"(d[25]),"+f"(d[26]),"+f"(d[27]),"+f"(d[28]),"+f"(d[29]),"+f"(d[30]),"+f"(d[31]),"+f"(d[32]),"+f"(d[33]),"+f"(d[34]),"+f"(d[35]),"+f"(d[36]),"+f"(d[37]),"+f"(d[38]),"+f"(d[39]),"+f"(d[40]),"+f"(d[41]),"+f"(d[42]),"+f"(d[43]),"+f"(d[44]),"+f"(d[45]),"+f"(d[46]),"+f"(d[47]),"+f"(d[48]),"+f"(d[49]),"+f"(d[50]),"+f"(d[51]),"+f"(d[52]),"+f"(d[53]),"+f"(d[54]),"+f"(d[55]),"+f"(d[56]),"+f"(d[57]),"+f"(d[58]),"+f"(d[59]),"+f"(d[60]),"+f"(d[61]),"+f"(d[62]),"+f"(d[63]),"+f"(d[64]),"+f"(d[65]),"+f"(d[66]),"+f"(d[67]),"+f"(d[68]),"+f"(d[69]),"+f"(d[70]),"+f"(d[71]),"+f"(d[72]),"+f"(d[73]),"+f"(d[74]),"+f"(d[75]),"+f"(d[76]),"+f"(d[77]),"+f"(d[78]),"+f"(d[79]),"+f"(d[80]),"+f"(d[81]),"+f"(d[82]),"+f"(d[83]),"+f"(d[84]),"+f"(d[85]),"+f"(d[86]),"+f"(d[87]),"+f"(d[88]),"+f"(d[89]),"+f"(d[90]),"+f"(d[91]),"+f"(d[92]),"+f"(d[93]),"+f"(d[94]),"+f"(d[95]) : "l"(da),"l"(db),"r"(sc));
}
__device__ __forceinline__ void wg_ss192_01(float* d, uint64_t da, uint64_t db, int sc) {
  asm volatile("{.reg .pred p; setp.ne.b32 p, %98, 0; wgmma.mma_async.sync.aligned.m64n192k16.f32.bf16.bf16 {%0,%1,%2,%3,%4,%5,%6,%7,%8,%9,%10,%11,%12,%13,%14,%15,%16,%17,%18,%19,%20,%21,%22,%23,%24,%25,%26,%27,%28,%29,%30,%31,%32,%33,%34,%35,%36,%37,%38,%39,%40,%41,%42,%43,%44,%45,%46,%47,%48,%49,%50,%51,%52,%53,%54,%55,%56,%57,%58,%59,%60,%61,%62,%63,%64,%65,%66,%67,%68,%69,%70,%71,%72,%73,%74,%75,%76,%77,%78,%79,%80,%81,%82,%83,%84,%85,%86,%87,%88,%89,%90,%91,%92,%93,%94,%95}, %96, %97, p, 1, 1, 0, 1;}"
    : "+f"(d[0]),"+f"(d[1]),"+f"(d[2]),"+f"(d[3]),"+f"(d[4]),"+f"(d[5]),"+f"(d[6]),"+f"(d[7]),"+f"(d[8]),"+f"(d[9]),"+f"(d[10]),"+f"(d[11]),"+f"(d[12]),"+f"(d[13]),"+f"(d[14]),"+f"(d[15]),"+f"(d[16]),"+f"(d[17]),"+f"(d[18]),"+f"(d[19]),"+f"(d[20]),"+f"(d[21]),"+f"(d[22]),"+f"(d[23]),"+f"(d[24]),"+f"(d[25]),"+f"(d[26]),"+f"(d[27]),"+f"(d[28]),"+f"(d[29]),"+f"(d[30]),"+f"(d[31]),"+f"(d[32]),"+f"(d[33]),"+f"(d[34]),"+f"(d[35]),"+f"(d[36]),"+f"(d[37]),"+f"(d[38]),"+f"(d[39]),"+f"(d[40]),"+f"(d[41]),"+f"(d[42]),"+f"(d[43]),"+f"(d[44]),"+f"(d[45]),"+f"(d[46]),"+f"(d[47]),"+f"(d[48]),"+f"(d[49]),"+f"(d[50]),"+f"(d[51]),"+f"(d[52]),"+f"(d[53]),"+f"(d[54]),"+f"(d[55]),"+f"(d[56]),"+f"(d[57]),"+f"(d[58]),"+f"(d[59]),"+f"(d[60]),"+f"(d[61]),"+f"(d[62]),"+f"(d[63]),"+f"(d[64]),"+f"(d[65]),"+f"(d[66]),"+f"(d[67]),"+f"(d[68]),"+f"(d[69]),"+f"(d[70]),"+f"(d[71]),"+f"(d[72]),"+f"(d[73]),"+f"(d[74]),"+f"(d[75]),"+f"(d[76]),"+f"(d[77]),"+f"(d[78]),"+f"(d[79]),"+f"(d[80]),"+f"(d[81]),"+f"(d[82]),"+f"(d[83]),"+f"(d[84]),"+f"(d[85]),"+f"(d[86]),"+f"(d[87]),"+f"(d[88]),"+f"(d[89]),"+f"(d[90]),"+f"(d[91]),"+f"(d[92]),"+f"(d[93]),"+f"(d[94]),"+f"(d[95]) : "l"(da),"l"(db),"r"(sc));
}
__device__ __forceinline__ void wg_ss64_11(float* d, uint64_t da, uint64_t db, int sc) {
  asm volatile("{.reg .pred p; setp.ne.b32 p, %34, 0; wgmma.mma_async.sync.aligned.m64n64k16.f32.bf16.bf16 {%0,%1,%2,%3,%4,%5,%6,%7,%8,%9,%10,%11,%12,%13,%14,%15,%16,%17,%18,%19,%20,%21,%22,%23,%24,%25,%26,%27,%28,%29,%30,%31}, %32, %33, p, 1, 1, 1, 1;}"
    : "+f"(d[0]),"+f"(d[1]),"+f"(d[2]),"+f"(d[3]),"+f"(d[4]),"+f"(d[5]),"+f"(d[6]),"+f"(d[7]),"+f"(d[8]),"+f"(d[9]),"+f"(d[10]),"+f"(d[11]),"+f"(d[12]),"+f"(d[13]),"+f"(d[14]),"+f"(d[15]),"+f"(d[16]),"+f"(d[17]),"+f"(d[18]),"+f"(d[19]),"+f"(d[20]),"+f"(d[21]),"+f"(d[22]),"+f"(d[23]),"+f"(d[24]),"+f"(d[25]),"+f"(d[26]),"+f"(d[27]),"+f"(d[28]),"+f"(d[29]),"+f"(d[30]),"+f"(d[31]) : "l"(da),"l"(db),"r"(sc));
}
__device__ __forceinline__ void wg_ss64_01(float* d, uint64_t da, uint64_t db, int sc) {
  asm volatile("{.reg .pred p; setp.ne.b32 p, %34, 0; wgmma.mma_async.sync.aligned.m64n64k16.f32.bf16.bf16 {%0,%1,%2,%3,%4,%5,%6,%7,%8,%9,%10,%11,%12,%13,%14,%15,%16,%17,%18,%19,%20,%21,%22,%23,%24,%25,%26,%27,%28,%29,%30,%31}, %32, %33, p, 1, 1, 0, 1;}"
    : "+f"(d[0]),"+f"(d[1]),"+f"(d[2]),"+f"(d[3]),"+f"(d[4]),"+f"(d[5]),"+f"(d[6]),"+f"(d[7]),"+f"(d[8]),"+f"(d[9]),"+f"(d[10]),"+f"(d[11]),"+f"(d[12]),"+f"(d[13]),"+f"(d[14]),"+f"(d[15]),"+f"(d[16]),"+f"(d[17]),"+f"(d[18]),"+f"(d[19]),"+f"(d[20]),"+f"(d[21]),"+f"(d[22]),"+f"(d[23]),"+f"(d[24]),"+f"(d[25]),"+f"(d[26]),"+f"(d[27]),"+f"(d[28]),"+f"(d[29]),"+f"(d[30]),"+f"(d[31]) : "l"(da),"l"(db),"r"(sc));
}
__device__ __forceinline__ void wg_ss128_11(float* d, uint64_t da, uint64_t db, int sc) {
  asm volatile("{.reg .pred p; setp.ne.b32 p, %66, 0; wgmma.mma_async.sync.aligned.m64n128k16.f32.bf16.bf16 {%0,%1,%2,%3,%4,%5,%6,%7,%8,%9,%10,%11,%12,%13,%14,%15,%16,%17,%18,%19,%20,%21,%22,%23,%24,%25,%26,%27,%28,%29,%30,%31,%32,%33,%34,%35,%36,%37,%38,%39,%40,%41,%42,%43,%44,%45,%46,%47,%48,%49,%50,%51,%52,%53,%54,%55,%56,%57,%58,%59,%60,%61,%62,%63}, %64, %65, p, 1, 1, 1, 1;}"
    : "+f"(d[0]),"+f"(d[1]),"+f"(d[2]),"+f"(d[3]),"+f"(d[4]),"+f"(d[5]),"+f"(d[6]),"+f"(d[7]),"+f"(d[8]),"+f"(d[9]),"+f"(d[10]),"+f"(d[11]),"+f"(d[12]),"+f"(d[13]),"+f"(d[14]),"+f"(d[15]),"+f"(d[16]),"+f"(d[17]),"+f"(d[18]),"+f"(d[19]),"+f"(d[20]),"+f"(d[21]),"+f"(d[22]),"+f"(d[23]),"+f"(d[24]),"+f"(d[25]),"+f"(d[26]),"+f"(d[27]),"+f"(d[28]),"+f"(d[29]),"+f"(d[30]),"+f"(d[31]),"+f"(d[32]),"+f"(d[33]),"+f"(d[34]),"+f"(d[35]),"+f"(d[36]),"+f"(d[37]),"+f"(d[38]),"+f"(d[39]),"+f"(d[40]),"+f"(d[41]),"+f"(d[42]),"+f"(d[43]),"+f"(d[44]),"+f"(d[45]),"+f"(d[46]),"+f"(d[47]),"+f"(d[48]),"+f"(d[49]),"+f"(d[50]),"+f"(d[51]),"+f"(d[52]),"+f"(d[53]),"+f"(d[54]),"+f"(d[55]),"+f"(d[56]),"+f"(d[57]),"+f"(d[58]),"+f"(d[59]),"+f"(d[60]),"+f"(d[61]),"+f"(d[62]),"+f"(d[63]) : "l"(da),"l"(db),"r"(sc));
}
__device__ __forceinline__ void wg_ss128_01(float* d, uint64_t da, uint64_t db, int sc) {
  asm volatile("{.reg .pred p; setp.ne.b32 p, %66, 0; wgmma.mma_async.sync.aligned.m64n128k16.f32.bf16.bf16 {%0,%1,%2,%3,%4,%5,%6,%7,%8,%9,%10,%11,%12,%13,%14,%15,%16,%17,%18,%19,%20,%21,%22,%23,%24,%25,%26,%27,%28,%29,%30,%31,%32,%33,%34,%35,%36,%37,%38,%39,%40,%41,%42,%43,%44,%45,%46,%47,%48,%49,%50,%51,%52,%53,%54,%55,%56,%57,%58,%59,%60,%61,%62,%63}, %64, %65, p, 1, 1, 0, 1;}"
    : "+f"(d[0]),"+f"(d[1]),"+f"(d[2]),"+f"(d[3]),"+f"(d[4]),"+f"(d[5]),"+f"(d[6]),"+f"(d[7]),"+f"(d[8]),"+f"(d[9]),"+f"(d[10]),"+f"(d[11]),"+f"(d[12]),"+f"(d[13]),"+f"(d[14]),"+f"(d[15]),"+f"(d[16]),"+f"(d[17]),"+f"(d[18]),"+f"(d[19]),"+f"(d[20]),"+f"(d[21]),"+f"(d[22]),"+f"(d[23]),"+f"(d[24]),"+f"(d[25]),"+f"(d[26]),"+f"(d[27]),"+f"(d[28]),"+f"(d[29]),"+f"(d[30]),"+f"(d[31]),"+f"(d[32]),"+f"(d[33]),"+f"(d[34]),"+f"(d[35]),"+f"(d[36]),"+f"(d[37]),"+f"(d[38]),"+f"(d[39]),"+f"(d[40]),"+f"(d[41]),"+f"(d[42]),"+f"(d[43]),"+f"(d[44]),"+f"(d[45]),"+f"(d[46]),"+f"(d[47]),"+f"(d[48]),"+f"(d[49]),"+f"(d[50]),"+f"(d[51]),"+f"(d[52]),"+f"(d[53]),"+f"(d[54]),"+f"(d[55]),"+f"(d[56]),"+f"(d[57]),"+f"(d[58]),"+f"(d[59]),"+f"(d[60]),"+f"(d[61]),"+f"(d[62]),"+f"(d[63]) : "l"(da),"l"(db),"r"(sc));
}
__device__ __forceinline__ void wg_ss96_01(float* d, uint64_t da, uint64_t db, int sc) {
  asm volatile("{.reg .pred p; setp.ne.b32 p, %50, 0; wgmma.mma_async.sync.aligned.m64n96k16.f32.bf16.bf16 {%0,%1,%2,%3,%4,%5,%6,%7,%8,%9,%10,%11,%12,%13,%14,%15,%16,%17,%18,%19,%20,%21,%22,%23,%24,%25,%26,%27,%28,%29,%30,%31,%32,%33,%34,%35,%36,%37,%38,%39,%40,%41,%42,%43,%44,%45,%46,%47}, %48, %49, p, 1, 1, 0, 1;}"
    : "+f"(d[0]),"+f"(d[1]),"+f"(d[2]),"+f"(d[3]),"+f"(d[4]),"+f"(d[5]),"+f"(d[6]),"+f"(d[7]),"+f"(d[8]),"+f"(d[9]),"+f"(d[10]),"+f"(d[11]),"+f"(d[12]),"+f"(d[13]),"+f"(d[14]),"+f"(d[15]),"+f"(d[16]),"+f"(d[17]),"+f"(d[18]),"+f"(d[19]),"+f"(d[20]),"+f"(d[21]),"+f"(d[22]),"+f"(d[23]),"+f"(d[24]),"+f"(d[25]),"+f"(d[26]),"+f"(d[27]),"+f"(d[28]),"+f"(d[29]),"+f"(d[30]),"+f"(d[31]),"+f"(d[32]),"+f"(d[33]),"+f"(d[34]),"+f"(d[35]),"+f"(d[36]),"+f"(d[37]),"+f"(d[38]),"+f"(d[39]),"+f"(d[40]),"+f"(d[41]),"+f"(d[42]),"+f"(d[43]),"+f"(d[44]),"+f"(d[45]),"+f"(d[46]),"+f"(d[47]) : "l"(da),"l"(db),"r"(sc));
}
__device__ __forceinline__ void wg_rs64_1(float* d, const uint32_t* a, uint64_t db, int sc) {
  asm volatile("{.reg .pred p; setp.ne.b32 p, %37, 0; wgmma.mma_async.sync.aligned.m64n64k16.f32.bf16.bf16 {%0,%1,%2,%3,%4,%5,%6,%7,%8,%9,%10,%11,%12,%13,%14,%15,%16,%17,%18,%19,%20,%21,%22,%23,%24,%25,%26,%27,%28,%29,%30,%31}, {%32,%33,%34,%35}, %36, p, 1, 1, 1;}"
    : "+f"(d[0]),"+f"(d[1]),"+f"(d[2]),"+f"(d[3]),"+f"(d[4]),"+f"(d[5]),"+f"(d[6]),"+f"(d[7]),"+f"(d[8]),"+f"(d[9]),"+f"(d[10]),"+f"(d[11]),"+f"(d[12]),"+f"(d[13]),"+f"(d[14]),"+f"(d[15]),"+f"(d[16]),"+f"(d[17]),"+f"(d[18]),"+f"(d[19]),"+f"(d[20]),"+f"(d[21]),"+f"(d[22]),"+f"(d[23]),"+f"(d[24]),"+f"(d[25]),"+f"(d[26]),"+f"(d[27]),"+f"(d[28]),"+f"(d[29]),"+f"(d[30]),"+f"(d[31]) : "r"(a[0]),"r"(a[1]),"r"(a[2]),"r"(a[3]),"l"(db),"r"(sc));
}
__device__ __forceinline__ void wg_rs96_1(float* d, const uint32_t* a, uint64_t db, int sc) {
  asm volatile("{.reg .pred p; setp.ne.b32 p, %53, 0; wgmma.mma_async.sync.aligned.m64n96k16.f32.bf16.bf16 {%0,%1,%2,%3,%4,%5,%6,%7,%8,%9,%10,%11,%12,%13,%14,%15,%16,%17,%18,%19,%20,%21,%22,%23,%24,%25,%26,%27,%28,%29,%30,%31,%32,%33,%34,%35,%36,%37,%38,%39,%40,%41,%42,%43,%44,%45,%46,%47}, {%48,%49,%50,%51}, %52, p, 1, 1, 1;}"
    : "+f"(d[0]),"+f"(d[1]),"+f"(d[2]),"+f"(d[3]),"+f"(d[4]),"+f"(d[5]),"+f"(d[6]),"+f"(d[7]),"+f"(d[8]),"+f"(d[9]),"+f"(d[10]),"+f"(d[11]),"+f"(d[12]),"+f"(d[13]),"+f"(d[14]),"+f"(d[15]),"+f"(d[16]),"+f"(d[17]),"+f"(d[18]),"+f"(d[19]),"+f"(d[20]),"+f"(d[21]),"+f"(d[22]),"+f"(d[23]),"+f"(d[24]),"+f"(d[25]),"+f"(d[26]),"+f"(d[27]),"+f"(d[28]),"+f"(d[29]),"+f"(d[30]),"+f"(d[31]),"+f"(d[32]),"+f"(d[33]),"+f"(d[34]),"+f"(d[35]),"+f"(d[36]),"+f"(d[37]),"+f"(d[38]),"+f"(d[39]),"+f"(d[40]),"+f"(d[41]),"+f"(d[42]),"+f"(d[43]),"+f"(d[44]),"+f"(d[45]),"+f"(d[46]),"+f"(d[47]) : "r"(a[0]),"r"(a[1]),"r"(a[2]),"r"(a[3]),"l"(db),"r"(sc));
}
__device__ __forceinline__ void wg_ss160_01(float* d, uint64_t da, uint64_t db, int sc) {
  asm volatile("{.reg .pred p; setp.ne.b32 p, %82, 0; wgmma.mma_async.sync.aligned.m64n160k16.f32.bf16.bf16 {%0,%1,%2,%3,%4,%5,%6,%7,%8,%9,%10,%11,%12,%13,%14,%15,%16,%17,%18,%19,%20,%21,%22,%23,%24,%25,%26,%27,%28,%29,%30,%31,%32,%33,%34,%35,%36,%37,%38,%39,%40,%41,%42,%43,%44,%45,%46,%47,%48,%49,%50,%51,%52,%53,%54,%55,%56,%57,%58,%59,%60,%61,%62,%63,%64,%65,%66,%67,%68,%69,%70,%71,%72,%73,%74,%75,%76,%77,%78,%79}, %80, %81, p, 1, 1, 0, 1;}"
    : "+f"(d[0]),"+f"(d[1]),"+f"(d[2]),"+f"(d[3]),"+f"(d[4]),"+f"(d[5]),"+f"(d[6]),"+f"(d[7]),"+f"(d[8]),"+f"(d[9]),"+f"(d[10]),"+f"(d[11]),"+f"(d[12]),"+f"(d[13]),"+f"(d[14]),"+f"(d[15]),"+f"(d[16]),"+f"(d[17]),"+f"(d[18]),"+f"(d[19]),"+f"(d[20]),"+f"(d[21]),"+f"(d[22]),"+f"(d[23]),"+f"(d[24]),"+f"(d[25]),"+f"(d[26]),"+f"(d[27]),"+f"(d[28]),"+f"(d[29]),"+f"(d[30]),"+f"(d[31]),"+f"(d[32]),"+f"(d[33]),"+f"(d[34]),"+f"(d[35]),"+f"(d[36]),"+f"(d[37]),"+f"(d[38]),"+f"(d[39]),"+f"(d[40]),"+f"(d[41]),"+f"(d[42]),"+f"(d[43]),"+f"(d[44]),"+f"(d[45]),"+f"(d[46]),"+f"(d[47]),"+f"(d[48]),"+f"(d[49]),"+f"(d[50]),"+f"(d[51]),"+f"(d[52]),"+f"(d[53]),"+f"(d[54]),"+f"(d[55]),"+f"(d[56]),"+f"(d[57]),"+f"(d[58]),"+f"(d[59]),"+f"(d[60]),"+f"(d[61]),"+f"(d[62]),"+f"(d[63]),"+f"(d[64]),"+f"(d[65]),"+f"(d[66]),"+f"(d[67]),"+f"(d[68]),"+f"(d[69]),"+f"(d[70]),"+f"(d[71]),"+f"(d[72]),"+f"(d[73]),"+f"(d[74]),"+f"(d[75]),"+f"(d[76]),"+f"(d[77]),"+f"(d[78]),"+f"(d[79]) : "l"(da),"l"(db),"r"(sc));
}
__device__ __forceinline__ void wg_rs160_1(float* d, const uint32_t* a, uint64_t db, int sc) {
  asm volatile("{.reg .pred p; setp.ne.b32 p, %85, 0; wgmma.mma_async.sync.aligned.m64n160k16.f32.bf16.bf16 {%0,%1,%2,%3,%4,%5,%6,%7,%8,%9,%10,%11,%12,%13,%14,%15,%16,%17,%18,%19,%20,%21,%22,%23,%24,%25,%26,%27,%28,%29,%30,%31,%32,%33,%34,%35,%36,%37,%38,%39,%40,%41,%42,%43,%44,%45,%46,%47,%48,%49,%50,%51,%52,%53,%54,%55,%56,%57,%58,%59,%60,%61,%62,%63,%64,%65,%66,%67,%68,%69,%70,%71,%72,%73,%74,%75,%76,%77,%78,%79}, {%80,%81,%82,%83}, %84, p, 1, 1, 1;}"
    : "+f"(d[0]),"+f"(d[1]),"+f"(d[2]),"+f"(d[3]),"+f"(d[4]),"+f"(d[5]),"+f"(d[6]),"+f"(d[7]),"+f"(d[8]),"+f"(d[9]),"+f"(d[10]),"+f"(d[11]),"+f"(d[12]),"+f"(d[13]),"+f"(d[14]),"+f"(d[15]),"+f"(d[16]),"+f"(d[17]),"+f"(d[18]),"+f"(d[19]),"+f"(d[20]),"+f"(d[21]),"+f"(d[22]),"+f"(d[23]),"+f"(d[24]),"+f"(d[25]),"+f"(d[26]),"+f"(d[27]),"+f"(d[28]),"+f"(d[29]),"+f"(d[30]),"+f"(d[31]),"+f"(d[32]),"+f"(d[33]),"+f"(d[34]),"+f"(d[35]),"+f"(d[36]),"+f"(d[37]),"+f"(d[38]),"+f"(d[39]),"+f"(d[40]),"+f"(d[41]),"+f"(d[42]),"+f"(d[43]),"+f"(d[44]),"+f"(d[45]),"+f"(d[46]),"+f"(d[47]),"+f"(d[48]),"+f"(d[49]),"+f"(d[50]),"+f"(d[51]),"+f"(d[52]),"+f"(d[53]),"+f"(d[54]),"+f"(d[55]),"+f"(d[56]),"+f"(d[57]),"+f"(d[58]),"+f"(d[59]),"+f"(d[60]),"+f"(d[61]),"+f"(d[62]),"+f"(d[63]),"+f"(d[64]),"+f"(d[65]),"+f"(d[66]),"+f"(d[67]),"+f"(d[68]),"+f"(d[69]),"+f"(d[70]),"+f"(d[71]),"+f"(d[72]),"+f"(d[73]),"+f"(d[74]),"+f"(d[75]),"+f"(d[76]),"+f"(d[77]),"+f"(d[78]),"+f"(d[79]) : "r"(a[0]),"r"(a[1]),"r"(a[2]),"r"(a[3]),"l"(db),"r"(sc));
}
__device__ __forceinline__ void wg_ss8_10(float* d, uint64_t da, uint64_t db, int sc) {
  asm volatile("{.reg .pred p; setp.ne.b32 p, %6, 0; wgmma.mma_async.sync.aligned.m64n8k16.f32.bf16.bf16 {%0,%1,%2,%3}, %4, %5, p, 1, 1, 1, 0;}"
    : "+f"(d[0]),"+f"(d[1]),"+f"(d[2]),"+f"(d[3]) : "l"(da),"l"(db),"r"(sc));
}
__device__ __forceinline__ void wg_ss8_if(float* d, uint64_t da, uint64_t db, int sc, int skip) {
  asm volatile("{.reg .pred p, q; setp.ne.b32 p, %6, 0; setp.eq.b32 q, %7, 0; @q wgmma.mma_async.sync.aligned.m64n8k16.f32.bf16.bf16 {%0,%1,%2,%3}, %4, %5, p, 1, 1, 1, 0;}"
    : "+f"(d[0]),"+f"(d[1]),"+f"(d[2]),"+f"(d[3]) : "l"(da),"l"(db),"r"(sc),"r"(skip));
}

constexpr uint32_t DB = 1024;
constexpr int UNIT = 8192, WSLOT = 16384, W2TILE = 24576, OFF_R = 12 * UNIT;
constexpr int OFF_PB = 26 * UNIT;
constexpr int OFF_CV = OFF_PB + 16384, OFF_ST = OFF_CV + 768, OFF_TS = OFF_ST + 256, OFF_MODR = OFF_TS + 512, OFF_ROLE = OFF_MODR + 80, OFF_BAR = OFF_ROLE + 16, SMEM_BYTES = OFF_BAR + 1368;
constexpr int OFF_BX = OFF_PB, OFF_AX = OFF_BX + 12288, OFF_RT = OFF_AX + 2048, OFF_GB = OFF_RT + 512, OFF_CO = OFF_CV;
constexpr int OFF_UV = 4 * UNIT, OFF_SX = 24 * UNIT, OFF_XCH = 12 * UNIT;
constexpr int OFF_Q = 99328, KV_V = 4096, KV_H = 8192, F_E = 128, F_O = 4288, OFF_WM = 20 * UNIT, OFF_TAP = 12672, OFF_MR = 25 * UNIT;
constexpr uint64_t pk5(int a, int b, int c, int d, int e) { return (uint64_t)(a / 128) | (uint64_t)(b / 128) << 12 | (uint64_t)(c / 128) << 24 | (uint64_t)(d / 128) << 36 | (uint64_t)(e / 128) << 48; }
constexpr uint64_t T_KV = pk5(119808, 16384, 130048, 65536, 49152), T_F = pk5(140288, 90368, 148736, 81920, OFF_PB), T_X = pk5(0, 4224, 8448, 0, 4224),
                   T_P = pk5(32768, 16384, 65536, 81920, OFF_PB);
__host__ __device__ __forceinline__ uint32_t tab(uint64_t t, int c) { return ((uint32_t)(t >> (12 * c)) & 0xFFF) << 7; }
enum { B_KV = 0, B_FRAW = 5, B_Q = 10, B_WM = 15, B_XR = 17, B_MR = B_XR + 5, B_QTOK, B_ST1, B_MODR, B_ROLE = B_MODR + 5, B_FL = 32, B_PFULL = B_FL + 5, B_PEMPTY = B_PFULL + 5, B_FRDY = B_PEMPTY + 5,
       B_G = B_FRDY + 5, B_EXT = B_G + 2, B_QTD, B_ED, B_S2 = B_ED + 2, B_GB, B_FULL = 60, B_RETRY = B_FULL + 43, B_XFREE = B_RETRY + 8, B_BX, B_UVB, B_CO, B_SX, B_EMPTY = 121, B_SC = 164, B_STD = B_SC + 5, B_LAG };
static_assert(B_ROLE < B_FL && B_GB < B_FULL && B_SX + 5 <= B_EMPTY - 1 && OFF_MR == OFF_SX + 8192 && SMEM_BYTES <= 232448, "barrier groups");
#define BAR(i) (base + OFF_BAR + 8 * (i))

#define PRES ""
constexpr int NE = 21, PRE = sizeof(PRES) / 2;
struct Maps { CUtensorMap km, v, q, fm, wmp, kh, tap, wm, w1a, w3a, xs, w1u, w3u, w1b, w3b, x1s, x1b, w2a, w2b, outa, outb; };
struct Load { uint32_t t, dst, bar, map, ck, gate, par, pad; };
struct Ptrs { const bf16 *c, *ssmd; Scratch* g; uint64_t prog[2]; int boff, ulo, er, ne; uint32_t sseq, mq, st2, xh, gt, m8, gpass, xdep, hstart, hpause, hl[8], eseq, seq2, uvd, mpos, wt0, wpace; float one; Load sched[NE]; uint32_t wdep[30], adep[14]; uint2 w2t[12]; int hid[3][9]; };

#define REGION_IDS int tid, lane, bid; \
  asm volatile("mov.u32 %0, %%tid.x;" : "=r"(tid)); asm volatile("mov.u32 %0, %%laneid;" : "=r"(lane)); asm volatile("mov.u32 %0, %%ctaid.x;" : "=r"(bid)); \
  const int i0 = tid & 127; (void)i0; (void)lane; (void)bid

#define ffn_role(h, j, r) do { \
  mbar_wait(BAR(B_ROLE)); \
  r = __shfl_sync(~0u, lds32(base + OFF_ROLE), 0); \
  asm volatile("mov.u32 %0, %%ctaid.x;" : "=r"(h)); \
  h &= 1; j = r >> 4; r &= 15; } while (0)
__device__ __forceinline__ void rank_pair(Scratch* G, uint32_t base, uint32_t epoch, bool put) {
  REGION_IDS;
  uint32_t t;
  asm volatile("mov.u32 %0, %%smid;" : "=r"(t));
  t >>= 1;
  const uint32_t q = (t - 32) * 37 >> 8, g = t < 32 ? t & 7 : t < 60 ? t - 31 - 7 * q : t < 62 ? t - 54 : 0;
  const uint32_t key = epoch << 20 | (g & 3) << 18 | (g & 4) << 15 | (t & 127) << 6 | bid >> 1;
  if (put) {
    if (lane == (bid & 1) * 99) publish(&G->key[bid >> 1], key);
    return;
  }
  uint2 x;
  int it = 0;
#pragma unroll 1
  do x = ld_relaxed64(&G->key[2 * lane]); while (__any_sync(~0u, ((x.x ^ key) | (x.y ^ key)) >> 20) && ++it < SPIN_LIMIT);
  sts32(base + OFF_ROLE, __popc(__ballot_sync(~0u, x.x < key)) + __popc(__ballot_sync(~0u, x.y < key)));
  arrive1(BAR(B_ROLE));
}
__device__ __forceinline__ int mod_ch(int p) { return p < 40 ? (p >> 3) * 128 + (p & 1) * 64 : 64 * (p < 50 ? p - 40 : p - 50); }
__device__ __forceinline__ int mod_col(int p) { return mod_ch(p) + 640 * (p < 40 ? 0x4210 >> (2 * (p & 6)) & 7 : p < 50 ? 3 : 5); }
__device__ __forceinline__ uint32_t mod_sum(uint2 v) { return pack_bf16(0.f, __uint_as_float(v.x) + __uint_as_float(v.y)); }
#define UVS 5
#define XP 2
#define GA 3
#define GB 1
#define HL 0
#define EH 0
#define MG 4
#define SG 0x88
#define LAG2 38
#define NP 8
__device__ __forceinline__ int nib(uint32_t t, int i) { return (t >> (4 * i)) & 15; }
__device__ __forceinline__ int w_block(int up, int m) { return m < 2 ? 2 * up + m : 4 + up; }
__host__ __device__ constexpr int w2_at(int v) { return UNIT * (v == 1 ? 0 : 0x0811030C18ull >> (v - (v > 1)) % 5 * 8 & 255); }
__host__ __device__ constexpr int hid_at(int m, int g) { return UNIT * ((g ? 0x0200150710ull : 0x010B14060Full) >> m % 5 * 8 & 255); }
__host__ __device__ constexpr int x1_at(int k) { return k < 4 ? 22 * UNIT + 4096 * k : OFF_BX + UNIT; }
__host__ __device__ constexpr uint32_t w2_desc(int v) { return (DB + w2_at(v)) >> 4 | UNIT << 12; }
__host__ __device__ constexpr int a_at(int n) { return WSLOT * (0x54323251041032ull >> 4 * n & 15); }
__host__ __device__ constexpr int second(int v) { return 0xDCBA657498ull >> 4 * v & 15; }

constexpr int NL = sizeof(ORDER) / 2;
__host__ __device__ constexpr int load_bar(int e) { return e < 0 ? B_KV : ORDER[2 * e + 1] - '0' + (ORDER[2 * e] == 'q' ? B_Q : ORDER[2 * e] == 'f' ? B_FRAW : ORDER[2 * e] == 'w' ? B_WM : B_KV); }
__host__ __device__ constexpr int load_gate(int e) {
  int i = e, sum = 0;
  while (i >= -1 && sum + (i < 0 ? 8 : ORDER[2 * i] == 'w' ? 10 : 4) <= WIN) { sum += i < 0 ? 8 : ORDER[2 * i] == 'w' ? 10 : 4; i--; }
  for (; i >= -1; i--) {
    bool ok = i < e;
    for (int k = e; k < NL; k++) ok = ok && load_bar(k) != load_bar(i);
    if (ok) return load_bar(i);
  }
  return -1;
}
template <int E, int E1> __device__ __forceinline__ void loads(const Maps& maps, uint32_t base, uint32_t gt) {
  if constexpr (E < E1) {
    constexpr int r = ORDER[2 * E + 1] - '0', g = load_gate(E);
    constexpr char x = ORDER[2 * E];
    const int c0 = 128 * r + 64 * (blockIdx.x & 1), c1 = 2 * (blockIdx.x & 126);
    if (g >= 0 && (E == 0 || g != load_gate(E - 1))) mbar_wait(BAR(g));
    if (elect()) {
      if (x == 'k') { tma3d(base + tab(T_KV, r), &maps.km, c0, c1, 0, BAR(B_KV + r)); tma3d(base + tab(T_KV, r) + KV_H, &maps.kh, c0, c1 - 1, 5, BAR(B_KV + r)); }
      if (x == 'v') tma3d(base + tab(T_KV, r) + KV_V, &maps.v, c0, c1, 0, BAR(B_KV + r));
      if (x == 'q') tma3d(base + OFF_Q + 4096 * r, &maps.q, c0, c1, 0, BAR(B_Q + r));
      if (x == 'f') tma3d(base + tab(T_F, r) + F_E, &maps.fm, 0, 0, 128 * r + blockIdx.x, BAR(B_FRAW + r));
      if (x == 'w') tma3d(base + OFF_WM + WSLOT * r, &maps.wmp, mod_col((gt >> 8 * r & 255) + (blockIdx.x >> 3)), 80 * (blockIdx.x & 7), 0, BAR(B_WM + r));
    }
    loads<E + 1, E1>(maps, base, gt);
  }
}

template <int U> __device__ __forceinline__ void cstep(float* acc, const uint32_t* A, uint64_t db) {
  const uint32_t* a = A + 4 * U;
  const uint64_t d = db + 16 * U;
  if (U == 4) { wg_rs64_0(acc + 96, A, db + 192, 0); wg_rs48_0(acc + 96, A + 4, db + 208, 1); wg_rs32_0(acc + 96, A + 8, db + 224, 1); wg_rs16_0(acc + 96, A + 12, db + 240, 1); }
  if (U <= 4) wg_rs192_0(acc, a, d, U);
  if (U == 5) wg_rs176_0(acc, a, d, 1);
  if (U == 6) wg_rs160_0(acc, a, d, 1);
  if (U == 7) wg_rs144_0(acc, a, d, 1);
  if (U == 8) wg_rs128_0(acc, a, d, 1);
  if (U == 9) wg_rs112_0(acc, a, d, 1);
  if (U == 10) wg_rs96_0(acc, a, d, 1);
  if (U == 11) wg_rs80_0(acc, a, d, 1);
  if (U == 12) wg_rs64_0(acc, a, d, 1);
  if (U == 13) wg_rs48_0(acc, a, d, 1);
  if (U == 14) wg_rs32_0(acc, a, d, 1);
  if (U == 15) wg_rs16_0(acc, a, d, 1);
}
template <int U0, int U1> __device__ __forceinline__ void csteps(float* acc, const uint32_t* A, uint64_t db) {
  cstep<U0>(acc, A, db);
  if constexpr (U0 > U1) csteps<U0 - 1, U1>(acc, A, db);
}
template <int U0, int U1> __device__ __forceinline__ void cload(uint32_t* A, uint32_t fa) {
  asm volatile("{ld.shared.b32 %0, [%4+%5]; ld.shared.b32 %1, [%4+%5+128]; ld.shared.b32 %2, [%4+%5+16]; ld.shared.b32 %3, [%4+%5+144];}"
               : "=r"(A[4 * U0]), "=r"(A[4 * U0 + 1]), "=r"(A[4 * U0 + 2]), "=r"(A[4 * U0 + 3]) : "r"(fa), "n"(256 * U0) : "memory");
  if constexpr (U0 > U1) cload<U0 - 1, U1>(A, fa);
}

template <int NK> __device__ __forceinline__ void mod_gemv(Scratch* G, uint32_t wm, int p, int part, int w, int lane, uint32_t par) {
  float d[4] = {};
  fence_regs(d);
  wg_fence();
#pragma unroll 1
  for (int k = 0; k < NK; k += 5) {
#pragma unroll
    for (int i = 0; i < 5; i++) wg_ss8_10(d, mkdesc(DB + wm + 2048 * (k + i), 16, 1024, 1), mkdesc(DB + OFF_CV + 32 * (k + i), 16, 128, 0), 1);
  }
  wg_commit();
  const int ch = mod_ch(p) + 16 * w + (lane >> 2);
  uint32_t* dst = (p < 40 ? &G->modc[ch & 127][p >> 3][4 * (p & 6)] : (uint32_t*)&G->modv[p >= 50][ch]) + part;
  wg_wait<0>();
  fence_regs(d);
  if (!(lane & 3)) {
    publish(dst, (__float_as_uint(d[0]) & ~1u) | par);
    publish(dst + (p < 40 ? 1280 : 16), (__float_as_uint(d[2]) & ~1u) | par);
    if (NK == 20 && p < 40 && (p & 6) == 6) {
      dst = (uint32_t*)&G->modv[2][ch] + part;
      publish(dst, (__float_as_uint(d[0]) & ~1u) | par);
      publish(dst + 16, (__float_as_uint(d[2]) & ~1u) | par);
    }
  }
}
__device__ __forceinline__ void mod_fetch(Scratch* G, uint32_t base, uint32_t epoch, uint32_t m8, uint32_t c, uint32_t c1) {
  REGION_IDS;
  const uint32_t* mp = &G->modc[bid][0][lane];
  auto unused = [&]() { return (lane & 6) && !(m8 >> c & 1); };
#pragma unroll 1
  for (int it = 0; c < c1 && it < SPIN_LIMIT; it++) {
    uint32_t m = ld_relaxed32(mp + 32 * c);
    const uint32_t m1 = ld_relaxed32(mp + 32 * min(c + 1, c1 - 1));
#pragma unroll 1
    for (int k = 0; k < 2 && c < c1 && __all_sync(~0u, unused() || !((m ^ epoch) & 1)); k++) {
      float x = unused() ? 0.f : __uint_as_float(m);
      x += __shfl_xor_sync(~0u, x, 1); x += __shfl_xor_sync(~0u, x, 2); x += __shfl_xor_sync(~0u, x, 4);
      const uint32_t y = __byte_perm(badd2(pack_bf16(0.f, x), (lane & 8) * 0x07F00000u), 0, 0x3232), ga = __shfl_sync(~0u, y, 16);
      sts32(base + OFF_MODR + 16 * c + 4 * (lane >> 3), lane < 16 ? bmul2(y, ga) : y);
      arrive1(BAR(B_MODR + c));
      if (lane >= 30 && (m8 >> c & 1)) publish((uint32_t*)&G->modv[2][128 * c + bid] + (lane & 1), ((lane & 1 ? 0 : __float_as_uint(x)) & ~1u) | (epoch & 1));
      m = m1;
      c++;
    }
  }
}
__device__ __forceinline__ void add4(uint4& y, const uint4& z) { y.x = badd2(y.x, z.x); y.y = badd2(y.y, z.y); y.z = badd2(y.z, z.z); y.w = badd2(y.w, z.w); }
template <int MODE> __device__ __forceinline__ void e_round(Scratch* G, uint32_t base, uint32_t sa, uint4*& gp, uint4* q, int c, int nc, int w, uint32_t tag, uint32_t epoch) {
  constexpr int QO = -D_ * 256;
  constexpr bool WIDE = MODE == 1;
  mbar_wait(BAR(B_MODR + c));
  const uint4 co = lds128(base + OFF_MODR + 16 * c);
  mbar_wait(BAR(B_PFULL + c));
  const uint32_t pb = sa + tab(T_P, c);
  uint4 l[2][6];
  auto load = [&](int hf, int k) { l[hf][k] = lds128((k < 4 ? pb + 4096 * k : sa + OFF_MR + 4096 * (k - 4)) + 2048 * hf); };
#pragma unroll
  for (int k = 0; k < 12 && WIDE; k++) load(k / 6, k % 6);
#pragma unroll
  for (int hf = 0; hf < 2; hf++) {
    uint4 &y = l[hf][0], &z = l[hf][4], &m = l[hf][5];
    if (!WIDE) load(hf, 0);
    if (MODE != 2) {
      if (!WIDE) load(hf, 1);
      add4(y, l[hf][1]);
      if (!WIDE) { load(hf, 2); load(hf, 3); }
      add4(l[hf][2], l[hf][3]);
      add4(y, l[hf][2]);
    }
    if (!WIDE) { load(hf, 4); load(hf, 5); }
    if (MODE == 2) {
#pragma unroll 1
      for (int it = 0; __any_sync(~0u, ((z.x >> 15 ^ epoch) | (m.x ^ epoch)) & tag) && it < SPIN_LIMIT; it++) {
        const uint4* sp = (const uint4*)G->st1 + (opaque(sa) - base >> 4) + 128 * hf;
        z = ld_relaxed128(sp);
        m = ld_relaxed128(sp + 256);
        sts128(sa + OFF_MR + 2048 * hf, z.x, z.y, z.z, z.w);
        sts128(sa + OFF_MR + 2048 * hf + 4096, m.x, m.y, m.z, m.w);
      }
      z.x &= 0xFFFF7FFFu;
      sts32(sa + OFF_MR + 2048 * hf, z.x);
    }
#pragma unroll 1
    for (int it = 0; __any_sync(~0u, (q[hf].x ^ epoch) & tag) && it < SPIN_LIMIT; it++) {
      q[hf] = ld_relaxed128(gp + QO + 128 * hf);
    }
    y.x = bfma2(bfma2(bfma2(q[hf].x, z.x, m.x), co.y, co.x), y.x, q[hf].x);
    auto hint = [&]() {
      __syncwarp();
      asm volatile("{.reg .pred p; elect.sync _|p, 0xffffffff; @p red.relaxed.gpu.global.add.u32 [%0], 1; @p mbarrier.arrive.shared::cta.b64 _, [%1];}"
                   ::"l"(G->xsh[c][2 * w + (blockIdx.x >> 6)]), "r"(BAR(B_PEMPTY + c)), "r"(y.x) : "memory");
    };
    if (hf && !EH) hint();
    y.y = bfma2(bfma2(bfma2(q[hf].y, z.y, m.y), co.y, co.x), y.y, q[hf].y);
    y.z = bfma2(bfma2(bfma2(q[hf].z, z.z, m.z), co.y, co.x), y.z, q[hf].z);
    y.w = bfma2(bfma2(bfma2(q[hf].w, z.w, m.w), co.y, co.x), y.w, q[hf].w);
    st_relaxed128(gp + 128 * hf, set_tag(bmul2(y.x, co.w), tag, epoch), bmul2(y.y, co.w), bmul2(y.z, co.w), bmul2(y.w, co.w));
    if (hf && EH == 1) hint();
    asm volatile("{.reg .pred p; .reg .b32 t; setp.ne.u32 p, %5, 0; max.u32 t, %1, 1; @!p st.relaxed.gpu.global.v4.u32 [%0+%6], {t,%2,%3,%4}; @p st.relaxed.gpu.global.v4.u32 [%0+%7], {t,%2,%3,%4};}"
                 ::"l"(gp + 128 * hf), "r"(y.x), "r"(y.y), "r"(y.z), "r"(y.w), "r"(epoch & 1), "n"(D_ * 4096), "n"(D_ * 8192) : "memory");
    if (hf && EH == 2) hint();
    if (hf) gp += 32768 * (nc - c);
    if (nc >= 0) q[hf] = ld_relaxed128(gp + QO + (hf ? 128 : 32768 * (nc - c)));
  }
}
__device__ __forceinline__ void q_stats(uint32_t base, int w) {
  REGION_IDS;
  float s0 = 0.f, s1 = 0.f, q0 = 0.f, q1 = 0.f;
  const uint32_t a = OFF_Q + 1024 * w + 128 * (lane & 7) + (((lane >> 3) ^ (lane & 7)) << 4);
  const uint32_t ra = mapa(base + OFF_ST + 128 * (bid & 1) + 64 * (lane & 1) + 16 * w + 8 * (lane >> 2), lane >> 1 & 1), rb = mapa(BAR(B_ST1), lane >> 1 & 1);
  if (w == 3 && elect()) mbar_expect_tx(BAR(B_ST1), 256);
#pragma unroll 1
  for (int k = 0; k < 5; k++) {
    mbar_wait(BAR(B_Q + k));
    const uint32_t o = opaque(base + 4096 * k);
    const uint4 x = lds128(o + a), y = lds128(o + (a ^ 64));
    const uint32_t e[8] = {x.x, x.y, x.z, x.w, y.x, y.y, y.z, y.w};
#pragma unroll
    for (int i = 0; i < 8; i++) { const float lo = bf_lo(e[i]), hi = bf_hi(e[i]); s0 += lo; s1 += hi; q0 = fmaf(lo, lo, q0); q1 = fmaf(hi, hi, q1); }
  }
  s0 += s1; q0 += q1;
  arrive1(BAR(B_STD));
  s0 += __shfl_xor_sync(~0u, s0, 8); q0 += __shfl_xor_sync(~0u, q0, 8);
  s0 += __shfl_xor_sync(~0u, s0, 16); q0 += __shfl_xor_sync(~0u, q0, 16);
  if (lane < 8) asm volatile("st.async.shared::cluster.mbarrier::complete_tx::bytes.v2.b32 [%0], {%1,%2}, [%3];" ::"r"(ra), "r"(__float_as_uint(s0)), "r"(__float_as_uint(q0)), "r"(rb) : "memory");
}
__device__ __forceinline__ void short_conv(Scratch* G, uint32_t base, int s, int w, uint32_t par, uint32_t xh) {
  REGION_IDS;
  const uint32_t a = base + tab(T_KV, s) + 128 * (lane & 3) + ((w ^ (lane & 3)) << 4) + 4 * (lane & 16) + (lane & 12), keep = ~(lane & 1);
  uint4* dst = G->xr + (128 * s + 64 * (bid & 1) + 8 * w + 2 * (lane & 16) + (lane >> 1 & 6)) * 256 + 255 - 4 * (bid >> 1) - (lane & 3);
  mbar_wait(BAR(B_KV));
  mbar_wait(BAR(B_KV + s));
  const uint4 wv = lds128(base + OFF_TAP + 512 * s + 64 * w + 16 * (lane & 16) + 4 * (lane & 12));
  uint32_t kk[11], r[8];
#pragma unroll
  for (int k = 0; k < 11; k++) kk[k] = k < 3 ? lds32((a ^ (64 * (k & 1))) + KV_H + 512 * k) : lds32((a ^ (64 * (~k & 1))) + 512 * (k - 3));
  if (xh == 0 && elect()) red_hint(G->hint[s][4 * (bid & 1) + w]);
#pragma unroll
  for (int k = 0; k < 8; k++) r[k] = lds32((a ^ (64 * (k & 1))) + KV_V + 512 * k);
  arrive1(BAR(B_SC + s));
  const uint32_t w0 = __byte_perm(wv.x, wv.z, 0x5410), w1 = __byte_perm(wv.x, wv.z, 0x7632),
                 w2 = __byte_perm(wv.y, wv.w, 0x5410), w3 = __byte_perm(wv.y, wv.w, 0x7632);
#pragma unroll
  for (int k = 0; k < 8; k++) r[k] = bmul2(bfma2(kk[k + 3], w0, bfma2(kk[k + 2], w1, bfma2(kk[k + 1], w2, bmul2(kk[k], w3)))), r[k]);
  const uint32_t bit = ~par >> 7 & lane & 1;
  if (xh == 1 && elect()) red_hint(G->hint[s][4 * (bid & 1) + w]);
  st_relaxed128(dst, (__byte_perm(r[7], r[6], 0x5410) & keep) | bit, __byte_perm(r[5], r[4], 0x5410), __byte_perm(r[3], r[2], 0x5410), __byte_perm(r[1], r[0], 0x5410));
  st_relaxed128(dst + 256, (__byte_perm(r[7], r[6], 0x7632) & keep) | bit, __byte_perm(r[5], r[4], 0x7632), __byte_perm(r[3], r[2], 0x7632), __byte_perm(r[1], r[0], 0x7632));
  if (xh == 2 && elect()) red_hint(G->hint[s][4 * (bid & 1) + w]);
}
__device__ __forceinline__ void silu_vector(const bf16* c, int n, uint32_t base) {
  REGION_IDS;
  if (tid < n) {
    const uint32_t x = ldg32(c + 2 * tid);
    sts32(base + OFF_CV + 4 * tid, pack_bf16(silu_f(bf_lo(x)), silu_f(bf_hi(x))));
  }
  fence_async_smem();
}

template <int FIRST> __global__ void __cluster_dims__(2, 1, 1) __launch_bounds__(512, 1) k_fused(const __grid_constant__ Ptrs P, const __grid_constant__ Maps maps) {
  Scratch* const G = P.g;
  extern __shared__ __align__(1024) uint8_t smem_raw[];
  const uint32_t t_start = clock();
  const uint32_t base = __shfl_sync(~0u, smem_u32(smem_raw), 0);
  if (threadIdx.x == 416 && blockIdx.x + FIRST < 128) {
    const int c0 = 64 * (blockIdx.x & 1), c1 = 2 * (blockIdx.x & 126);
    mbar_init<1>(BAR(B_KV), 1);
    mbar_expect_tx(BAR(B_KV), 12288);
    tma3d(base + tab(T_KV, 0), &maps.km, c0, c1, 0, BAR(B_KV));
    tma3d(base + tab(T_KV, 0) + KV_V, &maps.v, c0, c1, 0, BAR(B_KV));
    tma3d(base + tab(T_KV, 0) + KV_H, &maps.kh, c0, c1 - 1, 5, BAR(B_KV));
    tma3d(base + OFF_TAP, &maps.tap, 0, blockIdx.x & 1, 0, BAR(B_KV));
  }
  if ((base & 0xFFFFFFu) != DB) __trap();
  const int wid = __shfl_sync(~0u, threadIdx.x >> 5, 0), wg = wid >> 2, w = wid & 3;
  if (blockIdx.x + FIRST >= 128) {
    REGION_IDS;
    auto unit = [&](int n) { return 4 * (P.hl[n >> 2] >> 8 * (n & 3) & 255) + (bid & 3); };
    auto fetch = [&](int n, int b) {
      if (unit(n) < 120 && elect()) {
        mbar_expect_tx(BAR(n), 40960);
#pragma unroll 1
        for (int k = 0; k < 5; k++) tma3d(base + 40960 * b + 8192 * k, &maps.wm, mod_col(unit(n) >> 1), 320 * (bid & 1) + 64 * k, 0, BAR(n));
      }
    };
    if (wid == 0) {
      mbar_init<4>(BAR(0), 1);
#pragma unroll 1
      for (int n = 0; n < 4; n++) { wait_clock(t_start + (P.hstart & 0xFFFF) + n * (P.hstart >> 16)); fetch(n, n); }
      mbar_init<28>(BAR(4), 1);
    }
    const uint32_t par = ~ld_relaxed32(G->hint[7][0]) >> 7 & 1;
    silu_vector(P.c + 320 * (bid & 1), 160, base);
    __syncthreads();
#pragma unroll 1
    for (int n = wg; unit(n) < 120; n += 4) {
      mbar_wait(BAR(n));
      mod_gemv<20>(G, 40960 * (n % 5), unit(n) >> 1, bid & 1, w, lane, par);
      named_bar(1 + wg, 128);
      if (w == 0) {
        wait_clock(t_start + P.hpause);
        if (n == 0) fetch(4, 4);
        fetch(n + 5, n % 5);
      }
    }
    return;
  }
  mbar_init<3>(BAR(wid < 15 ? 4 * wid + 1 : B_SC + 1), wid < 8 ? 1 : 4);
  mbar_init<1>(BAR(!wid ? B_SC + 4 : wid < 15 ? 4 * wid : B_SC), wid && wid < 8 ? 1 : 4);
  if (wid == 0) mbar_init<2>(BAR(B_SC + 5), 4);
  asm volatile("fence.mbarrier_init.release.cluster; bar.sync 0, 512;" ::: "memory");
  if (wid == 13) loads<0, EARLY>(maps, base, 0);
  if (wid == 13 && PRE && elect()) {
#pragma unroll
    for (int e = 0; e < PRE; e++) {
      const int r = PRES[2 * e + 1] - '0', c0 = 128 * r + 64 * (blockIdx.x & 1), c1 = 2 * (blockIdx.x & 126);
      if (PRES[2 * e] == 'k') { tma3d(base + tab(T_KV, r), &maps.km, c0, c1, 0, BAR(B_KV + r)); tma3d(base + tab(T_KV, r) + KV_H, &maps.kh, c0, c1 - 1, 5, BAR(B_KV + r)); }
      if (PRES[2 * e] == 'v') tma3d(base + tab(T_KV, r) + KV_V, &maps.v, c0, c1, 0, BAR(B_KV + r));
      if (PRES[2 * e] == 'q') tma3d(base + OFF_Q + 4096 * r, &maps.q, c0, c1, 0, BAR(B_Q + r));
      if (PRES[2 * e] == 'f') tma3d(base + tab(T_F, r) + F_E, &maps.fm, 0, 0, 128 * r + blockIdx.x, BAR(B_FRAW + r));
    }
  }
  asm volatile("barrier.cluster.arrive.relaxed.aligned;" ::: "memory");
#define LAUNCHES const uint32_t launches = ld_relaxed32(G->hint[7][blockIdx.x >> 4])
#define EPOCH ((__shfl_sync(~0u, launches, 0) >> 7) + 1)
  if (wg < 2) {
    asm volatile("setmaxnreg.inc.sync.aligned.u32 224;");
    LAUNCHES;
    uint32_t par = launches;
    {
      float acc[128];
      uint32_t A[64];
#pragma unroll
      for (int i = 0; i < 64; i++) asm volatile("" : "=r"(A[i]));
      int c = wg, g = P.gpass >> wg & 1;
#pragma unroll 1
      for (uint64_t prog = P.prog[wg]; prog; prog >>= 8) {
        REGION_IDS;
        const int s = prog & 7;
        if (s < 5) short_conv(G, base, s, w, par, P.xh);
        if (prog == P.prog[wg]) cluster_wait();
        if (prog & 16) {
          mbar_wait(BAR(B_QTD));
          mbar_wait(BAR(B_WM + g));
          mod_gemv<5>(G, OFF_WM + WSLOT * g, (P.gt >> 8 * g & 255) + (bid >> 3), bid & 7, w, lane, ~par >> 7 & 1);
          arrive1(BAR(B_G + g));
          g++;
        }
        if (prog & 8) q_stats(base, w);
        if (prog & 32) {
          const int L = 16 * w + (lane >> 2) + 2 * (lane & 3) - 7;
          const uint32_t fo = base + ((L & 1) ? F_O + 2 * (L + 1) : F_E + 2 * L);
          mbar_wait(BAR(B_FRDY + c));
          cload<0, 0>(A, fo + tab(T_F, c));
          cload<15, 1>(A, fo + tab(T_F, c));
          arrive1(BAR(B_FL + c));
        }
        if (!(prog & 64)) continue;
        uint32_t xo;
#pragma unroll 1
        for (int it = 0; it < SPIN_LIMIT; it++) {
          xo = tab(T_X, opaque(c));
          mbar_wait(BAR(B_XR + c), it & 1);
          const uint32_t tag = lds32(base + xo + 32 * i0);
          wg_fence();
          csteps<0, 0>(acc, A, mkdesc(DB + xo, 16, 128, 0));
          csteps<15, 6>(acc, A, mkdesc(DB + xo, 16, 128, 0));
          wg_commit();
          if (bar_all(1 + wg, (tag ^ par >> 7) & 1)) break;
          wg_wait<0>();
          if (w == 0 && elect()) { mbar_expect_tx(BAR(B_XR + c), 4096); bulk_load(base + xo, G->xr + (128 * c + bid) * 256, 4096, BAR(B_XR + c)); }
        }
        wg_fence();
        csteps<5, 1>(acc, A, mkdesc(DB + tab(T_X, opaque(c)), 16, 128, 0));
        wg_commit();
        mbar_wait(BAR(B_SC + (c == 2 ? 3 : c)));
        wg_wait<0>();
        fence_regs(acc);
        const uint32_t pb = base + tab(T_P, c) + 4096 * w;
#pragma unroll
        for (int k = 0; k < 8; k++) {
          uint32_t p[4];
#pragma unroll
          for (int e = 0; e < 4; e++) { const int i = 4 * k + e; p[e] = i < 31 ? pack_bf16(acc[4 * i] + acc[4 * i + 6], acc[4 * i + 1] + acc[4 * i + 7]) : pack_bf16(acc[124], acc[125]); }
          if (k == 0 && (lane & 3) < w) p[0] = 0;
          stmatrix_x4_t(k == 0 ? pb + 16 * ((255 - lane + 2 * w) & 255) : pb + 16 * (255 - lane + 2 * w) - 512 * k, p[0], p[1], p[2], p[3]);
        }
        arrive1(BAR(B_PFULL + c));
        c += 2;
      }
    }
    par = ~par >> 7 & 1;
    if (wg) arrive1(BAR(B_ED + 1));
    uint32_t ck;
    { REGION_IDS; ck = base + wg * UNIT + lane * 128 + (((2 * w) ^ (lane & 7)) << 4); }
    const uint32_t abd = DB + wg * UNIT;
    auto tags = [&](int as, bool first) { return (lds32(ck + as) ^ par) | (lds32(ck + as + (first ? 4096 : 256)) ^ par); };
    int role;
    { int h, j, r; ffn_role(h, j, r); role = (2 * r + (h ^ wg)) * 8 + 4 * h + j; }
    auto a_tile = [&](int as, int n, bool first) {
#pragma unroll 1
      for (int it = 0; __any_sync(~0u, tags(as, first) & 1) && it < SPIN_LIMIT; it++) {
        if (elect()) {
          mbar_expect_tx(BAR(B_RETRY + wid), UNIT);
          if (first) tma2d(base + wg * UNIT + as, &maps.xs, 8 * role & ~63, 64 * n, BAR(B_RETRY + wid));
          else bulk_load(base + as, G->hh + ((role & ~3) + ((role + n) & 3)) * 1536 + (n >> 2) * 512, UNIT, BAR(B_RETRY + wid));
        }
        mbar_wait(BAR(B_RETRY + wid), par >> 1);
        par ^= 2;
      }
    };
    float acc[128], acb[64];
    int ws = 0;
    float d[8];
    uint32_t *ud0, *ud1;
    unsigned* uh;
    {
      REGION_IDS;
      const int r = role >> 4, row = (r & 14) + (lane >> 2 & 1);
      ud0 = &G->uv[role & 7][32 * row + 4 * ((2 * w ^ row) & 7) + (lane & 3)];
      ud1 = ud0 + 512 * w_block(r & 1, 2);
      ud0 += 512 * w_block(r & 1, wg);
      uh = G->hint[8][role & 7];
      asm volatile("" : "+l"(ud0), "+l"(ud1), "+l"(uh));
    }
    auto step = [&](int n, int uv) {
      const int as = a_at(n);
      const uint64_t da = mkdesc(abd + as, 16, 1024, 1), db = mkdesc(DB + OFF_R + ws, 4096, 1024, 1);
      mbar_wait(BAR(B_FULL + 2 * n));
      a_tile(as, n, true);
      if (uv == 1) { mbar_wait(BAR(B_UVB)); mbar_wait(BAR(B_CO)); }
      wg_fence();
#pragma unroll
      for (int k = 0; k < 4; k++) {
        wg_ss64_11(acc + 96, da + 128 * k, db + 768 + 128 * (k & 1) + 1024 * (k >> 1), k ? 1 : n);
        if (k == GA - 1) { wg_commit(); wg_wait<1>(); if (elect()) mbar_arrive(BAR(B_EMPTY + 2 * n - 1)); if (uv == 2) fence_regs(d); }
      }
      if (uv == 1) {
#pragma unroll
        for (int k = 0; k < 5; k++) {
          wg_ss8_10(d, mkdesc(DB + OFF_UV + 2048 * wg + 6144 * k, 16, 1024, 1), mkdesc(DB + OFF_CO + 64 * k, 32, 128, 0), k);
        }
        if (!wg) {
#pragma unroll
          for (int k = 0; k < 5; k++) wg_ss8_10(d + 4, mkdesc(DB + OFF_UV + 4096 + 6144 * k, 16, 1024, 1), mkdesc(DB + OFF_CO + 64 * k, 32, 128, 0), k);
        }
      }
#pragma unroll
      for (int k = 0; k < 4; k++) wg_ss192_11(acc, da + 128 * k, db + 128 * (k & 1) + 1024 * (k >> 1), k ? 1 : n);
      wg_commit();
      ws = ws == 4 * WSLOT ? 0 : ws + 2 * WSLOT;
      if (uv == 2) {
        split(P.ulo, 30);
        REGION_IDS;
        const uint32_t tag = !(lane & 3);
        if (elect()) red_hint(uh);
        uint32_t x[4];
#pragma unroll
        for (int k = 0; k < 4; k++) asm volatile("movmatrix.sync.aligned.m8n8.trans.b16 %0, %1;" : "=r"(x[k]) : "r"(pack_bf16(d[2 * k], d[2 * k + 1])));
        const uint32_t y1 = __shfl_up_sync(~0u, x[1], 8), y3 = __shfl_up_sync(~0u, x[3], 8);
        if (lane < 16) {
          st_relaxed32((uint32_t*)((uint64_t)ud0 ^ 2 * (lane & 8)), set_tag(lane < 8 ? x[0] : y1, tag, par));
          if (!wg) st_relaxed32((uint32_t*)((uint64_t)ud1 ^ 2 * (lane & 8)), set_tag(lane < 8 ? x[2] : y3, tag, par));
        }
      }
    };
#pragma unroll 1
    for (int n = 0; n < UVS; n++) step(n, 0);
    step(UVS, 1);
    step(UVS + 1, 2);
#pragma unroll 1
    for (int n = UVS + 2; n < 10; n++) step(n, 0);
    float o[80];
    uint32_t fr[3][16], bo;
    {
      REGION_IDS;
      float r0, r1, s0, s1;
      const int id = role, j = role;
      uint4* const hdst = G->hh + id * 1536 + 128 * w + (lane ^ lane >> 3);
      const uint32_t keep = ~(~lane & 1), bit = par & ~keep;
      bo = 1024 + ((j & 1) << 23);
      auto own = [&](int i) { wg_rs160_1(o, fr[i >> 2] + 4 * (i & 3), mkdesc(DB + w2_at(i / 4) + (i & 3) * 2048, UNIT, bo, 1), i); };
      auto hint = [&](int v) { asm volatile("{.reg .pred p; setp.eq.u32 p, %1, 0; @p red.relaxed.gpu.global.add.u32 [%0], 1;}" ::"l"(&G->hhf[id * 8 + v]), "r"(lane) : "memory"); };
      auto put = [&](int v, int k) {
        uint32_t* x = fr[v] + 2 * k;
        const uint32_t t0 = (x[k / 2] & keep) | bit, t1 = (x[5 + k / 2] & keep) | bit;
        x[k / 2] = t0; x[5 + k / 2] = t1;
        st_relaxed128(hdst + 512 * v + 8 * k, x[0], x[2], x[4], x[6]);
        st_relaxed128(hdst + 512 * v + 8 * k + 64, x[1], x[3], x[5], x[7]);
      };
      auto move = [&](uint32_t* x, int n) {
#pragma unroll
        for (int k = 0; k < n; k++) asm volatile("mul.rn.f32 %0, %0, %1;" : "+r"(x[k]) : "f"(P.one));
      };
      auto act = [&](int i) {
        const int v = i >> 3, k = 7 - (i & 7);
        const float *g = v < 2 ? acc + 32 * v + 4 * k : acb + 4 * k, *up = g + (v < 2 ? 64 : 32);
        fr[v][2 * k] = pack_bf16(silu2(g[0], r0, s0) * up[0], silu2(g[1], r0, s0) * up[1]);
        fr[v][2 * k + 1] = pack_bf16(silu2(g[2], r1, s1) * up[2], silu2(g[3], r1, s1) * up[3]);
        if (!(k & 3)) { put(v, k); if (!k && !(HL >> v & 1)) hint(v); if (i == 15) { move(fr[0], 16); } }
        else pin(P.ulo, fr[v][2 * k] ^ fr[v][2 * k + 1]);
      };
#pragma unroll
      for (int v = 0; v < 10; v++) {
        mbar_wait(BAR(B_FULL + 20 + v));
        if (v == XP) {
          mbar_wait(BAR(B_EXT));
          wg_fence();
          wg_ss192_01(acc, mkdesc(DB + OFF_AX + 1024 * opaque(wg), 0, 128, 0), mkdesc(DB + OFF_BX, 2048, 1024, 1), 1);
          wg_ss64_01(acc + 96, mkdesc(DB + OFF_AX + 1024 * opaque(wg), 0, 128, 0), mkdesc(DB + OFF_BX + 6144, 2048, 1024, 1), 1);
          wg_commit();
          r0 = 0.5f * __uint_as_float(lds32(base + OFF_RT + 256 * wg + 64 * w + (lane & 28)));
          r1 = 0.5f * __uint_as_float(lds32(base + OFF_RT + 256 * wg + 64 * w + 32 + (lane & 28)));
          s0 = 2.f * r0 * r0;
          s1 = 2.f * r1 * r1;
        }
        wg_fence();
#pragma unroll
        for (int k = 0; k < 4; k++) {
          wg_ss128_11(acb, mkdesc(opaque(abd) + a_at(second(v)) + k * 2048, 16, 1024, 1), mkdesc(DB + OFF_R + WSLOT * ((v + 2) % 6) + k * 2048, UNIT, 1024, 1), v + k);
          if (k == GB - 1) { wg_commit(); wg_wait<1>(); if (v == XP) fence_regs(acc); if (elect()) mbar_arrive(BAR(B_EMPTY + 19 + v)); }
        }
        if (v == 9) wg_ss128_01(acb, mkdesc(DB + OFF_AX + 1024 * opaque(wg), 0, 128, 0), mkdesc(DB + OFF_BX + UNIT, 2048, 1024, 1), 1);
        wg_commit();
        split(P.ulo, v);
        if (v == XP + NP / 2 && (HL & 1)) hint(0);
        if (v == XP + NP && (HL & 2)) hint(1);
#pragma unroll
        for (int i = 0; i < 16; i++) if (v >= XP && i * NP / 16 == v - XP) act(i);
      }
#pragma unroll
      for (int v = 0; v < 3; v++) {
        mbar_wait(BAR(B_FULL + 30 + v));
        wg_fence();
#pragma unroll
        for (int i = 0; i < 4; i++) {
          own(4 * v + i);
          if (i == GB - 1) { wg_commit(); wg_wait<1>(); if (v == 0) fence_regs(acb); if (elect()) mbar_arrive(BAR(B_EMPTY + 29 + v)); }
        }
        wg_commit();
        split(P.ulo, 10 + v);
        if (v == 0 && XP + NP == 10 && (HL & 2)) hint(1);
        if (v == 2 && (HL & 4)) hint(2);
#pragma unroll
        for (int i = 0; i < 4; i++) if (v < 2) act(16 + 4 * v + i);
      }
      ck = base + 2048 * w + 516 * (lane >> 3) + 144 * (lane >> 2 & 1) + 32 * (lane & 3);
    }
    uint32_t x1[40], gb[20];
    if (!wg) {
      REGION_IDS;
      mbar_wait(BAR(B_GB));
#pragma unroll
      for (int k = 0; k < 5; k++) {
        const uint4 g = lds128(base + OFF_GB + 80 * (lane & 3) + 16 * k);
        gb[4 * k] = g.x; gb[4 * k + 1] = g.y; gb[4 * k + 2] = g.z; gb[4 * k + 3] = g.w;
      }
    }
#pragma unroll 1
    for (int u = 33; u < 42; u++) {
      const int x = P.hid[wg][u - 33], as = x & ~15;
      const uint64_t wd = mkdesc(0, 0, bo, 1) | P.w2t[u - 30].x;
      mbar_wait(BAR(B_FULL + u));
      a_tile(as, x & 15, false);
      if (wg || u < LAG2) {
        wg_fence();
#pragma unroll
        for (int kk = 0; kk < 4; kk++) {
          wg_ss160_01(o, mkdesc(DB + as + kk / 2 * 512 + (kk & 1) * 32, 16, 1024, 2), wd + kk * 128, 1);
          if (kk == GB - 1) { wg_commit(); wg_wait<1>(); if (elect()) mbar_arrive(BAR(B_EMPTY + u - 1)); }
        }
        wg_commit();
        if (u == 41 && elect()) mbar_arrive(BAR(B_LAG));
      }
      if (u == LAG2 - 1 && !wg) {
        REGION_IDS;
        const uint32_t xa = base + (lane >> 4) * 1024 + (lane & 7) * 128 + (((2 * w + ((lane >> 3) & 1)) ^ (lane & 7)) << 4);
        mbar_wait(BAR(B_FULL + 42));
        wg_wait<0>();
        if (elect()) mbar_arrive(BAR(B_EMPTY + LAG2 - 1));
#pragma unroll
        for (int k = 0; k < 10; k++) ldmatrix_x4_t(x1 + 4 * k, xa + x1_at(k / 2) + (k & 1) * 2048);
      }
    }
    REGION_IDS;
    const int h = role >> 2 & 1, j = role & 3;
    const uint32_t xb = base + OFF_XCH + 5120 * w;
    if (wg) {
      const uint32_t rdst = mapa(xb + 16 * lane, h ^ 1), rbar = mapa(BAR(B_FULL + 1), h ^ 1);
      mbar_wait(BAR(B_XFREE));
      wg_wait<0>();
      fence_regs(o);
#pragma unroll
      for (int k = 0; k < 10; k++)
        asm volatile("st.async.shared::cluster.mbarrier::complete_tx::bytes.v4.b32 [%0], {%1,%2,%3,%4}, [%5];" ::"r"(rdst + 512 * k), "r"(pack_bf16(o[8 * k], o[8 * k + 1])),
                     "r"(pack_bf16(o[8 * k + 2], o[8 * k + 3])), "r"(pack_bf16(o[8 * k + 4], o[8 * k + 5])), "r"(pack_bf16(o[8 * k + 6], o[8 * k + 7])), "r"(rbar + 16 * (k / 4)) : "memory");
    } else {
      mbar_wait(BAR(B_LAG));
      wg_fence();
#pragma unroll
      for (int i = 4 * LAG2; i < 168; i++) wg_ss160_01(o, mkdesc(DB + hid_at(i / 4 - 33, 0) + (i & 2) * 256 + (i & 1) * 32, 16, 1024, 2), mkdesc(DB + w2_at(i / 4 - 30) + (i & 3) * 2048, UNIT, bo, 1), 1);
      wg_commit();
      const int row = (8 * role & ~63) + 16 * w;
      auto merge = [&](int e0, int e1) {
#pragma unroll
        for (int e = e0; e < e1; e++) {
          if (e % 4 == 0) mbar_wait_cluster(BAR(B_FULL + 1 + e / 2));
          const uint4 p = lds128(xb + 16 * lane + 512 * e);
          x1[4 * e] = bfma2(gb[2 * e], p.x, x1[4 * e]); x1[4 * e + 1] = bfma2(gb[2 * e], p.y, x1[4 * e + 1]);
          x1[4 * e + 2] = bfma2(gb[2 * e + 1], p.z, x1[4 * e + 2]); x1[4 * e + 3] = bfma2(gb[2 * e + 1], p.w, x1[4 * e + 3]);
        }
        __syncwarp();
      };
      merge(0, MG);
      wg_wait<0>();
      fence_regs(o);
#pragma unroll
      for (int k = 0; k < 10; k++) {
        if (k >= MG && k % 4 == 0) merge(k, k < 8 ? k + 4 : 10);
        uint32_t y[4];
#pragma unroll
        for (int e = 0; e < 4; e++) y[e] = bfma2(gb[2 * k + e / 2], pack_bf16(o[8 * k + 2 * e], o[8 * k + 2 * e + 1]), x1[4 * k + e]);
        stmatrix_x4(k < 8 ? xb + 2048 * (k >> 2) + (lane & 15) * 128 + (((2 * (k & 3) + (lane >> 4)) ^ (lane & 7) ^ 4 * (j & 1)) << 4)
                          : xb + 4096 + (lane & 15) * 64 + (((2 * (k & 1) + (lane >> 4)) ^ (lane >> 1 & 3)) << 4), y[0], y[1], y[2], y[3]);
        if ((SG >> k & 1) || k == 9) {
          fence_async_smem();
          __syncwarp();
#pragma unroll
          for (int b = 0; b < 3; b++) {
            const int e = b < 2 ? 4 * b + 3 : 9;
            if (e <= k && !(SG & ((1 << k) - 1) & ~((1 << e) - 1)) && lane == 0) tma2d_store(b < 2 ? &maps.outa : &maps.outb, b < 2 ? 128 * j + 64 * b : 512 + 32 * j, row, xb + 2048 * b);
          }
        }
      }
      if (lane == 0) { bulk_commit(); bulk_wait_read(); }
    }
  } else if (wg == 2) {
    asm volatile("setmaxnreg.dec.sync.aligned.u32 40;");
    mbar_init<15>(BAR(B_FULL + 15 * w), 1);
    mbar_init<11>(BAR(B_EMPTY - 1 + 11 * w), 8);
    asm volatile("fence.mbarrier_init.release.cluster;" ::: "memory");
    LAUNCHES;
    silu_vector(P.c + 80 * (blockIdx.x & 7) - 512, 296, base - 1024);
    const uint32_t epoch = EPOCH;
    if (w == 2) rank_pair(G, base, epoch, true);
    cluster_wait();
    {
      REGION_IDS;
      const uint32_t tag = opaque(~lane & 1);
      auto q_t = [&]() {
        const int tr = 4 * (lane & 1) + (lane >> 1 & 3);
        uint32_t a = base + OFF_Q + 128 * ((lane & 24) + tr) + ((w ^ tr) << 4);
        uint4* dst = G->qt + (64 * (bid & 1) + 8 * w + (lane >> 2)) * 256 + 4 * (bid >> 1) + (lane & 3);
#pragma unroll 1
        for (int c = 0; c < 5; c++) {
          mbar_wait(BAR(B_Q + c));
#pragma unroll
          for (int k = 0; k < 2; k++) {
            uint32_t x[4];
            ldmatrix_x4_t(x, a ^ (64 * k));
            st_relaxed128(dst + 8192 * k, set_tag(x[0], tag, epoch), x[1], x[2], x[3]);
          }
          a += 4096;
          dst += 32768;
        }
        arrive1(BAR(B_QTD));
      };
      q_t();
      if (w == 3) {
        mbar_wait_cluster(BAR(B_ST1));
        if (lane < 8) red_hint(G->hint[5][lane]);
        const uint2 x = lds64(base + OFF_ST + 8 * (lane & 15)), y = lds64(base + OFF_ST + 128 + 8 * (lane & 15));
        float m, sd;
        ln_final(__uint_as_float(x.x) + __uint_as_float(y.x), __uint_as_float(x.y) + __uint_as_float(y.y), m, sd);
        sd = rbf(rcpf(sd));
        const uint32_t mr = pack_bf16(sd, -rbf(m) * sd), tg = lane & 7 ? 0 : lane & 8 ? 1 : 0x8000;
        const uint32_t o = __byte_perm(__shfl_sync(~0u, mr, 2 * lane & 14), __shfl_sync(~0u, mr, (2 * lane & 14) + 1), (lane & 8) ? 0x7632 : 0x5410);
        if (lane < 16) st_relaxed32(&G->st1[lane >> 3][8 * bid + (lane & 7)], (o & ~tg) | ((epoch & 1) * tg));
      }
      if (w == 2) rank_pair(G, base, epoch, false);
      if (w == 1) mod_fetch(G, base, epoch, P.m8, 0, 1);
    }
    {
      REGION_IDS;
      const uint32_t tag = opaque(~lane & 1), sa = opaque(base + 16 * i0);
      uint4 q[2];
      mbar_wait(BAR(B_PFULL));
#pragma unroll 1
      for (uint32_t a = sa + tab(T_P, 0); a < sa + tab(T_P, 0) + 4096; a += 2048) {
        uint4 y = lds128(a), z = lds128(a + 4096), u = lds128(a + 8192);
        const uint4 v = lds128(a + 12288);
        add4(y, z); add4(u, v); add4(y, u);
        sts128(a, y.x, y.y, y.z, y.w);
      }
      uint4* gp = G->xs + 256 * bid + (sa - base >> 4);
      q[0] = ld_relaxed128(gp - D_ * 256);
      q[1] = ld_relaxed128(gp - D_ * 256 + 128);
      mbar_wait(BAR(B_MR));
      e_round<2>(G, base, sa, gp, q, 0, (P.eseq >> 4 & 15) - 1, w, tag, epoch);
#pragma unroll 1
      for (int g = 0; g < P.st2; g++) {
        mbar_wait(BAR(B_WM + g));
        mod_gemv<5>(G, OFF_WM + WSLOT * g, (P.gt >> 8 * g & 255) + (blockIdx.x >> 3), blockIdx.x & 7, w, threadIdx.x & 31, epoch & 1);
        arrive1(BAR(B_G + g));
      }
#pragma unroll 1
      for (uint32_t seq = P.eseq >> 4; seq; seq >>= 4) e_round<0>(G, base, sa, gp, q, (seq & 15) - 1, (seq >> 4 & 15) - 1, w, tag, epoch);
    }
    int h, j, r;
    ffn_role(h, j, r);
    arrive1(BAR(B_ED));
    {
      REGION_IDS;
      float s0 = 0.f, q0 = 0.f, s1 = 0.f, q1 = 0.f;
#pragma unroll 1
      for (int c = 2; c < 5; c++) {
        const uint32_t buf = base + OFF_SX + 4096 * (c - 2), b = BAR(B_SX + c);
        uint32_t x[8];
#pragma unroll 1
        for (int it = 0; it < SPIN_LIMIT; it++) {
          mbar_wait(b, it & 1);
#pragma unroll
          for (int i = 0; i < 8; i++) x[i] = lds32(buf + 1024 * w + 4 * lane + 128 * i);
          if (bar_all(3, (lane & 7) || min(min(min(x[0], x[1]), min(x[2], x[3])), min(min(x[4], x[5]), min(x[6], x[7]))))) break;
          if (w == 0 && elect()) { mbar_expect_tx(b, 4096); tma2d(buf, &maps.x1s, 128 * r + 64 * h, D_ * (epoch & 1) + 128 * c + 32 * j, b); }
        }
#pragma unroll
        for (int i = 0; i < 8; i++) { const float lo = bf_lo(x[i]), hi = bf_hi(x[i]); s0 += lo; q0 = fmaf(lo, lo, q0); s1 += hi; q1 = fmaf(hi, hi, q1); }
      }
      sts128(base + OFF_MR + 1024 * w + 16 * lane, __float_as_uint(s0), __float_as_uint(q0), __float_as_uint(s1), __float_as_uint(q1));
      arrive1(BAR(B_S2));
    }
    {
      REGION_IDS;
      const uint32_t* sp = &G->st2[2 * r + (h ^ (w >> 1))][0][2 * (i0 & 63)];
      uint2 x[4];
      int it;
#pragma unroll 1
      for (it = 0; it < SPIN_LIMIT; it++) {
        mbar_wait(BAR(B_BX), it & 1);
        uint32_t y = 0;
#pragma unroll
        for (int k = 0; k < 3; k++) y |= lds32(base + OFF_BX + 32 * i0 + 4096 * k) ^ epoch;
        if (bar_all(3, !(y & 1))) break;
        if (w == 0 && elect()) { mbar_expect_tx(BAR(B_BX), 12288); bulk_load(base + OFF_BX, G->uv[4 * h + j], 12288, BAR(B_BX)); }
      }
      it = 0;
#pragma unroll 1
      do {
#pragma unroll
        for (int k = 0; k < 4; k++) x[k] = ld_relaxed64(sp + 128 * k);
      } while (__any_sync(~0u, ((x[0].x ^ epoch) | (x[1].x ^ epoch) | (x[2].x ^ epoch) | (x[3].x ^ epoch)) & 1) && ++it < SPIN_LIMIT);
      float m, sd;
      ln_final((__uint_as_float(x[0].x) + __uint_as_float(x[1].x)) + (__uint_as_float(x[2].x) + __uint_as_float(x[3].x)),
               (__uint_as_float(x[0].y) + __uint_as_float(x[1].y)) + (__uint_as_float(x[2].y) + __uint_as_float(x[3].y)), m, sd);
      const uint32_t e = pack_bf16(-m, sd);
      sts128(base + OFF_AX + 16 * i0, e, e, e, e);
      sts32(base + OFF_RT + 4 * i0, __float_as_uint(rcpf(sd)));
      fence_async_smem();
      arrive1(BAR(B_EXT));
      {
        uint2 g0, g1;
        int it = 0;
#pragma unroll 1
        do {
          g0 = ld_relaxed64(&G->modv[1][128 * j + i0]);
          g1 = ld_relaxed64(&G->modv[1][512 + 32 * j + lane]);
        } while (__any_sync(~0u, ((g0.x ^ epoch) | (g0.y ^ epoch) | (g1.x ^ epoch) | (g1.y ^ epoch)) & 1) && ++it < SPIN_LIMIT);
        const uint32_t a = base + OFF_GB + 40 * (lane & 6) + 2 * (lane & 1) + (lane >> 3) * 4;
        asm volatile("st.shared.u16 [%0], %1; st.shared.u16 [%2], %3;" ::"r"(a + 16 * (w ^ (j & 1))), "h"((uint16_t)(mod_sum(g0) >> 16)), "r"(a + 64), "h"((uint16_t)(mod_sum(g1) >> 16)) : "memory");
        arrive1(BAR(B_GB));
      }
      const int id = 16 * r + 4 * h + ((j + 1 + w) & 3);
#pragma unroll 1
      for (int q = w == 3 ? 3 : 0; q < 3; q++) {
        const int m = 3 * q + w;
        const uint4* src = G->hh + id * 1536 + 512 * q;
        it = 0;
#pragma unroll 1
        while (__any_sync(~0u, ld_relaxed32(&G->hhf[8 * id + 64 * (lane & 1) + q]) != 4 * epoch) && ++it < SPIN_LIMIT);
        mbar_wait(BAR(P.hid[2][m]));
        if (elect()) {
          bulk_load(base + (P.hid[h][m] & ~15), src, UNIT, BAR(B_FULL + 33 + m));
          bulk_load(base + (P.hid[h ^ 1][m] & ~15), src + 8 * 1536, UNIT, BAR(B_FULL + 33 + m));
        }
      }
    }
  } else {
    asm volatile("setmaxnreg.dec.sync.aligned.u32 24;");
    if (w >= 2) {
      LAUNCHES;
      uint32_t epoch;
      {
        REGION_IDS;
        uint32_t dv;
        asm volatile("ld.global.nc.u16 %0, [%1];" : "=r"(dv) : "l"(P.ssmd + 128 * (lane & 7) % D_ + bid));
        if (lane < 5) sts128(base + tab(T_F, lane) + (w & 1) * (F_O - F_E) + F_E - 16, 0, 0, 0, 0);
        epoch = EPOCH;
        __syncwarp();
#pragma unroll 1
        for (int c = 0; c < 5; c++) {
          const float d = i0 == 64 ? bf_lo(dv) : 0.f;
          dv = __shfl_down_sync(~0u, dv, 1);
          const uint32_t a = base + tab(T_F, c) + 16 * (i0 - 64);
          mbar_wait(BAR(B_FRAW + c));
#pragma unroll
          for (int k = 0; k < 4; k++) {
            uint4 x = lds128(a + F_E + 1024 * k);
            const uint32_t pv = lds32(a + F_E - 4 + 1024 * k);
            if (k == 0) { x.x = pack_bf16(bf_lo(x.x) + d, bf_hi(x.x)); sts32(a + F_E, x.x); }
            sts128(a + F_O + 1024 * k, __byte_perm(pv, x.x, 0x5432), __byte_perm(x.x, x.y, 0x5432), __byte_perm(x.y, x.z, 0x5432), __byte_perm(x.z, x.w, 0x5432));
          }
          __syncwarp();
          if (elect()) mbar_arrive2(BAR(B_FRDY + c));
          if (c == 0 && w == 3) {
#pragma unroll 1
            for (int k = 0; k < 13; k++) prefetch_map(&maps.w1a + k);
          }
        }
      }
      REGION_IDS;
      int h, j, r;
      ffn_role(h, j, r);
      cluster_wait();
      if (w == 2) {
        const unsigned* fp = G->xsh[lane < 10 ? lane >> 1 : 0][(r & 6) + (lane & 1)];
        uint32_t rdy = 0;
        mbar_wait(BAR(B_SC + 4));
#pragma unroll 1
        for (int e = 0; e < 14; e++) {
          const uint32_t x = P.adep[e], n = x >> 21 & 15, s = base + (x >> 25 << 13), b = BAR(B_FULL + (x >> 16 & 31));
          mbar_wait(BAR(opaque(x & 255)));
          mbar_wait(BAR(opaque(x >> 8 & 255)));
#pragma unroll 1
          for (int it = 0; !(rdy >> n & 1) && it < SPIN_LIMIT; it++) rdy = __ballot_sync(~0u, ld_relaxed32(fp) == 64 * epoch);
          if (elect()) {
            tma2d(s, &maps.xs, 128 * r + 64 * h, 64 * n, b);
            tma2d(s + UNIT, &maps.xs, 128 * r + 64 - 64 * h, 64 * n, b);
          }
        }
#pragma unroll 1
        for (int v = 0; v < 12; v++) {
          const int q = v * 11 >> 5, e = v - 3 * q, k32 = 24 * h + (q ? 6 * ((j + 1 + e) & 3) + 2 * q - 2 : 6 * j + 2 * e);
          const uint2 x = P.w2t[v];
          mbar_wait(BAR(x.y));
          if (elect()) {
            mbar_expect_tx(BAR(B_FULL + 30 + v), q ? W2TILE + 2 * UNIT : W2TILE);
#pragma unroll
            for (int k = 0; k < 3; k++) tma5d(base - DB + 16 * (x.x & 0xFFFF) + UNIT * k, &maps.w2a + (q > 0), k < 2 ? 128 * j + 64 * k : 512 + 32 * (j & 2), k32, BAR(B_FULL + 30 + v));
          }
        }
      } else {
        float s0 = 0.f, q0 = 0.f, s1 = 0.f, q1 = 0.f;
        uint32_t nl = 0, np = 0, ph = 0;
#pragma unroll 1
        for (uint32_t seq = P.seq2; seq > 1; seq >>= 1) {
          const uint32_t c = seq & 1 ? np : nl, buf = base + OFF_SX + 4096 * (c < 4 ? c & 1 : 2), b = BAR(opaque(B_SX + c));
          int it = 0;
          if (seq & 1) {
            mbar_wait(b, ph >> c & 1);
            ph ^= 1 << c;
            const uint32_t a = buf + 32 * lane;
            if (__all_sync(~0u, min(min(lds32(a), lds32(a + 1024)), min(lds32(a + 2048), lds32(a + 3072)))) || ph > SPIN_LIMIT) {
#pragma unroll 1
              for (uint32_t o = buf + 4 * lane; o < buf + 4096; o += 1024) {
                uint32_t x[8];
#pragma unroll
                for (int i = 0; i < 8; i++) x[i] = lds32(o + 128 * i);
#pragma unroll
                for (int i = 0; i < 8; i++) { const float lo = bf_lo(x[i]), hi = bf_hi(x[i]); s0 += lo; q0 = fmaf(lo, lo, q0); s1 += hi; q1 = fmaf(hi, hi, q1); }
              }
              np++;
              continue;
            }
            ph += 4;
            seq = 2 * seq + 1;
          } else {
#pragma unroll 1
            while (__any_sync(~0u, ld_relaxed32(G->xsh[c][(r & 6) + (j >> 1)]) != 64 * epoch) && ++it < SPIN_LIMIT);
            if (++nl == 5) { mbar_wait(BAR(B_PEMPTY + 4)); mbar_wait(BAR(B_ED + 1)); }
          }
          if (elect()) { mbar_expect_tx(b, 4096); tma2d(buf, &maps.x1s, 128 * r + 64 * h, D_ * (epoch & 1) + 128 * c + 32 * j, b); }
        }
        mbar_wait(BAR(B_S2));
#pragma unroll
        for (int k = 0; k < 4; k++) {
          const uint4 x = lds128(base + OFF_MR + 1024 * k + 16 * lane);
          s0 += __uint_as_float(x.x); q0 += __uint_as_float(x.y); s1 += __uint_as_float(x.z); q1 += __uint_as_float(x.w);
        }
        asm volatile("{.reg .b128 t, x; .reg .b64 a, b; mov.b64 a, {%1,%2}; mov.b64 b, {%3,%4}; mov.b128 x, {a,b}; atom.relaxed.gpu.global.exch.b128 t, [%0], x;}"
                     ::"l"(&G->st2[2 * r + h][j][4 * lane]), "r"((__float_as_uint(s0) & ~1u) | (epoch & 1)), "f"(q0), "r"((__float_as_uint(s1) & ~1u) | (epoch & 1)), "f"(q1) : "memory");
        uint4* z = G->x1[~epoch & 1] + 1280 * bid + lane;
#pragma unroll 1
        for (int k = 0; k < 40; k++) st_relaxed128(z + 32 * k, 0, 0, 0, 0);
      }
    } else if (w == 0) {
      LAUNCHES;
      uint32_t epoch;
      {
        REGION_IDS;
        const unsigned* hp = G->hint[0][4 * (bid >> 6) + (bid >> 3 & 3)];
        uint32_t v = ld_relaxed32(hp + 256 * min(lane, 5));
        if (lane < 3) sts128(base + tab(T_X, lane) + 4096, 0, 0, 0, 0);
        if (lane && lane < B_XR) mbar_expect_tx(BAR(lane), lane < B_FRAW ? 9728 : lane >= B_WM ? 10240 : 4096);
        epoch = EPOCH;
        fence_async_smem();
        const uint32_t rdy = __ballot_sync(~0u, v == epoch << 6) & 31;
        uint32_t nx = 0, mr = 1;
#pragma unroll 1
        for (int it = 0; (nx < 5 || mr) && it < SPIN_LIMIT; it++) {
          const bool second = nx == 5 || (lane && mr && nx >= P.mq);
          if (!(rdy >> nx & 1)) v = ld_relaxed32(hp + 256 * (second ? 5 : nx));
          const uint32_t ok = __ballot_sync(~0u, v == epoch << (second ? 7 : 6)) | (rdy >> nx & 1);
          if (nx < 5 && (ok & 1)) {
            if (nx >= 3) mbar_wait(BAR(B_PFULL - 3 + nx));
            if (elect()) { mbar_expect_tx(BAR(B_XR + nx), 4096); bulk_load(base + tab(T_X, nx), G->xr + (128 * nx + bid) * 256, 4096, BAR(B_XR + nx)); }
          }
          if (mr && (nx == 5 || nx >= P.mq) && (ok & 2) && !(rdy >> nx & 1)) {
            if (elect()) { mbar_expect_tx(BAR(B_MR), 8192); bulk_load(base + OFF_MR, G->st1, 8192, BAR(B_MR)); mbar_arrive(BAR(B_QTOK)); }
            mr = 0;
          }
          if (nx < 5) nx += ok & 1;
        }
        mod_fetch(G, base, epoch, P.m8, 2, 5);
      }
      REGION_IDS;
      int h, j, r;
      ffn_role(h, j, r);
      cluster_wait();
      if (elect()) mbar_expect_tx(BAR(B_UVB), 30720);
#pragma unroll 1
      for (int k = 0; k < 5; k++) {
        mbar_wait(BAR(opaque(B_EMPTY + nib(P.uvd, k))));
        if (elect()) tma3d(base + OFF_UV + 6144 * k, &maps.w1u + (r & 1), 0, 40 * (r & 14) + 16 * k, 3 * (4 * h + j), BAR(B_UVB));
      }
      mbar_wait(BAR(B_G));
      mbar_wait(BAR(B_G + (P.gt >> 16)));
      {
        const uint2* mp = &G->modv[lane & 4 ? 0 : 2][40 * (r & 14) + (lane & 24) + 2 * (lane & 3)];
        uint4 v[3];
        int it = 0;
#pragma unroll 1
        do {
          v[0] = ld_relaxed128(mp); v[1] = ld_relaxed128(mp + 32); v[2] = ld_relaxed128(mp + 64 - (lane & 16));
        } while (__any_sync(~0u, ((v[0].x ^ epoch) | (v[0].y ^ epoch) | (v[0].z ^ epoch) | (v[0].w ^ epoch) | (v[1].x ^ epoch) | (v[1].y ^ epoch) | (v[1].z ^ epoch) | (v[1].w ^ epoch) |
                                  (v[2].x ^ epoch) | (v[2].y ^ epoch) | (v[2].z ^ epoch) | (v[2].w ^ epoch)) & 1) && ++it < SPIN_LIMIT);
#pragma unroll
        for (int i = 0; i < 3; i++)
          sts32(base + OFF_CO + 128 * i + 4 * lane, badd2(pack_bf16(__uint_as_float(v[i].x) + __uint_as_float(v[i].y), __uint_as_float(v[i].z) + __uint_as_float(v[i].w)), lane & 4 ? 0 : 0x3F803F80u));
      }
      fence_async_smem();
      arrive1(BAR(B_CO));
      ffn_role(h, j, r);
      mbar_wait(BAR(B_ED));
      mbar_wait(BAR(B_ED + 1));
      asm volatile("fence.acq_rel.gpu;" ::: "memory");
      if (lane < 8) red_hint(G->hint[7][lane]);
      unsigned x;
      int it = 0;
#pragma unroll 1
      while (__any_sync(~0u, ld_relaxed32(G->hint[8][4 * h + j]) != 128 * epoch) && ++it < SPIN_LIMIT);
      if (elect()) { mbar_expect_tx(BAR(B_BX), 12288); bulk_load(base + OFF_BX, G->uv[4 * h + j], 12288, BAR(B_BX)); }
      it = 0;
#pragma unroll 1
      do { asm volatile("ld.acquire.gpu.global.u32 %0, [%1];" : "=r"(x) : "l"(G->hint[7][bid >> 4]) : "memory"); } while (__any_sync(~0u, x != 128 * epoch) && ++it < SPIN_LIMIT);
      fence_async_all();
      const int ch = D_ * (epoch & 1);
      mbar_wait(BAR(P.xdep));
      if (elect()) {
        mbar_expect_tx(BAR(B_FULL + 42), 20480);
#pragma unroll
        for (int k = 0; k < 4; k++) tma2d(base + x1_at(k), &maps.x1b, 128 * r + 64 * h, ch + 128 * j + 32 * (k ^ (j & 1)), BAR(B_FULL + 42));
        tma2d(base + x1_at(4), &maps.x1b, 128 * r + 64 * h, ch + 512 + 32 * j, BAR(B_FULL + 42));
        mbar_expect_tx(BAR(B_FULL + 1), 8192); mbar_expect_tx(BAR(B_FULL + 3), 8192); mbar_expect_tx(BAR(B_FULL + 5), 4096);
      }
      mbar_wait(BAR(B_EMPTY + 37));
      if (elect()) mbar_arrive_remote(mapa(BAR(B_XFREE), h ^ 1));
    } else {
      LAUNCHES;
      {
        REGION_IDS;
        loads<EARLY, NL>(maps, base, P.gt);
      }
      cluster_wait();
      int h, j, r;
      ffn_role(h, j, r);
      mbar_wait(BAR(B_QTD));
      mbar_wait(BAR(B_STD));
      mbar_wait(BAR(B_SC));
      mbar_wait(BAR(B_SC + 2));
      mbar_wait(BAR(B_FL));
#pragma unroll 1
      for (int u = 0; u < 30; u++) {
        if (u == P.mpos) mod_fetch(G, base, EPOCH, P.m8, 1, 2);
        if (u < 6) wait_clock(t_start + P.wt0 + u * P.wpace);
        const uint32_t x = P.wdep[u], b = x >> 8 & 1;
        uint32_t s = base + OFF_R + WSLOT * (x >> 9 & 7), f = BAR(B_FULL + (b ? u : u & ~1)), n = x & 0xC000, y = x >> 16, z = 3 * (4 * h + j) + 2 * b;
        const CUtensorMap* m = &maps.w1a + 5 * b;
        asm volatile("{.reg .pred p, q; .reg .b32 i, t; .reg .b64 m; mov.u32 i, 0; add.u32 t, %0, 8192; add.u64 m, %1, 128; elect.sync _|q, 0xffffffff;"
                     "W: mbarrier.try_wait.parity.shared::cta.b64 p, [%6], 0; @p bra.uni D; add.u32 i, i, 1; setp.lt.u32 p, i, %7; @p bra.uni W; D:"
                     "setp.ne.and.u32 p, %3, 0, q; @p mbarrier.arrive.expect_tx.shared::cta.b64 _, [%2], %3;"
                     "@q cp.async.bulk.tensor.3d.shared::cluster.global.mbarrier::complete_tx::bytes [%0], [%1, {0,%4,%5}], [%2];"
                     "@q cp.async.bulk.tensor.3d.shared::cluster.global.mbarrier::complete_tx::bytes [t], [m, {0,%4,%5}], [%2];}"
                     ::"r"(s), "l"(m), "r"(f), "r"(n), "r"(y), "r"(z), "r"(BAR(opaque(x & 255))), "n"(SPIN_LIMIT) : "memory");
      }
    }
  }
}

typedef CUresult (*EncFn)(CUtensorMap*, CUtensorMapDataType, cuuint32_t, void*, const cuuint64_t*, const cuuint64_t*, const cuuint32_t*,
                          const cuuint32_t*, CUtensorMapInterleave, CUtensorMapSwizzle, CUtensorMapL2promotion, CUtensorMapFloatOOBfill);
static int enc_err = 0;
static void enc(EncFn fn, CUtensorMap* m, const void* p, int rank, const cuuint64_t* gd, const cuuint64_t* gs, const cuuint32_t* bd, CUtensorMapSwizzle sw) {
  cuuint32_t es[5] = {1, 1, 1, 1, 1};
  enc_err = 2 * enc_err + (fn(m, CU_TENSOR_MAP_DATA_TYPE_BFLOAT16, rank, (void*)p, gd, gs, bd, es, CU_TENSOR_MAP_INTERLEAVE_NONE, sw,
                              CU_TENSOR_MAP_L2_PROMOTION_L2_128B, CU_TENSOR_MAP_FLOAT_OOB_FILL_NONE) != CUDA_SUCCESS);
}

extern "C" void kernel_launch(void* const* d_in, const int* in_sizes, int n_in, void* d_out, int out_size) {
  const bf16 *q = (const bf16*)d_in[0], *k = (const bf16*)d_in[1], *v = (const bf16*)d_in[2], *shift = (const bf16*)d_in[3],
             *ssmk = (const bf16*)d_in[4], *ssmd = (const bf16*)d_in[5], *w1 = (const bf16*)d_in[7], *w3 = (const bf16*)d_in[8],
             *w2 = (const bf16*)d_in[9], *c = (const bf16*)d_in[10], *wmod = (const bf16*)d_in[11];
  EncFn fn = nullptr;
  cudaDriverEntryPointQueryResult qr;
  cudaGetDriverEntryPoint("cuTensorMapEncodeTiled", (void**)&fn, cudaEnableDefault, &qr);
  Scratch* pg;
  cudaGetSymbolAddress((void**)&pg, g_s);
  Maps maps;
  enc_err = 0;
  const CUtensorMapSwizzle S128 = CU_TENSOR_MAP_SWIZZLE_128B;
  { cuuint64_t gd[3] = {D_, S_ / 8, 8}, gs[2] = {D_ * 16, D_ * 2}; cuuint32_t b[3] = {64, 4, 8};
    enc(fn, &maps.km, k, 3, gd, gs, b, S128);
    enc(fn, &maps.v, v, 3, gd, gs, b, S128);
    enc(fn, &maps.q, q, 3, gd, gs, b, S128);
    b[2] = 3;
    enc(fn, &maps.kh, k, 3, gd, gs, b, S128); }
  { cuuint64_t gd[3] = {256, 8, D_}, gs[2] = {512, 4096}; cuuint32_t b[3] = {256, 8, 1};
    enc(fn, &maps.fm, ssmk, 3, gd, gs, b, CU_TENSOR_MAP_SWIZZLE_NONE); }
  { cuuint64_t gd[3] = {256, 2, 5}, gs[2] = {512, 1024}; cuuint32_t b[3] = {256, 1, 5};
    enc(fn, &maps.tap, shift, 3, gd, gs, b, CU_TENSOR_MAP_SWIZZLE_NONE); }
  { cuuint64_t gd[3] = {6 * D_, D_, 1}, gs[2] = {6 * D_ * 2, 6 * D_ * 2 * D_}; cuuint32_t b[3] = {64, 64, 1};
    enc(fn, &maps.wm, wmod, 3, gd, gs, b, S128);
    b[1] = 80;
    enc(fn, &maps.wmp, wmod, 3, gd, gs, b, S128); }
  { cuuint64_t gd[3] = {64, D_, F_ / 64}, gs[2] = {F_ * 2, 128}; cuuint32_t b[3] = {64, 16, 3};
    enc(fn, &maps.w1u, w1, 3, gd, gs, b, S128);
    enc(fn, &maps.w3u, w3, 3, gd, gs, b, S128);
    b[1] = 32; b[2] = 2;
    enc(fn, &maps.w1a, w1, 3, gd, gs, b, S128);
    enc(fn, &maps.w3a, w3, 3, gd, gs, b, S128);
    b[1] = 64; b[2] = 1;
    enc(fn, &maps.w1b, w1, 3, gd, gs, b, S128);
    enc(fn, &maps.w3b, w3, 3, gd, gs, b, S128); }
  { cuuint64_t gd[2] = {S_, D_}, gs[1] = {S_ * 2}; cuuint32_t b1[2] = {64, 64}, b2[2] = {64, 32};
    enc(fn, &maps.xs, pg->xs, 2, gd, gs, b1, S128);
    gd[1] = 2 * D_;
    enc(fn, &maps.x1b, pg->x1, 2, gd, gs, b2, S128);
    enc(fn, &maps.x1s, pg->x1, 2, gd, gs, b2, CU_TENSOR_MAP_SWIZZLE_NONE); }
  { cuuint64_t gd[5] = {D_, 2, 4, 4, 48}, gs[4] = {D_ * 2, D_ * 4, D_ * 16, D_ * 64}; cuuint32_t b[5] = {64, 2, 4, 4, 2};
    enc(fn, &maps.w2a, w2, 5, gd, gs, b, S128);
    gs[1] = D_ * 16; gs[2] = D_ * 4;
    enc(fn, &maps.w2b, w2, 5, gd, gs, b, S128); }
  { cuuint64_t gd[2] = {D_, S_}, gs[1] = {D_ * 2}; cuuint32_t b1[2] = {64, 16}, b2[2] = {32, 16};
    enc(fn, &maps.outa, d_out, 2, gd, gs, b1, S128);
    enc(fn, &maps.outb, d_out, 2, gd, gs, b2, CU_TENSOR_MAP_SWIZZLE_64B); }
  if (enc_err) return;
  cudaFuncSetAttribute(k_fused<0>, cudaFuncAttributeMaxDynamicSharedMemorySize, SMEM_BYTES);
  cudaFuncSetAttribute(k_fused<128>, cudaFuncAttributeMaxDynamicSharedMemorySize, SMEM_BYTES);
  cudaLaunchConfig_t cfg = {132, 512, SMEM_BYTES};
  cudaLaunchAttribute at = {cudaLaunchAttributeClusterDimension};
  at.val.clusterDim.x = 2; at.val.clusterDim.y = at.val.clusterDim.z = 1;
  cfg.attrs = &at; cfg.numAttrs = 1;
  int nc = 0;
  cudaOccupancyMaxActiveClusters(&nc, k_fused<0>, &cfg);
  Ptrs P = {c, ssmd, pg, {0x676360, 0x57246209}, 0, 32, 5, 0, 0x0, 2, 0, 0, 0, 0, 0, B_EMPTY + 32, 0 | 0 << 16, 0, {}, 0x54321, 0x94, 0x55311, 1, 11600, 900, 1.f};
  const char* sched = "k11v11f01q01q11q21q31q41k21v21f11k31v31f21k41v41f31w01f41n00n00n00n00n00";
  const char* ho = "abcdefghijklmnopqrstuvwxyz{|}~";
  int t = 300, pace = 300, ta = 16, tb = 0, win = 16;
  P.gt = ta | tb << 8 | !!tb << 16;
  P.m8 = 3 << ta / 8 | (tb ? 3 << tb / 8 : 0);
  memset(P.hl, 255, sizeof(P.hl));
  for (int k = 0, n = 0; k < 30; k++) {
    const int i = ho[k] - 'a';
    if (i >= 20 || !(P.m8 >> i / 4 & 1)) ((uint8_t*)P.hl)[n++] = i;
  }
  for (int e = 0; e < NE - 1 && sched[3 * e] != 'n'; e++) {
    const char x = sched[3 * e];
    const int r = sched[3 * e + 1] - '0', kind = x == 'k' ? 0 : x == 'v' ? 1 : x == 'q' ? 2 : x == 'f' ? 3 : 4;
    if (e < PRE && (x != PRES[2 * e] || sched[3 * e + 1] != PRES[2 * e + 1])) return;
    t += (sched[3 * e + 2] - '0') * pace / 4;
    P.sched[e] = {(uint32_t)t, kind < 2 ? tab(T_KV, r) + kind * KV_V : kind == 2 ? OFF_Q + 4096 * r : kind == 3 ? tab(T_F, r) + F_E : OFF_WM + WSLOT * r,
                  OFF_BAR + 8u * (r + (kind < 2 ? B_KV : kind == 2 ? B_Q : kind == 3 ? B_FRAW : B_WM)), 128u * kind, kind < 4 ? 128u * r : r ? tb : ta};
  }
  for (int e = 0; P.sched[e].t; e++) {
    auto size = [&](int i) { return i < 0 ? 8 : sched[3 * i] == 'w' ? 10 : 4; };
    int i = e, sum = 0;
    while (i >= -1 && sum + size(i) <= win) sum += size(i--);
    P.sched[e].gate = P.sched[e].bar; P.sched[e].par = 1;
    for (; i >= -1; i--) {
      const uint32_t b = i < 0 ? OFF_BAR + 8 * B_KV : P.sched[i].bar;
      bool ok = i < e;
      for (int k = e; P.sched[k].t; k++) ok = ok && P.sched[k].bar != b;
      if (ok) { P.sched[e].gate = b; P.sched[e].par = 0; break; }
    }
  }
  for (int u = 0; u < 30; u++) P.wdep[u] = (u < 4 ? B_FL + 1 + u / 3 : u < 6 ? B_G + (u == 5 && tb) : B_EMPTY + (u < 26 ? (u - 6) | 1 : u - 6)) | (u >= 20) << 8 | u % 6 << 9 | (u < 20 ? 3 * (~u & 1) : 1 + (u >= 26)) << 14 | (u < 20 ? 32 * u : 64 * (second(u - 20) % 10)) << 16;
  const int adep[14] = {B_PEMPTY, B_PEMPTY, B_PFULL + 4, B_PEMPTY + 1, B_PEMPTY + 2, B_EMPTY + 5, B_EMPTY + 7, B_PEMPTY + 3, B_EMPTY + 2 * UVS + 1, B_EMPTY + 2 * UVS + 1, B_EMPTY + 20, B_EMPTY + 21, B_EMPTY + 22, B_EMPTY + 23};
  const char *ad = "--*--df-jhvxwy", *wd = "55677:;<>?\?A", *hd = "679;;>?@A";
  for (int n = 0; n < 14; n++) P.adep[n] = adep[n] | (ad[n] == '-' ? adep[n] : ad[n] == '*' ? B_PFULL + 3 : B_EMPTY + ad[n] - 'a') << 8 | (n < 10 ? 2 * n : n + 16) << 16 | n % 10 << 21 | a_at(n) / UNIT << 25;
  for (int v = 0; v < 12; v++) P.w2t[v] = make_uint2(w2_desc(v), B_EMPTY + 20 + wd[v] - '0');
  for (int m = 0; m < 9; m++) { P.hid[0][m] = hid_at(m, 0) | m / 3 * 4 | (m % 3 + 1); P.hid[1][m] = hid_at(m, 1) | m / 3 * 4 | (m % 3 + 1); P.hid[2][m] = B_EMPTY + 20 + hd[m] - '0'; }
  if (nc < 66) k_fused<128><<<4, 512, SMEM_BYTES, cudaStreamPerThread>>>(P, maps);
  k_fused<0><<<nc < 66 ? 128 : 132, 512, SMEM_BYTES, cudaStreamPerThread>>>(P, maps);
}
```

```cpp
#include <cuda_runtime.h>
#include <cuda.h>
#include <cuda_bf16.h>
#include <stdint.h>
#include <stdlib.h>
#include <string.h>

typedef __nv_bfloat16 bf16;
constexpr int S_ = 2048, D_ = 640, F_ = 1536;

struct Scratch {
  uint32_t st1[2][1024];
  uint32_t st2[32][4][128];
  uint32_t modc[128][5][32];
  uint2 modv[3][D_];
  uint32_t uv[8][3072];
  unsigned hint[9][8][32];
  unsigned xsh[5][8][32], hhf[256 * 8], key[256];
  uint4 xr[D_ * 256];
  uint4 qt[D_ * 256];
  uint4 xs[D_ * 256];
  uint4 x1[2][D_ * 256];
  uint4 hh[32 * 8 * 1536];
};
__device__ __align__(1024) Scratch g_s;

__device__ __forceinline__ uint32_t smem_u32(const void* p) { return (uint32_t)__cvta_generic_to_shared(p); }
__device__ __forceinline__ void mbar_expect_tx(uint32_t b, uint32_t n) { asm volatile("mbarrier.arrive.expect_tx.shared::cta.b64 _, [%0], %1;" ::"r"(b), "r"(n) : "memory"); }
__device__ __forceinline__ void mbar_arrive(uint32_t b) { asm volatile("mbarrier.arrive.shared::cta.b64 _, [%0];" ::"r"(b) : "memory"); }
__device__ __forceinline__ void mbar_arrive2(uint32_t b) { asm volatile("mbarrier.arrive.shared::cta.b64 _, [%0], 2;" ::"r"(b) : "memory"); }
__device__ __forceinline__ uint32_t mapa(uint32_t a, uint32_t cta) { uint32_t r; asm volatile("mapa.shared::cluster.u32 %0, %1, %2;" : "=r"(r) : "r"(a), "r"(cta)); return r; }
__device__ __forceinline__ void mbar_arrive_remote(uint32_t rb) { asm volatile("mbarrier.arrive.shared::cluster.b64 _, [%0];" ::"r"(rb) : "memory"); }
constexpr int SPIN_LIMIT = 1 << 16;
template <int N> __device__ __forceinline__ void mbar_init(uint32_t b, uint32_t count) {
#pragma unroll
  for (int i = 0; i < N; i++) asm volatile("mbarrier.init.shared::cta.b64 [%0], %1;" ::"r"(b + 8 * i), "r"(count) : "memory");
}
__device__ __forceinline__ bool elect() { uint32_t p; asm volatile("{.reg .pred q; elect.sync _|q, 0xffffffff; selp.u32 %0, 1, 0, q;}" : "=r"(p)); return p; }
__device__ __forceinline__ void arrive1(uint32_t b) { __syncwarp(); if (elect()) mbar_arrive(b); }
__device__ __forceinline__ bool mbar_test(uint32_t b) {
  uint32_t ok;
  asm volatile("{.reg .pred p; mbarrier.test_wait.parity.shared::cta.b64 p, [%1], 0; selp.u32 %0,1,0,p;}" : "=r"(ok) : "r"(b) : "memory");
  return ok;
}
#define WAIT_LOOP(sem) "{.reg .pred p; mov.u32 %0, 0; W: mbarrier.try_wait.parity" sem ".shared::cta.b64 p, [%1], %2; @p bra.uni D; add.u32 %0, %0, 1; setp.lt.u32 p, %0, %3; @p bra.uni W; D:}"
__device__ __forceinline__ void mbar_wait(uint32_t b, uint32_t ph = 0) {
  int it;
  asm volatile(WAIT_LOOP("") : "=&r"(it) : "r"(b), "r"(ph), "n"(SPIN_LIMIT) : "memory");
}
__device__ __forceinline__ void mbar_wait_cluster(uint32_t b, uint32_t ph = 0) {
  int it;
  asm volatile(WAIT_LOOP(".acquire.cluster") : "=&r"(it) : "r"(b), "r"(ph), "n"(SPIN_LIMIT) : "memory");
}
__device__ __forceinline__ void wait_clock(uint32_t t) {
  asm volatile("{.reg .pred p; .reg .s32 d; W: mov.u32 d, %%clock; sub.s32 d, d, %0; setp.lt.s32 p, d, 0; @p bra.uni W;}" ::"r"(t) : "memory");
}
__device__ __forceinline__ void tma2d(uint32_t dst, const CUtensorMap* m, int c0, int c1, uint32_t bar) {
  asm volatile("cp.async.bulk.tensor.2d.shared::cluster.global.mbarrier::complete_tx::bytes [%0], [%1, {%3,%4}], [%2];" ::"r"(dst), "l"(m), "r"(bar), "r"(c0), "r"(c1) : "memory");
}
__device__ __forceinline__ void tma3d(uint32_t dst, const CUtensorMap* m, int c0, int c1, int c2, uint32_t bar) {
  asm volatile("cp.async.bulk.tensor.3d.shared::cluster.global.mbarrier::complete_tx::bytes [%0], [%1, {%3,%4,%5}], [%2];" ::"r"(dst), "l"(m), "r"(bar), "r"(c0), "r"(c1), "r"(c2) : "memory");
}
__device__ __forceinline__ void tma5d(uint32_t dst, const CUtensorMap* m, int c0, int c4, uint32_t bar) {
  asm volatile("cp.async.bulk.tensor.5d.shared::cluster.global.mbarrier::complete_tx::bytes [%0], [%1, {%4,%3,%3,%3,%5}], [%2];" ::"r"(dst), "l"(m), "r"(bar), "r"(0), "r"(c0), "r"(c4) : "memory");
}
__device__ __forceinline__ void tma2d_store(const CUtensorMap* m, int c0, int c1, uint32_t src) {
  asm volatile("cp.async.bulk.tensor.2d.global.shared::cta.bulk_group [%0, {%2,%3}], [%1];" ::"l"(m), "r"(src), "r"(c0), "r"(c1) : "memory");
}
__device__ __forceinline__ void bulk_load(uint32_t dst, const void* src, uint32_t bytes, uint32_t bar) {
  asm volatile("cp.async.bulk.shared::cluster.global.mbarrier::complete_tx::bytes [%0], [%1], %2, [%3];" ::"r"(dst), "l"(src), "r"(bytes), "r"(bar) : "memory");
}
__device__ __forceinline__ void prefetch_map(const CUtensorMap* m) { asm volatile("prefetch.tensormap [%0];" ::"l"(m) : "memory"); }
__device__ __forceinline__ void bulk_commit() { asm volatile("cp.async.bulk.commit_group;" ::: "memory"); }
__device__ __forceinline__ void bulk_wait_read() { asm volatile("cp.async.bulk.wait_group.read 0;" ::: "memory"); }
__device__ __forceinline__ void fence_async_smem() { asm volatile("fence.proxy.async.shared::cta;" ::: "memory"); }
__device__ __forceinline__ void fence_async_all() { asm volatile("fence.proxy.async.global;" ::: "memory"); }
__device__ __forceinline__ void named_bar(int id, int n) { asm volatile("bar.sync %0, %1;" ::"r"(id), "r"(n) : "memory"); }
__device__ __forceinline__ bool bar_all(int id, bool v) {
  uint32_t r;
  asm volatile("{.reg .pred p, q; setp.ne.u32 p, %2, 0; bar.red.and.pred q, %1, 128, p; selp.u32 %0, 1, 0, q;}" : "=r"(r) : "r"(id), "r"((uint32_t)v) : "memory");
  return __all_sync(~0u, r);
}
__device__ __forceinline__ void cluster_wait() { asm volatile("barrier.cluster.wait.aligned;" ::: "memory"); }
__device__ __forceinline__ void wg_fence() { asm volatile("wgmma.fence.sync.aligned;" ::: "memory"); }
__device__ __forceinline__ void wg_commit() { asm volatile("wgmma.commit_group.sync.aligned;" ::: "memory"); }
template <int N> __device__ __forceinline__ void wg_wait() { asm volatile("wgmma.wait_group.sync.aligned %0;" ::"n"(N) : "memory"); }
template <int N> __device__ __forceinline__ void fence_regs(float (&a)[N]) {
#pragma unroll
  for (int i = 0; i < N; i++) asm volatile("" : "+f"(a[i])::"memory");
}
__device__ __forceinline__ uint64_t mkdesc(uint32_t addr, uint32_t lbo, uint32_t sbo, uint32_t swz) {
  uint32_t lo = (addr >> 4) | ((lbo >> 4) << 16), hi = (sbo >> 4) | (swz << 30);
  return ((uint64_t)hi << 32) | lo;
}
__device__ __forceinline__ void stmatrix_x4(uint32_t a, uint32_t r0, uint32_t r1, uint32_t r2, uint32_t r3) {
  asm volatile("stmatrix.sync.aligned.m8n8.x4.shared.b16 [%0], {%1,%2,%3,%4};" ::"r"(a), "r"(r0), "r"(r1), "r"(r2), "r"(r3) : "memory");
}
__device__ __forceinline__ void stmatrix_x4_t(uint32_t a, uint32_t r0, uint32_t r1, uint32_t r2, uint32_t r3) {
  asm volatile("stmatrix.sync.aligned.m8n8.x4.trans.shared.b16 [%0], {%1,%2,%3,%4};" ::"r"(a), "r"(r0), "r"(r1), "r"(r2), "r"(r3) : "memory");
}
__device__ __forceinline__ void ldmatrix_x4_t(uint32_t* r, uint32_t a) {
  asm volatile("ldmatrix.sync.aligned.m8n8.x4.trans.shared.b16 {%0,%1,%2,%3}, [%4];" : "=r"(r[0]), "=r"(r[1]), "=r"(r[2]), "=r"(r[3]) : "r"(a) : "memory");
}
__device__ __forceinline__ uint32_t lds32(uint32_t a) { uint32_t v; asm volatile("ld.shared.b32 %0, [%1];" : "=r"(v) : "r"(a) : "memory"); return v; }
__device__ __forceinline__ uint2 lds64(uint32_t a) { uint2 v; asm volatile("ld.shared.v2.b32 {%0,%1}, [%2];" : "=r"(v.x), "=r"(v.y) : "r"(a) : "memory"); return v; }
__device__ __forceinline__ uint4 lds128(uint32_t a) { uint4 v; asm volatile("ld.shared.v4.b32 {%0,%1,%2,%3}, [%4];" : "=r"(v.x), "=r"(v.y), "=r"(v.z), "=r"(v.w) : "r"(a) : "memory"); return v; }
__device__ __forceinline__ void sts32(uint32_t a, uint32_t v) { asm volatile("st.shared.b32 [%0], %1;" ::"r"(a), "r"(v) : "memory"); }
__device__ __forceinline__ void sts64(uint32_t a, uint32_t x, uint32_t y) { asm volatile("st.shared.v2.b32 [%0], {%1,%2};" ::"r"(a), "r"(x), "r"(y) : "memory"); }
__device__ __forceinline__ void sts128(uint32_t a, uint32_t x, uint32_t y, uint32_t z, uint32_t w) { asm volatile("st.shared.v4.b32 [%0], {%1,%2,%3,%4};" ::"r"(a), "r"(x), "r"(y), "r"(z), "r"(w) : "memory"); }
__device__ __forceinline__ uint4 ld_relaxed128(const void* p) { uint4 v; asm volatile("ld.relaxed.gpu.global.v4.u32 {%0,%1,%2,%3}, [%4];" : "=r"(v.x), "=r"(v.y), "=r"(v.z), "=r"(v.w) : "l"(p) : "memory"); return v; }
__device__ __forceinline__ uint2 ld_relaxed64(const void* p) { uint2 v; asm volatile("ld.relaxed.gpu.global.v2.u32 {%0,%1}, [%2];" : "=r"(v.x), "=r"(v.y) : "l"(p) : "memory"); return v; }
__device__ __forceinline__ uint32_t ld_relaxed32(const void* p) { uint32_t v; asm volatile("ld.relaxed.gpu.global.u32 %0, [%1];" : "=r"(v) : "l"(p) : "memory"); return v; }
__device__ __forceinline__ void st_relaxed128(void* p, uint32_t x, uint32_t y, uint32_t z, uint32_t w) { asm volatile("st.relaxed.gpu.global.v4.u32 [%0], {%1,%2,%3,%4};" ::"l"(p), "r"(x), "r"(y), "r"(z), "r"(w) : "memory"); }
__device__ __forceinline__ void st_relaxed32(void* p, uint32_t x) { asm volatile("st.relaxed.gpu.global.u32 [%0], %1;" ::"l"(p), "r"(x) : "memory"); }
__device__ __forceinline__ void red_hint(unsigned* p) { asm volatile("red.relaxed.gpu.global.add.u32 [%0], 1;" ::"l"(p) : "memory"); }
__device__ __forceinline__ void publish(uint32_t* p, uint32_t x) { asm volatile("{.reg .b32 t; atom.relaxed.gpu.global.exch.b32 t, [%0], %1;}" ::"l"(p), "r"(x) : "memory"); }
__device__ __forceinline__ uint32_t ldg32(const void* p) { uint32_t v; asm volatile("ld.global.nc.L1::no_allocate.b32 %0, [%1];" : "=r"(v) : "l"(p)); return v; }
__device__ __forceinline__ uint32_t pack_bf16(float lo, float hi) { uint32_t r; asm("cvt.rn.bf16x2.f32 %0, %1, %2;" : "=r"(r) : "f"(hi), "f"(lo)); return r; }
__device__ __forceinline__ float bf_lo(uint32_t v) { return __uint_as_float(v << 16); }
__device__ __forceinline__ float bf_hi(uint32_t v) { return __uint_as_float(v & 0xFFFF0000u); }
__device__ __forceinline__ uint32_t bmul2(uint32_t a, uint32_t b) { uint32_t r; asm("mul.rn.bf16x2 %0, %1, %2;" : "=r"(r) : "r"(a), "r"(b)); return r; }
__device__ __forceinline__ uint32_t badd2(uint32_t a, uint32_t b) { uint32_t r; asm("add.rn.bf16x2 %0, %1, %2;" : "=r"(r) : "r"(a), "r"(b)); return r; }
__device__ __forceinline__ uint32_t bfma2(uint32_t a, uint32_t b, uint32_t c) { uint32_t r; asm("fma.rn.bf16x2 %0, %1, %2, %3;" : "=r"(r) : "r"(a), "r"(b), "r"(c)); return r; }
__device__ __forceinline__ uint32_t set_tag(uint32_t x, uint32_t mask, uint32_t e) { uint32_t r; asm("lop3.b32 %0, %1, %2, %3, 0xB8;" : "=r"(r) : "r"(x), "r"(mask), "r"(e)); return r; }
__device__ __forceinline__ uint32_t opaque(uint32_t x) { asm volatile("" : "+r"(x)); return x; }
__device__ __forceinline__ float rbf(float x) { return __bfloat162float(__float2bfloat16(x)); }
__device__ __forceinline__ float silu_f(float x) {
  float e, r;
  asm("ex2.approx.ftz.f32 %0, %1;" : "=f"(e) : "f"(x * -1.4426950408889634f));
  asm("rcp.approx.ftz.f32 %0, %1;" : "=f"(r) : "f"(1.f + e));
  return x * r;
}
__device__ __forceinline__ float silu2(float g, float a, float b) {
  float t;
  asm("tanh.approx.f32 %0, %1;" : "=f"(t) : "f"(g * a));
  return fmaf(g * b, t, g * b);
}
__device__ __forceinline__ void pin(int off, uint32_t x) { asm volatile("{.reg .pred p; setp.lt.s32 p, %0, 0; @p st.shared.b32 [%0], %1;}" ::"r"(off), "r"(x) : "memory"); }
__device__ __forceinline__ void pin4(int off, const uint32_t* x) { asm volatile("{.reg .pred p; setp.lt.s32 p, %0, 0; @p st.shared.v4.b32 [%0], {%1,%2,%3,%4};}" ::"r"(off), "r"(x[0]), "r"(x[1]), "r"(x[2]), "r"(x[3]) : "memory"); }
__device__ __forceinline__ void split(int x, int n) { asm volatile("{.reg .pred p; setp.eq.s32 p, %0, %1; @p trap;}" ::"r"(x), "r"(~n) : "memory"); }
__device__ __forceinline__ void ln_final(float s, float q, float& m, float& sd) {
  m = s * (1.f / D_);
  asm("sqrt.approx.f32 %0, %1;" : "=f"(sd) : "f"(rbf(rbf(fmaxf(fmaf(-m, m, q * (1.f / D_)), 0.f)) + 1e-5f)));
  sd = rbf(sd);
}
__device__ __forceinline__ float rcpf(float x) { float r; asm("rcp.approx.f32 %0, %1;" : "=f"(r) : "f"(x)); return r; }

__device__ __forceinline__ void wg_rs16_0(float* d, const uint32_t* a, uint64_t db, int sc) {
  asm volatile("{.reg .pred p; setp.ne.b32 p, %13, 0; wgmma.mma_async.sync.aligned.m64n16k16.f32.bf16.bf16 {%0,%1,%2,%3,%4,%5,%6,%7}, {%8,%9,%10,%11}, %12, p, 1, 1, 0;}"
    : "+f"(d[0]),"+f"(d[1]),"+f"(d[2]),"+f"(d[3]),"+f"(d[4]),"+f"(d[5]),"+f"(d[6]),"+f"(d[7]) : "r"(a[0]),"r"(a[1]),"r"(a[2]),"r"(a[3]),"l"(db),"r"(sc));
}
__device__ __forceinline__ void wg_rs32_0(float* d, const uint32_t* a, uint64_t db, int sc) {
  asm volatile("{.reg .pred p; setp.ne.b32 p, %21, 0; wgmma.mma_async.sync.aligned.m64n32k16.f32.bf16.bf16 {%0,%1,%2,%3,%4,%5,%6,%7,%8,%9,%10,%11,%12,%13,%14,%15}, {%16,%17,%18,%19}, %20, p, 1, 1, 0;}"
    : "+f"(d[0]),"+f"(d[1]),"+f"(d[2]),"+f"(d[3]),"+f"(d[4]),"+f"(d[5]),"+f"(d[6]),"+f"(d[7]),"+f"(d[8]),"+f"(d[9]),"+f"(d[10]),"+f"(d[11]),"+f"(d[12]),"+f"(d[13]),"+f"(d[14]),"+f"(d[15]) : "r"(a[0]),"r"(a[1]),"r"(a[2]),"r"(a[3]),"l"(db),"r"(sc));
}
__device__ __forceinline__ void wg_rs48_0(float* d, const uint32_t* a, uint64_t db, int sc) {
  asm volatile("{.reg .pred p; setp.ne.b32 p, %29, 0; wgmma.mma_async.sync.aligned.m64n48k16.f32.bf16.bf16 {%0,%1,%2,%3,%4,%5,%6,%7,%8,%9,%10,%11,%12,%13,%14,%15,%16,%17,%18,%19,%20,%21,%22,%23}, {%24,%25,%26,%27}, %28, p, 1, 1, 0;}"
    : "+f"(d[0]),"+f"(d[1]),"+f"(d[2]),"+f"(d[3]),"+f"(d[4]),"+f"(d[5]),"+f"(d[6]),"+f"(d[7]),"+f"(d[8]),"+f"(d[9]),"+f"(d[10]),"+f"(d[11]),"+f"(d[12]),"+f"(d[13]),"+f"(d[14]),"+f"(d[15]),"+f"(d[16]),"+f"(d[17]),"+f"(d[18]),"+f"(d[19]),"+f"(d[20]),"+f"(d[21]),"+f"(d[22]),"+f"(d[23]) : "r"(a[0]),"r"(a[1]),"r"(a[2]),"r"(a[3]),"l"(db),"r"(sc));
}
__device__ __forceinline__ void wg_rs64_0(float* d, const uint32_t* a, uint64_t db, int sc) {
  asm volatile("{.reg .pred p; setp.ne.b32 p, %37, 0; wgmma.mma_async.sync.aligned.m64n64k16.f32.bf16.bf16 {%0,%1,%2,%3,%4,%5,%6,%7,%8,%9,%10,%11,%12,%13,%14,%15,%16,%17,%18,%19,%20,%21,%22,%23,%24,%25,%26,%27,%28,%29,%30,%31}, {%32,%33,%34,%35}, %36, p, 1, 1, 0;}"
    : "+f"(d[0]),"+f"(d[1]),"+f"(d[2]),"+f"(d[3]),"+f"(d[4]),"+f"(d[5]),"+f"(d[6]),"+f"(d[7]),"+f"(d[8]),"+f"(d[9]),"+f"(d[10]),"+f"(d[11]),"+f"(d[12]),"+f"(d[13]),"+f"(d[14]),"+f"(d[15]),"+f"(d[16]),"+f"(d[17]),"+f"(d[18]),"+f"(d[19]),"+f"(d[20]),"+f"(d[21]),"+f"(d[22]),"+f"(d[23]),"+f"(d[24]),"+f"(d[25]),"+f"(d[26]),"+f"(d[27]),"+f"(d[28]),"+f"(d[29]),"+f"(d[30]),"+f"(d[31]) : "r"(a[0]),"r"(a[1]),"r"(a[2]),"r"(a[3]),"l"(db),"r"(sc));
}
__device__ __forceinline__ void wg_rs80_0(float* d, const uint32_t* a, uint64_t db, int sc) {
  asm volatile("{.reg .pred p; setp.ne.b32 p, %45, 0; wgmma.mma_async.sync.aligned.m64n80k16.f32.bf16.bf16 {%0,%1,%2,%3,%4,%5,%6,%7,%8,%9,%10,%11,%12,%13,%14,%15,%16,%17,%18,%19,%20,%21,%22,%23,%24,%25,%26,%27,%28,%29,%30,%31,%32,%33,%34,%35,%36,%37,%38,%39}, {%40,%41,%42,%43}, %44, p, 1, 1, 0;}"
    : "+f"(d[0]),"+f"(d[1]),"+f"(d[2]),"+f"(d[3]),"+f"(d[4]),"+f"(d[5]),"+f"(d[6]),"+f"(d[7]),"+f"(d[8]),"+f"(d[9]),"+f"(d[10]),"+f"(d[11]),"+f"(d[12]),"+f"(d[13]),"+f"(d[14]),"+f"(d[15]),"+f"(d[16]),"+f"(d[17]),"+f"(d[18]),"+f"(d[19]),"+f"(d[20]),"+f"(d[21]),"+f"(d[22]),"+f"(d[23]),"+f"(d[24]),"+f"(d[25]),"+f"(d[26]),"+f"(d[27]),"+f"(d[28]),"+f"(d[29]),"+f"(d[30]),"+f"(d[31]),"+f"(d[32]),"+f"(d[33]),"+f"(d[34]),"+f"(d[35]),"+f"(d[36]),"+f"(d[37]),"+f"(d[38]),"+f"(d[39]) : "r"(a[0]),"r"(a[1]),"r"(a[2]),"r"(a[3]),"l"(db),"r"(sc));
}
__device__ __forceinline__ void wg_rs96_0(float* d, const uint32_t* a, uint64_t db, int sc) {
  asm volatile("{.reg .pred p; setp.ne.b32 p, %53, 0; wgmma.mma_async.sync.aligned.m64n96k16.f32.bf16.bf16 {%0,%1,%2,%3,%4,%5,%6,%7,%8,%9,%10,%11,%12,%13,%14,%15,%16,%17,%18,%19,%20,%21,%22,%23,%24,%25,%26,%27,%28,%29,%30,%31,%32,%33,%34,%35,%36,%37,%38,%39,%40,%41,%42,%43,%44,%45,%46,%47}, {%48,%49,%50,%51}, %52, p, 1, 1, 0;}"
    : "+f"(d[0]),"+f"(d[1]),"+f"(d[2]),"+f"(d[3]),"+f"(d[4]),"+f"(d[5]),"+f"(d[6]),"+f"(d[7]),"+f"(d[8]),"+f"(d[9]),"+f"(d[10]),"+f"(d[11]),"+f"(d[12]),"+f"(d[13]),"+f"(d[14]),"+f"(d[15]),"+f"(d[16]),"+f"(d[17]),"+f"(d[18]),"+f"(d[19]),"+f"(d[20]),"+f"(d[21]),"+f"(d[22]),"+f"(d[23]),"+f"(d[24]),"+f"(d[25]),"+f"(d[26]),"+f"(d[27]),"+f"(d[28]),"+f"(d[29]),"+f"(d[30]),"+f"(d[31]),"+f"(d[32]),"+f"(d[33]),"+f"(d[34]),"+f"(d[35]),"+f"(d[36]),"+f"(d[37]),"+f"(d[38]),"+f"(d[39]),"+f"(d[40]),"+f"(d[41]),"+f"(d[42]),"+f"(d[43]),"+f"(d[44]),"+f"(d[45]),"+f"(d[46]),"+f"(d[47]) : "r"(a[0]),"r"(a[1]),"r"(a[2]),"r"(a[3]),"l"(db),"r"(sc));
}
__device__ __forceinline__ void wg_rs112_0(float* d, const uint32_t* a, uint64_t db, int sc) {
  asm volatile("{.reg .pred p; setp.ne.b32 p, %61, 0; wgmma.mma_async.sync.aligned.m64n112k16.f32.bf16.bf16 {%0,%1,%2,%3,%4,%5,%6,%7,%8,%9,%10,%11,%12,%13,%14,%15,%16,%17,%18,%19,%20,%21,%22,%23,%24,%25,%26,%27,%28,%29,%30,%31,%32,%33,%34,%35,%36,%37,%38,%39,%40,%41,%42,%43,%44,%45,%46,%47,%48,%49,%50,%51,%52,%53,%54,%55}, {%56,%57,%58,%59}, %60, p, 1, 1, 0;}"
    : "+f"(d[0]),"+f"(d[1]),"+f"(d[2]),"+f"(d[3]),"+f"(d[4]),"+f"(d[5]),"+f"(d[6]),"+f"(d[7]),"+f"(d[8]),"+f"(d[9]),"+f"(d[10]),"+f"(d[11]),"+f"(d[12]),"+f"(d[13]),"+f"(d[14]),"+f"(d[15]),"+f"(d[16]),"+f"(d[17]),"+f"(d[18]),"+f"(d[19]),"+f"(d[20]),"+f"(d[21]),"+f"(d[22]),"+f"(d[23]),"+f"(d[24]),"+f"(d[25]),"+f"(d[26]),"+f"(d[27]),"+f"(d[28]),"+f"(d[29]),"+f"(d[30]),"+f"(d[31]),"+f"(d[32]),"+f"(d[33]),"+f"(d[34]),"+f"(d[35]),"+f"(d[36]),"+f"(d[37]),"+f"(d[38]),"+f"(d[39]),"+f"(d[40]),"+f"(d[41]),"+f"(d[42]),"+f"(d[43]),"+f"(d[44]),"+f"(d[45]),"+f"(d[46]),"+f"(d[47]),"+f"(d[48]),"+f"(d[49]),"+f"(d[50]),"+f"(d[51]),"+f"(d[52]),"+f"(d[53]),"+f"(d[54]),"+f"(d[55]) : "r"(a[0]),"r"(a[1]),"r"(a[2]),"r"(a[3]),"l"(db),"r"(sc));
}
__device__ __forceinline__ void wg_rs128_0(float* d, const uint32_t* a, uint64_t db, int sc) {
  asm volatile("{.reg .pred p; setp.ne.b32 p, %69, 0; wgmma.mma_async.sync.aligned.m64n128k16.f32.bf16.bf16 {%0,%1,%2,%3,%4,%5,%6,%7,%8,%9,%10,%11,%12,%13,%14,%15,%16,%17,%18,%19,%20,%21,%22,%23,%24,%25,%26,%27,%28,%29,%30,%31,%32,%33,%34,%35,%36,%37,%38,%39,%40,%41,%42,%43,%44,%45,%46,%47,%48,%49,%50,%51,%52,%53,%54,%55,%56,%57,%58,%59,%60,%61,%62,%63}, {%64,%65,%66,%67}, %68, p, 1, 1, 0;}"
    : "+f"(d[0]),"+f"(d[1]),"+f"(d[2]),"+f"(d[3]),"+f"(d[4]),"+f"(d[5]),"+f"(d[6]),"+f"(d[7]),"+f"(d[8]),"+f"(d[9]),"+f"(d[10]),"+f"(d[11]),"+f"(d[12]),"+f"(d[13]),"+f"(d[14]),"+f"(d[15]),"+f"(d[16]),"+f"(d[17]),"+f"(d[18]),"+f"(d[19]),"+f"(d[20]),"+f"(d[21]),"+f"(d[22]),"+f"(d[23]),"+f"(d[24]),"+f"(d[25]),"+f"(d[26]),"+f"(d[27]),"+f"(d[28]),"+f"(d[29]),"+f"(d[30]),"+f"(d[31]),"+f"(d[32]),"+f"(d[33]),"+f"(d[34]),"+f"(d[35]),"+f"(d[36]),"+f"(d[37]),"+f"(d[38]),"+f"(d[39]),"+f"(d[40]),"+f"(d[41]),"+f"(d[42]),"+f"(d[43]),"+f"(d[44]),"+f"(d[45]),"+f"(d[46]),"+f"(d[47]),"+f"(d[48]),"+f"(d[49]),"+f"(d[50]),"+f"(d[51]),"+f"(d[52]),"+f"(d[53]),"+f"(d[54]),"+f"(d[55]),"+f"(d[56]),"+f"(d[57]),"+f"(d[58]),"+f"(d[59]),"+f"(d[60]),"+f"(d[61]),"+f"(d[62]),"+f"(d[63]) : "r"(a[0]),"r"(a[1]),"r"(a[2]),"r"(a[3]),"l"(db),"r"(sc));
}
__device__ __forceinline__ void wg_rs144_0(float* d, const uint32_t* a, uint64_t db, int sc) {
  asm volatile("{.reg .pred p; setp.ne.b32 p, %77, 0; wgmma.mma_async.sync.aligned.m64n144k16.f32.bf16.bf16 {%0,%1,%2,%3,%4,%5,%6,%7,%8,%9,%10,%11,%12,%13,%14,%15,%16,%17,%18,%19,%20,%21,%22,%23,%24,%25,%26,%27,%28,%29,%30,%31,%32,%33,%34,%35,%36,%37,%38,%39,%40,%41,%42,%43,%44,%45,%46,%47,%48,%49,%50,%51,%52,%53,%54,%55,%56,%57,%58,%59,%60,%61,%62,%63,%64,%65,%66,%67,%68,%69,%70,%71}, {%72,%73,%74,%75}, %76, p, 1, 1, 0;}"
    : "+f"(d[0]),"+f"(d[1]),"+f"(d[2]),"+f"(d[3]),"+f"(d[4]),"+f"(d[5]),"+f"(d[6]),"+f"(d[7]),"+f"(d[8]),"+f"(d[9]),"+f"(d[10]),"+f"(d[11]),"+f"(d[12]),"+f"(d[13]),"+f"(d[14]),"+f"(d[15]),"+f"(d[16]),"+f"(d[17]),"+f"(d[18]),"+f"(d[19]),"+f"(d[20]),"+f"(d[21]),"+f"(d[22]),"+f"(d[23]),"+f"(d[24]),"+f"(d[25]),"+f"(d[26]),"+f"(d[27]),"+f"(d[28]),"+f"(d[29]),"+f"(d[30]),"+f"(d[31]),"+f"(d[32]),"+f"(d[33]),"+f"(d[34]),"+f"(d[35]),"+f"(d[36]),"+f"(d[37]),"+f"(d[38]),"+f"(d[39]),"+f"(d[40]),"+f"(d[41]),"+f"(d[42]),"+f"(d[43]),"+f"(d[44]),"+f"(d[45]),"+f"(d[46]),"+f"(d[47]),"+f"(d[48]),"+f"(d[49]),"+f"(d[50]),"+f"(d[51]),"+f"(d[52]),"+f"(d[53]),"+f"(d[54]),"+f"(d[55]),"+f"(d[56]),"+f"(d[57]),"+f"(d[58]),"+f"(d[59]),"+f"(d[60]),"+f"(d[61]),"+f"(d[62]),"+f"(d[63]),"+f"(d[64]),"+f"(d[65]),"+f"(d[66]),"+f"(d[67]),"+f"(d[68]),"+f"(d[69]),"+f"(d[70]),"+f"(d[71]) : "r"(a[0]),"r"(a[1]),"r"(a[2]),"r"(a[3]),"l"(db),"r"(sc));
}
__device__ __forceinline__ void wg_rs160_0(float* d, const uint32_t* a, uint64_t db, int sc) {
  asm volatile("{.reg .pred p; setp.ne.b32 p, %85, 0; wgmma.mma_async.sync.aligned.m64n160k16.f32.bf16.bf16 {%0,%1,%2,%3,%4,%5,%6,%7,%8,%9,%10,%11,%12,%13,%14,%15,%16,%17,%18,%19,%20,%21,%22,%23,%24,%25,%26,%27,%28,%29,%30,%31,%32,%33,%34,%35,%36,%37,%38,%39,%40,%41,%42,%43,%44,%45,%46,%47,%48,%49,%50,%51,%52,%53,%54,%55,%56,%57,%58,%59,%60,%61,%62,%63,%64,%65,%66,%67,%68,%69,%70,%71,%72,%73,%74,%75,%76,%77,%78,%79}, {%80,%81,%82,%83}, %84, p, 1, 1, 0;}"
    : "+f"(d[0]),"+f"(d[1]),"+f"(d[2]),"+f"(d[3]),"+f"(d[4]),"+f"(d[5]),"+f"(d[6]),"+f"(d[7]),"+f"(d[8]),"+f"(d[9]),"+f"(d[10]),"+f"(d[11]),"+f"(d[12]),"+f"(d[13]),"+f"(d[14]),"+f"(d[15]),"+f"(d[16]),"+f"(d[17]),"+f"(d[18]),"+f"(d[19]),"+f"(d[20]),"+f"(d[21]),"+f"(d[22]),"+f"(d[23]),"+f"(d[24]),"+f"(d[25]),"+f"(d[26]),"+f"(d[27]),"+f"(d[28]),"+f"(d[29]),"+f"(d[30]),"+f"(d[31]),"+f"(d[32]),"+f"(d[33]),"+f"(d[34]),"+f"(d[35]),"+f"(d[36]),"+f"(d[37]),"+f"(d[38]),"+f"(d[39]),"+f"(d[40]),"+f"(d[41]),"+f"(d[42]),"+f"(d[43]),"+f"(d[44]),"+f"(d[45]),"+f"(d[46]),"+f"(d[47]),"+f"(d[48]),"+f"(d[49]),"+f"(d[50]),"+f"(d[51]),"+f"(d[52]),"+f"(d[53]),"+f"(d[54]),"+f"(d[55]),"+f"(d[56]),"+f"(d[57]),"+f"(d[58]),"+f"(d[59]),"+f"(d[60]),"+f"(d[61]),"+f"(d[62]),"+f"(d[63]),"+f"(d[64]),"+f"(d[65]),"+f"(d[66]),"+f"(d[67]),"+f"(d[68]),"+f"(d[69]),"+f"(d[70]),"+f"(d[71]),"+f"(d[72]),"+f"(d[73]),"+f"(d[74]),"+f"(d[75]),"+f"(d[76]),"+f"(d[77]),"+f"(d[78]),"+f"(d[79]) : "r"(a[0]),"r"(a[1]),"r"(a[2]),"r"(a[3]),"l"(db),"r"(sc));
}
__device__ __forceinline__ void wg_rs176_0(float* d, const uint32_t* a, uint64_t db, int sc) {
  asm volatile("{.reg .pred p; setp.ne.b32 p, %93, 0; wgmma.mma_async.sync.aligned.m64n176k16.f32.bf16.bf16 {%0,%1,%2,%3,%4,%5,%6,%7,%8,%9,%10,%11,%12,%13,%14,%15,%16,%17,%18,%19,%20,%21,%22,%23,%24,%25,%26,%27,%28,%29,%30,%31,%32,%33,%34,%35,%36,%37,%38,%39,%40,%41,%42,%43,%44,%45,%46,%47,%48,%49,%50,%51,%52,%53,%54,%55,%56,%57,%58,%59,%60,%61,%62,%63,%64,%65,%66,%67,%68,%69,%70,%71,%72,%73,%74,%75,%76,%77,%78,%79,%80,%81,%82,%83,%84,%85,%86,%87}, {%88,%89,%90,%91}, %92, p, 1, 1, 0;}"
    : "+f"(d[0]),"+f"(d[1]),"+f"(d[2]),"+f"(d[3]),"+f"(d[4]),"+f"(d[5]),"+f"(d[6]),"+f"(d[7]),"+f"(d[8]),"+f"(d[9]),"+f"(d[10]),"+f"(d[11]),"+f"(d[12]),"+f"(d[13]),"+f"(d[14]),"+f"(d[15]),"+f"(d[16]),"+f"(d[17]),"+f"(d[18]),"+f"(d[19]),"+f"(d[20]),"+f"(d[21]),"+f"(d[22]),"+f"(d[23]),"+f"(d[24]),"+f"(d[25]),"+f"(d[26]),"+f"(d[27]),"+f"(d[28]),"+f"(d[29]),"+f"(d[30]),"+f"(d[31]),"+f"(d[32]),"+f"(d[33]),"+f"(d[34]),"+f"(d[35]),"+f"(d[36]),"+f"(d[37]),"+f"(d[38]),"+f"(d[39]),"+f"(d[40]),"+f"(d[41]),"+f"(d[42]),"+f"(d[43]),"+f"(d[44]),"+f"(d[45]),"+f"(d[46]),"+f"(d[47]),"+f"(d[48]),"+f"(d[49]),"+f"(d[50]),"+f"(d[51]),"+f"(d[52]),"+f"(d[53]),"+f"(d[54]),"+f"(d[55]),"+f"(d[56]),"+f"(d[57]),"+f"(d[58]),"+f"(d[59]),"+f"(d[60]),"+f"(d[61]),"+f"(d[62]),"+f"(d[63]),"+f"(d[64]),"+f"(d[65]),"+f"(d[66]),"+f"(d[67]),"+f"(d[68]),"+f"(d[69]),"+f"(d[70]),"+f"(d[71]),"+f"(d[72]),"+f"(d[73]),"+f"(d[74]),"+f"(d[75]),"+f"(d[76]),"+f"(d[77]),"+f"(d[78]),"+f"(d[79]),"+f"(d[80]),"+f"(d[81]),"+f"(d[82]),"+f"(d[83]),"+f"(d[84]),"+f"(d[85]),"+f"(d[86]),"+f"(d[87]) : "r"(a[0]),"r"(a[1]),"r"(a[2]),"r"(a[3]),"l"(db),"r"(sc));
}
__device__ __forceinline__ void wg_rs192_0(float* d, const uint32_t* a, uint64_t db, int sc) {
  asm volatile("{.reg .pred p; setp.ne.b32 p, %101, 0; wgmma.mma_async.sync.aligned.m64n192k16.f32.bf16.bf16 {%0,%1,%2,%3,%4,%5,%6,%7,%8,%9,%10,%11,%12,%13,%14,%15,%16,%17,%18,%19,%20,%21,%22,%23,%24,%25,%26,%27,%28,%29,%30,%31,%32,%33,%34,%35,%36,%37,%38,%39,%40,%41,%42,%43,%44,%45,%46,%47,%48,%49,%50,%51,%52,%53,%54,%55,%56,%57,%58,%59,%60,%61,%62,%63,%64,%65,%66,%67,%68,%69,%70,%71,%72,%73,%74,%75,%76,%77,%78,%79,%80,%81,%82,%83,%84,%85,%86,%87,%88,%89,%90,%91,%92,%93,%94,%95}, {%96,%97,%98,%99}, %100, p, 1, 1, 0;}"
    : "+f"(d[0]),"+f"(d[1]),"+f"(d[2]),"+f"(d[3]),"+f"(d[4]),"+f"(d[5]),"+f"(d[6]),"+f"(d[7]),"+f"(d[8]),"+f"(d[9]),"+f"(d[10]),"+f"(d[11]),"+f"(d[12]),"+f"(d[13]),"+f"(d[14]),"+f"(d[15]),"+f"(d[16]),"+f"(d[17]),"+f"(d[18]),"+f"(d[19]),"+f"(d[20]),"+f"(d[21]),"+f"(d[22]),"+f"(d[23]),"+f"(d[24]),"+f"(d[25]),"+f"(d[26]),"+f"(d[27]),"+f"(d[28]),"+f"(d[29]),"+f"(d[30]),"+f"(d[31]),"+f"(d[32]),"+f"(d[33]),"+f"(d[34]),"+f"(d[35]),"+f"(d[36]),"+f"(d[37]),"+f"(d[38]),"+f"(d[39]),"+f"(d[40]),"+f"(d[41]),"+f"(d[42]),"+f"(d[43]),"+f"(d[44]),"+f"(d[45]),"+f"(d[46]),"+f"(d[47]),"+f"(d[48]),"+f"(d[49]),"+f"(d[50]),"+f"(d[51]),"+f"(d[52]),"+f"(d[53]),"+f"(d[54]),"+f"(d[55]),"+f"(d[56]),"+f"(d[57]),"+f"(d[58]),"+f"(d[59]),"+f"(d[60]),"+f"(d[61]),"+f"(d[62]),"+f"(d[63]),"+f"(d[64]),"+f"(d[65]),"+f"(d[66]),"+f"(d[67]),"+f"(d[68]),"+f"(d[69]),"+f"(d[70]),"+f"(d[71]),"+f"(d[72]),"+f"(d[73]),"+f"(d[74]),"+f"(d[75]),"+f"(d[76]),"+f"(d[77]),"+f"(d[78]),"+f"(d[79]),"+f"(d[80]),"+f"(d[81]),"+f"(d[82]),"+f"(d[83]),"+f"(d[84]),"+f"(d[85]),"+f"(d[86]),"+f"(d[87]),"+f"(d[88]),"+f"(d[89]),"+f"(d[90]),"+f"(d[91]),"+f"(d[92]),"+f"(d[93]),"+f"(d[94]),"+f"(d[95]) : "r"(a[0]),"r"(a[1]),"r"(a[2]),"r"(a[3]),"l"(db),"r"(sc));
}
__device__ __forceinline__ void wg_ss192_11(float* d, uint64_t da, uint64_t db, int sc) {
  asm volatile("{.reg .pred p; setp.ne.b32 p, %98, 0; wgmma.mma_async.sync.aligned.m64n192k16.f32.bf16.bf16 {%0,%1,%2,%3,%4,%5,%6,%7,%8,%9,%10,%11,%12,%13,%14,%15,%16,%17,%18,%19,%20,%21,%22,%23,%24,%25,%26,%27,%28,%29,%30,%31,%32,%33,%34,%35,%36,%37,%38,%39,%40,%41,%42,%43,%44,%45,%46,%47,%48,%49,%50,%51,%52,%53,%54,%55,%56,%57,%58,%59,%60,%61,%62,%63,%64,%65,%66,%67,%68,%69,%70,%71,%72,%73,%74,%75,%76,%77,%78,%79,%80,%81,%82,%83,%84,%85,%86,%87,%88,%89,%90,%91,%92,%93,%94,%95}, %96, %97, p, 1, 1, 1, 1;}"
    : "+f"(d[0]),"+f"(d[1]),"+f"(d[2]),"+f"(d[3]),"+f"(d[4]),"+f"(d[5]),"+f"(d[6]),"+f"(d[7]),"+f"(d[8]),"+f"(d[9]),"+f"(d[10]),"+f"(d[11]),"+f"(d[12]),"+f"(d[13]),"+f"(d[14]),"+f"(d[15]),"+f"(d[16]),"+f"(d[17]),"+f"(d[18]),"+f"(d[19]),"+f"(d[20]),"+f"(d[21]),"+f"(d[22]),"+f"(d[23]),"+f"(d[24]),"+f"(d[25]),"+f"(d[26]),"+f"(d[27]),"+f"(d[28]),"+f"(d[29]),"+f"(d[30]),"+f"(d[31]),"+f"(d[32]),"+f"(d[33]),"+f"(d[34]),"+f"(d[35]),"+f"(d[36]),"+f"(d[37]),"+f"(d[38]),"+f"(d[39]),"+f"(d[40]),"+f"(d[41]),"+f"(d[42]),"+f"(d[43]),"+f"(d[44]),"+f"(d[45]),"+f"(d[46]),"+f"(d[47]),"+f"(d[48]),"+f"(d[49]),"+f"(d[50]),"+f"(d[51]),"+f"(d[52]),"+f"(d[53]),"+f"(d[54]),"+f"(d[55]),"+f"(d[56]),"+f"(d[57]),"+f"(d[58]),"+f"(d[59]),"+f"(d[60]),"+f"(d[61]),"+f"(d[62]),"+f"(d[63]),"+f"(d[64]),"+f"(d[65]),"+f"(d[66]),"+f"(d[67]),"+f"(d[68]),"+f"(d[69]),"+f"(d[70]),"+f"(d[71]),"+f"(d[72]),"+f"(d[73]),"+f"(d[74]),"+f"(d[75]),"+f"(d[76]),"+f"(d[77]),"+f"(d[78]),"+f"(d[79]),"+f"(d[80]),"+f"(d[81]),"+f"(d[82]),"+f"(d[83]),"+f"(d[84]),"+f"(d[85]),"+f"(d[86]),"+f"(d[87]),"+f"(d[88]),"+f"(d[89]),"+f"(d[90]),"+f"(d[91]),"+f"(d[92]),"+f"(d[93]),"+f"(d[94]),"+f"(d[95]) : "l"(da),"l"(db),"r"(sc));
}
__device__ __forceinline__ void wg_ss192_01(float* d, uint64_t da, uint64_t db, int sc) {
  asm volatile("{.reg .pred p; setp.ne.b32 p, %98, 0; wgmma.mma_async.sync.aligned.m64n192k16.f32.bf16.bf16 {%0,%1,%2,%3,%4,%5,%6,%7,%8,%9,%10,%11,%12,%13,%14,%15,%16,%17,%18,%19,%20,%21,%22,%23,%24,%25,%26,%27,%28,%29,%30,%31,%32,%33,%34,%35,%36,%37,%38,%39,%40,%41,%42,%43,%44,%45,%46,%47,%48,%49,%50,%51,%52,%53,%54,%55,%56,%57,%58,%59,%60,%61,%62,%63,%64,%65,%66,%67,%68,%69,%70,%71,%72,%73,%74,%75,%76,%77,%78,%79,%80,%81,%82,%83,%84,%85,%86,%87,%88,%89,%90,%91,%92,%93,%94,%95}, %96, %97, p, 1, 1, 0, 1;}"
    : "+f"(d[0]),"+f"(d[1]),"+f"(d[2]),"+f"(d[3]),"+f"(d[4]),"+f"(d[5]),"+f"(d[6]),"+f"(d[7]),"+f"(d[8]),"+f"(d[9]),"+f"(d[10]),"+f"(d[11]),"+f"(d[12]),"+f"(d[13]),"+f"(d[14]),"+f"(d[15]),"+f"(d[16]),"+f"(d[17]),"+f"(d[18]),"+f"(d[19]),"+f"(d[20]),"+f"(d[21]),"+f"(d[22]),"+f"(d[23]),"+f"(d[24]),"+f"(d[25]),"+f"(d[26]),"+f"(d[27]),"+f"(d[28]),"+f"(d[29]),"+f"(d[30]),"+f"(d[31]),"+f"(d[32]),"+f"(d[33]),"+f"(d[34]),"+f"(d[35]),"+f"(d[36]),"+f"(d[37]),"+f"(d[38]),"+f"(d[39]),"+f"(d[40]),"+f"(d[41]),"+f"(d[42]),"+f"(d[43]),"+f"(d[44]),"+f"(d[45]),"+f"(d[46]),"+f"(d[47]),"+f"(d[48]),"+f"(d[49]),"+f"(d[50]),"+f"(d[51]),"+f"(d[52]),"+f"(d[53]),"+f"(d[54]),"+f"(d[55]),"+f"(d[56]),"+f"(d[57]),"+f"(d[58]),"+f"(d[59]),"+f"(d[60]),"+f"(d[61]),"+f"(d[62]),"+f"(d[63]),"+f"(d[64]),"+f"(d[65]),"+f"(d[66]),"+f"(d[67]),"+f"(d[68]),"+f"(d[69]),"+f"(d[70]),"+f"(d[71]),"+f"(d[72]),"+f"(d[73]),"+f"(d[74]),"+f"(d[75]),"+f"(d[76]),"+f"(d[77]),"+f"(d[78]),"+f"(d[79]),"+f"(d[80]),"+f"(d[81]),"+f"(d[82]),"+f"(d[83]),"+f"(d[84]),"+f"(d[85]),"+f"(d[86]),"+f"(d[87]),"+f"(d[88]),"+f"(d[89]),"+f"(d[90]),"+f"(d[91]),"+f"(d[92]),"+f"(d[93]),"+f"(d[94]),"+f"(d[95]) : "l"(da),"l"(db),"r"(sc));
}
__device__ __forceinline__ void wg_ss64_11(float* d, uint64_t da, uint64_t db, int sc) {
  asm volatile("{.reg .pred p; setp.ne.b32 p, %34, 0; wgmma.mma_async.sync.aligned.m64n64k16.f32.bf16.bf16 {%0,%1,%2,%3,%4,%5,%6,%7,%8,%9,%10,%11,%12,%13,%14,%15,%16,%17,%18,%19,%20,%21,%22,%23,%24,%25,%26,%27,%28,%29,%30,%31}, %32, %33, p, 1, 1, 1, 1;}"
    : "+f"(d[0]),"+f"(d[1]),"+f"(d[2]),"+f"(d[3]),"+f"(d[4]),"+f"(d[5]),"+f"(d[6]),"+f"(d[7]),"+f"(d[8]),"+f"(d[9]),"+f"(d[10]),"+f"(d[11]),"+f"(d[12]),"+f"(d[13]),"+f"(d[14]),"+f"(d[15]),"+f"(d[16]),"+f"(d[17]),"+f"(d[18]),"+f"(d[19]),"+f"(d[20]),"+f"(d[21]),"+f"(d[22]),"+f"(d[23]),"+f"(d[24]),"+f"(d[25]),"+f"(d[26]),"+f"(d[27]),"+f"(d[28]),"+f"(d[29]),"+f"(d[30]),"+f"(d[31]) : "l"(da),"l"(db),"r"(sc));
}
__device__ __forceinline__ void wg_ss64_01(float* d, uint64_t da, uint64_t db, int sc) {
  asm volatile("{.reg .pred p; setp.ne.b32 p, %34, 0; wgmma.mma_async.sync.aligned.m64n64k16.f32.bf16.bf16 {%0,%1,%2,%3,%4,%5,%6,%7,%8,%9,%10,%11,%12,%13,%14,%15,%16,%17,%18,%19,%20,%21,%22,%23,%24,%25,%26,%27,%28,%29,%30,%31}, %32, %33, p, 1, 1, 0, 1;}"
    : "+f"(d[0]),"+f"(d[1]),"+f"(d[2]),"+f"(d[3]),"+f"(d[4]),"+f"(d[5]),"+f"(d[6]),"+f"(d[7]),"+f"(d[8]),"+f"(d[9]),"+f"(d[10]),"+f"(d[11]),"+f"(d[12]),"+f"(d[13]),"+f"(d[14]),"+f"(d[15]),"+f"(d[16]),"+f"(d[17]),"+f"(d[18]),"+f"(d[19]),"+f"(d[20]),"+f"(d[21]),"+f"(d[22]),"+f"(d[23]),"+f"(d[24]),"+f"(d[25]),"+f"(d[26]),"+f"(d[27]),"+f"(d[28]),"+f"(d[29]),"+f"(d[30]),"+f"(d[31]) : "l"(da),"l"(db),"r"(sc));
}
__device__ __forceinline__ void wg_ss128_11(float* d, uint64_t da, uint64_t db, int sc) {
  asm volatile("{.reg .pred p; setp.ne.b32 p, %66, 0; wgmma.mma_async.sync.aligned.m64n128k16.f32.bf16.bf16 {%0,%1,%2,%3,%4,%5,%6,%7,%8,%9,%10,%11,%12,%13,%14,%15,%16,%17,%18,%19,%20,%21,%22,%23,%24,%25,%26,%27,%28,%29,%30,%31,%32,%33,%34,%35,%36,%37,%38,%39,%40,%41,%42,%43,%44,%45,%46,%47,%48,%49,%50,%51,%52,%53,%54,%55,%56,%57,%58,%59,%60,%61,%62,%63}, %64, %65, p, 1, 1, 1, 1;}"
    : "+f"(d[0]),"+f"(d[1]),"+f"(d[2]),"+f"(d[3]),"+f"(d[4]),"+f"(d[5]),"+f"(d[6]),"+f"(d[7]),"+f"(d[8]),"+f"(d[9]),"+f"(d[10]),"+f"(d[11]),"+f"(d[12]),"+f"(d[13]),"+f"(d[14]),"+f"(d[15]),"+f"(d[16]),"+f"(d[17]),"+f"(d[18]),"+f"(d[19]),"+f"(d[20]),"+f"(d[21]),"+f"(d[22]),"+f"(d[23]),"+f"(d[24]),"+f"(d[25]),"+f"(d[26]),"+f"(d[27]),"+f"(d[28]),"+f"(d[29]),"+f"(d[30]),"+f"(d[31]),"+f"(d[32]),"+f"(d[33]),"+f"(d[34]),"+f"(d[35]),"+f"(d[36]),"+f"(d[37]),"+f"(d[38]),"+f"(d[39]),"+f"(d[40]),"+f"(d[41]),"+f"(d[42]),"+f"(d[43]),"+f"(d[44]),"+f"(d[45]),"+f"(d[46]),"+f"(d[47]),"+f"(d[48]),"+f"(d[49]),"+f"(d[50]),"+f"(d[51]),"+f"(d[52]),"+f"(d[53]),"+f"(d[54]),"+f"(d[55]),"+f"(d[56]),"+f"(d[57]),"+f"(d[58]),"+f"(d[59]),"+f"(d[60]),"+f"(d[61]),"+f"(d[62]),"+f"(d[63]) : "l"(da),"l"(db),"r"(sc));
}
__device__ __forceinline__ void wg_ss128_01(float* d, uint64_t da, uint64_t db, int sc) {
  asm volatile("{.reg .pred p; setp.ne.b32 p, %66, 0; wgmma.mma_async.sync.aligned.m64n128k16.f32.bf16.bf16 {%0,%1,%2,%3,%4,%5,%6,%7,%8,%9,%10,%11,%12,%13,%14,%15,%16,%17,%18,%19,%20,%21,%22,%23,%24,%25,%26,%27,%28,%29,%30,%31,%32,%33,%34,%35,%36,%37,%38,%39,%40,%41,%42,%43,%44,%45,%46,%47,%48,%49,%50,%51,%52,%53,%54,%55,%56,%57,%58,%59,%60,%61,%62,%63}, %64, %65, p, 1, 1, 0, 1;}"
    : "+f"(d[0]),"+f"(d[1]),"+f"(d[2]),"+f"(d[3]),"+f"(d[4]),"+f"(d[5]),"+f"(d[6]),"+f"(d[7]),"+f"(d[8]),"+f"(d[9]),"+f"(d[10]),"+f"(d[11]),"+f"(d[12]),"+f"(d[13]),"+f"(d[14]),"+f"(d[15]),"+f"(d[16]),"+f"(d[17]),"+f"(d[18]),"+f"(d[19]),"+f"(d[20]),"+f"(d[21]),"+f"(d[22]),"+f"(d[23]),"+f"(d[24]),"+f"(d[25]),"+f"(d[26]),"+f"(d[27]),"+f"(d[28]),"+f"(d[29]),"+f"(d[30]),"+f"(d[31]),"+f"(d[32]),"+f"(d[33]),"+f"(d[34]),"+f"(d[35]),"+f"(d[36]),"+f"(d[37]),"+f"(d[38]),"+f"(d[39]),"+f"(d[40]),"+f"(d[41]),"+f"(d[42]),"+f"(d[43]),"+f"(d[44]),"+f"(d[45]),"+f"(d[46]),"+f"(d[47]),"+f"(d[48]),"+f"(d[49]),"+f"(d[50]),"+f"(d[51]),"+f"(d[52]),"+f"(d[53]),"+f"(d[54]),"+f"(d[55]),"+f"(d[56]),"+f"(d[57]),"+f"(d[58]),"+f"(d[59]),"+f"(d[60]),"+f"(d[61]),"+f"(d[62]),"+f"(d[63]) : "l"(da),"l"(db),"r"(sc));
}
__device__ __forceinline__ void wg_ss96_01(float* d, uint64_t da, uint64_t db, int sc) {
  asm volatile("{.reg .pred p; setp.ne.b32 p, %50, 0; wgmma.mma_async.sync.aligned.m64n96k16.f32.bf16.bf16 {%0,%1,%2,%3,%4,%5,%6,%7,%8,%9,%10,%11,%12,%13,%14,%15,%16,%17,%18,%19,%20,%21,%22,%23,%24,%25,%26,%27,%28,%29,%30,%31,%32,%33,%34,%35,%36,%37,%38,%39,%40,%41,%42,%43,%44,%45,%46,%47}, %48, %49, p, 1, 1, 0, 1;}"
    : "+f"(d[0]),"+f"(d[1]),"+f"(d[2]),"+f"(d[3]),"+f"(d[4]),"+f"(d[5]),"+f"(d[6]),"+f"(d[7]),"+f"(d[8]),"+f"(d[9]),"+f"(d[10]),"+f"(d[11]),"+f"(d[12]),"+f"(d[13]),"+f"(d[14]),"+f"(d[15]),"+f"(d[16]),"+f"(d[17]),"+f"(d[18]),"+f"(d[19]),"+f"(d[20]),"+f"(d[21]),"+f"(d[22]),"+f"(d[23]),"+f"(d[24]),"+f"(d[25]),"+f"(d[26]),"+f"(d[27]),"+f"(d[28]),"+f"(d[29]),"+f"(d[30]),"+f"(d[31]),"+f"(d[32]),"+f"(d[33]),"+f"(d[34]),"+f"(d[35]),"+f"(d[36]),"+f"(d[37]),"+f"(d[38]),"+f"(d[39]),"+f"(d[40]),"+f"(d[41]),"+f"(d[42]),"+f"(d[43]),"+f"(d[44]),"+f"(d[45]),"+f"(d[46]),"+f"(d[47]) : "l"(da),"l"(db),"r"(sc));
}
__device__ __forceinline__ void wg_rs64_1(float* d, const uint32_t* a, uint64_t db, int sc) {
  asm volatile("{.reg .pred p; setp.ne.b32 p, %37, 0; wgmma.mma_async.sync.aligned.m64n64k16.f32.bf16.bf16 {%0,%1,%2,%3,%4,%5,%6,%7,%8,%9,%10,%11,%12,%13,%14,%15,%16,%17,%18,%19,%20,%21,%22,%23,%24,%25,%26,%27,%28,%29,%30,%31}, {%32,%33,%34,%35}, %36, p, 1, 1, 1;}"
    : "+f"(d[0]),"+f"(d[1]),"+f"(d[2]),"+f"(d[3]),"+f"(d[4]),"+f"(d[5]),"+f"(d[6]),"+f"(d[7]),"+f"(d[8]),"+f"(d[9]),"+f"(d[10]),"+f"(d[11]),"+f"(d[12]),"+f"(d[13]),"+f"(d[14]),"+f"(d[15]),"+f"(d[16]),"+f"(d[17]),"+f"(d[18]),"+f"(d[19]),"+f"(d[20]),"+f"(d[21]),"+f"(d[22]),"+f"(d[23]),"+f"(d[24]),"+f"(d[25]),"+f"(d[26]),"+f"(d[27]),"+f"(d[28]),"+f"(d[29]),"+f"(d[30]),"+f"(d[31]) : "r"(a[0]),"r"(a[1]),"r"(a[2]),"r"(a[3]),"l"(db),"r"(sc));
}
__device__ __forceinline__ void wg_rs96_1(float* d, const uint32_t* a, uint64_t db, int sc) {
  asm volatile("{.reg .pred p; setp.ne.b32 p, %53, 0; wgmma.mma_async.sync.aligned.m64n96k16.f32.bf16.bf16 {%0,%1,%2,%3,%4,%5,%6,%7,%8,%9,%10,%11,%12,%13,%14,%15,%16,%17,%18,%19,%20,%21,%22,%23,%24,%25,%26,%27,%28,%29,%30,%31,%32,%33,%34,%35,%36,%37,%38,%39,%40,%41,%42,%43,%44,%45,%46,%47}, {%48,%49,%50,%51}, %52, p, 1, 1, 1;}"
    : "+f"(d[0]),"+f"(d[1]),"+f"(d[2]),"+f"(d[3]),"+f"(d[4]),"+f"(d[5]),"+f"(d[6]),"+f"(d[7]),"+f"(d[8]),"+f"(d[9]),"+f"(d[10]),"+f"(d[11]),"+f"(d[12]),"+f"(d[13]),"+f"(d[14]),"+f"(d[15]),"+f"(d[16]),"+f"(d[17]),"+f"(d[18]),"+f"(d[19]),"+f"(d[20]),"+f"(d[21]),"+f"(d[22]),"+f"(d[23]),"+f"(d[24]),"+f"(d[25]),"+f"(d[26]),"+f"(d[27]),"+f"(d[28]),"+f"(d[29]),"+f"(d[30]),"+f"(d[31]),"+f"(d[32]),"+f"(d[33]),"+f"(d[34]),"+f"(d[35]),"+f"(d[36]),"+f"(d[37]),"+f"(d[38]),"+f"(d[39]),"+f"(d[40]),"+f"(d[41]),"+f"(d[42]),"+f"(d[43]),"+f"(d[44]),"+f"(d[45]),"+f"(d[46]),"+f"(d[47]) : "r"(a[0]),"r"(a[1]),"r"(a[2]),"r"(a[3]),"l"(db),"r"(sc));
}
__device__ __forceinline__ void wg_ss160_01(float* d, uint64_t da, uint64_t db, int sc) {
  asm volatile("{.reg .pred p; setp.ne.b32 p, %82, 0; wgmma.mma_async.sync.aligned.m64n160k16.f32.bf16.bf16 {%0,%1,%2,%3,%4,%5,%6,%7,%8,%9,%10,%11,%12,%13,%14,%15,%16,%17,%18,%19,%20,%21,%22,%23,%24,%25,%26,%27,%28,%29,%30,%31,%32,%33,%34,%35,%36,%37,%38,%39,%40,%41,%42,%43,%44,%45,%46,%47,%48,%49,%50,%51,%52,%53,%54,%55,%56,%57,%58,%59,%60,%61,%62,%63,%64,%65,%66,%67,%68,%69,%70,%71,%72,%73,%74,%75,%76,%77,%78,%79}, %80, %81, p, 1, 1, 0, 1;}"
    : "+f"(d[0]),"+f"(d[1]),"+f"(d[2]),"+f"(d[3]),"+f"(d[4]),"+f"(d[5]),"+f"(d[6]),"+f"(d[7]),"+f"(d[8]),"+f"(d[9]),"+f"(d[10]),"+f"(d[11]),"+f"(d[12]),"+f"(d[13]),"+f"(d[14]),"+f"(d[15]),"+f"(d[16]),"+f"(d[17]),"+f"(d[18]),"+f"(d[19]),"+f"(d[20]),"+f"(d[21]),"+f"(d[22]),"+f"(d[23]),"+f"(d[24]),"+f"(d[25]),"+f"(d[26]),"+f"(d[27]),"+f"(d[28]),"+f"(d[29]),"+f"(d[30]),"+f"(d[31]),"+f"(d[32]),"+f"(d[33]),"+f"(d[34]),"+f"(d[35]),"+f"(d[36]),"+f"(d[37]),"+f"(d[38]),"+f"(d[39]),"+f"(d[40]),"+f"(d[41]),"+f"(d[42]),"+f"(d[43]),"+f"(d[44]),"+f"(d[45]),"+f"(d[46]),"+f"(d[47]),"+f"(d[48]),"+f"(d[49]),"+f"(d[50]),"+f"(d[51]),"+f"(d[52]),"+f"(d[53]),"+f"(d[54]),"+f"(d[55]),"+f"(d[56]),"+f"(d[57]),"+f"(d[58]),"+f"(d[59]),"+f"(d[60]),"+f"(d[61]),"+f"(d[62]),"+f"(d[63]),"+f"(d[64]),"+f"(d[65]),"+f"(d[66]),"+f"(d[67]),"+f"(d[68]),"+f"(d[69]),"+f"(d[70]),"+f"(d[71]),"+f"(d[72]),"+f"(d[73]),"+f"(d[74]),"+f"(d[75]),"+f"(d[76]),"+f"(d[77]),"+f"(d[78]),"+f"(d[79]) : "l"(da),"l"(db),"r"(sc));
}
__device__ __forceinline__ void wg_rs160_1(float* d, const uint32_t* a, uint64_t db, int sc) {
  asm volatile("{.reg .pred p; setp.ne.b32 p, %85, 0; wgmma.mma_async.sync.aligned.m64n160k16.f32.bf16.bf16 {%0,%1,%2,%3,%4,%5,%6,%7,%8,%9,%10,%11,%12,%13,%14,%15,%16,%17,%18,%19,%20,%21,%22,%23,%24,%25,%26,%27,%28,%29,%30,%31,%32,%33,%34,%35,%36,%37,%38,%39,%40,%41,%42,%43,%44,%45,%46,%47,%48,%49,%50,%51,%52,%53,%54,%55,%56,%57,%58,%59,%60,%61,%62,%63,%64,%65,%66,%67,%68,%69,%70,%71,%72,%73,%74,%75,%76,%77,%78,%79}, {%80,%81,%82,%83}, %84, p, 1, 1, 1;}"
    : "+f"(d[0]),"+f"(d[1]),"+f"(d[2]),"+f"(d[3]),"+f"(d[4]),"+f"(d[5]),"+f"(d[6]),"+f"(d[7]),"+f"(d[8]),"+f"(d[9]),"+f"(d[10]),"+f"(d[11]),"+f"(d[12]),"+f"(d[13]),"+f"(d[14]),"+f"(d[15]),"+f"(d[16]),"+f"(d[17]),"+f"(d[18]),"+f"(d[19]),"+f"(d[20]),"+f"(d[21]),"+f"(d[22]),"+f"(d[23]),"+f"(d[24]),"+f"(d[25]),"+f"(d[26]),"+f"(d[27]),"+f"(d[28]),"+f"(d[29]),"+f"(d[30]),"+f"(d[31]),"+f"(d[32]),"+f"(d[33]),"+f"(d[34]),"+f"(d[35]),"+f"(d[36]),"+f"(d[37]),"+f"(d[38]),"+f"(d[39]),"+f"(d[40]),"+f"(d[41]),"+f"(d[42]),"+f"(d[43]),"+f"(d[44]),"+f"(d[45]),"+f"(d[46]),"+f"(d[47]),"+f"(d[48]),"+f"(d[49]),"+f"(d[50]),"+f"(d[51]),"+f"(d[52]),"+f"(d[53]),"+f"(d[54]),"+f"(d[55]),"+f"(d[56]),"+f"(d[57]),"+f"(d[58]),"+f"(d[59]),"+f"(d[60]),"+f"(d[61]),"+f"(d[62]),"+f"(d[63]),"+f"(d[64]),"+f"(d[65]),"+f"(d[66]),"+f"(d[67]),"+f"(d[68]),"+f"(d[69]),"+f"(d[70]),"+f"(d[71]),"+f"(d[72]),"+f"(d[73]),"+f"(d[74]),"+f"(d[75]),"+f"(d[76]),"+f"(d[77]),"+f"(d[78]),"+f"(d[79]) : "r"(a[0]),"r"(a[1]),"r"(a[2]),"r"(a[3]),"l"(db),"r"(sc));
}
__device__ __forceinline__ void wg_ss8_10(float* d, uint64_t da, uint64_t db, int sc) {
  asm volatile("{.reg .pred p; setp.ne.b32 p, %6, 0; wgmma.mma_async.sync.aligned.m64n8k16.f32.bf16.bf16 {%0,%1,%2,%3}, %4, %5, p, 1, 1, 1, 0;}"
    : "+f"(d[0]),"+f"(d[1]),"+f"(d[2]),"+f"(d[3]) : "l"(da),"l"(db),"r"(sc));
}
__device__ __forceinline__ void wg_ss8_if(float* d, uint64_t da, uint64_t db, int sc, int skip) {
  asm volatile("{.reg .pred p, q; setp.ne.b32 p, %6, 0; setp.eq.b32 q, %7, 0; @q wgmma.mma_async.sync.aligned.m64n8k16.f32.bf16.bf16 {%0,%1,%2,%3}, %4, %5, p, 1, 1, 1, 0;}"
    : "+f"(d[0]),"+f"(d[1]),"+f"(d[2]),"+f"(d[3]) : "l"(da),"l"(db),"r"(sc),"r"(skip));
}

constexpr uint32_t DB = 1024;
constexpr int UNIT = 8192, WSLOT = 16384, W2TILE = 24576, OFF_R = 12 * UNIT;
constexpr int OFF_PB = 26 * UNIT;
constexpr int OFF_CV = OFF_PB + 16384, OFF_ST = OFF_CV + 768, OFF_TS = OFF_ST + 256, OFF_MODR = OFF_TS + 512, OFF_ROLE = OFF_MODR + 80, OFF_BAR = OFF_ROLE + 16, SMEM_BYTES = OFF_BAR + 1368;
constexpr int OFF_BX = OFF_PB, OFF_AX = OFF_BX + 12288, OFF_RT = OFF_AX + 2048, OFF_GB = OFF_RT + 512, OFF_CO = OFF_CV;
constexpr int OFF_UV = 4 * UNIT, OFF_SX = 24 * UNIT, OFF_XCH = 12 * UNIT;
constexpr int OFF_Q = 99328, KV_V = 4096, KV_H = 8192, F_E = 128, F_O = 4288, OFF_WM = 20 * UNIT, OFF_TAP = 12672, OFF_MR = 25 * UNIT;
constexpr uint64_t pk5(int a, int b, int c, int d, int e) { return (uint64_t)(a / 128) | (uint64_t)(b / 128) << 12 | (uint64_t)(c / 128) << 24 | (uint64_t)(d / 128) << 36 | (uint64_t)(e / 128) << 48; }
constexpr uint64_t T_KV = pk5(119808, 16384, 130048, 65536, 49152), T_F = pk5(140288, 90368, 148736, 81920, OFF_PB), T_X = pk5(0, 4224, 8448, 0, 4224),
                   T_P = pk5(32768, 16384, 65536, 81920, OFF_PB);
__host__ __device__ __forceinline__ uint32_t tab(uint64_t t, int c) { return ((uint32_t)(t >> (12 * c)) & 0xFFF) << 7; }
enum { B_KV = 0, B_FRAW = 5, B_Q = 10, B_WM = 15, B_XR = 17, B_MR = B_XR + 5, B_QTOK, B_ST1, B_MODR, B_ROLE = B_MODR + 5, B_FL = 32, B_PFULL = B_FL + 5, B_PEMPTY = B_PFULL + 5, B_FRDY = B_PEMPTY + 5,
       B_G = B_FRDY + 5, B_EXT = B_G + 2, B_QTD, B_ED, B_S2 = B_ED + 2, B_GB, B_FULL = 60, B_RETRY = B_FULL + 43, B_XFREE = B_RETRY + 8, B_BX, B_UVB, B_CO, B_SX, B_EMPTY = 121, B_SC = 164, B_STD = B_SC + 5, B_LAG };
static_assert(B_ROLE < B_FL && B_GB < B_FULL && B_SX + 5 <= B_EMPTY - 1 && OFF_MR == OFF_SX + 8192 && SMEM_BYTES <= 232448, "barrier groups");
#define BAR(i) (base + OFF_BAR + 8 * (i))

struct Maps { CUtensorMap km, v, q, fm, wmp, kh, tap, wm, w1a, w3a, xs, w1u, w3u, w1b, w3b, x1s, x1b, w2a, w2b, outa, outb; };
struct Ptrs { const bf16 *c, *ssmd; Scratch* g; uint64_t prog[2]; uint32_t gate[5]; int ulo; uint32_t mq, xh, xdep, hstart, hpause, hl[8], uvd, mpos, wt0, wpace; float one; uint32_t wdep[30], adep[14]; uint2 w2t[12]; int hid[3][9]; };

#define REGION_IDS int tid, lane, bid; \
  asm volatile("mov.u32 %0, %%tid.x;" : "=r"(tid)); asm volatile("mov.u32 %0, %%laneid;" : "=r"(lane)); asm volatile("mov.u32 %0, %%ctaid.x;" : "=r"(bid)); \
  const int i0 = tid & 127; (void)i0; (void)lane; (void)bid

#define ffn_role(h, j, r) do { \
  mbar_wait(BAR(B_ROLE)); \
  r = __shfl_sync(~0u, lds32(base + OFF_ROLE), 0); \
  asm volatile("mov.u32 %0, %%ctaid.x;" : "=r"(h)); \
  h &= 1; j = r >> 4; r &= 15; } while (0)
__device__ __forceinline__ void rank_pair(Scratch* G, uint32_t base, uint32_t epoch, bool put) {
  REGION_IDS;
  uint32_t t;
  asm volatile("mov.u32 %0, %%smid;" : "=r"(t));
  t >>= 1;
  const uint32_t q = (t - 32) * 37 >> 8, g = t < 32 ? t & 7 : t < 60 ? t - 31 - 7 * q : t < 62 ? t - 54 : 0;
  const uint32_t key = epoch << 20 | (g & 3) << 18 | (g & 4) << 15 | (t & 127) << 6 | bid >> 1;
  if (put) {
    if (lane == (bid & 1) * 99) publish(&G->key[bid >> 1], key);
    return;
  }
  uint2 x;
  int it = 0;
#pragma unroll 1
  do x = ld_relaxed64(&G->key[2 * lane]); while (__any_sync(~0u, ((x.x ^ key) | (x.y ^ key)) >> 20) && ++it < SPIN_LIMIT);
  sts32(base + OFF_ROLE, __popc(__ballot_sync(~0u, x.x < key)) + __popc(__ballot_sync(~0u, x.y < key)));
  arrive1(BAR(B_ROLE));
}
__device__ __forceinline__ int mod_ch(int p) { return p < 40 ? (p >> 3) * 128 + (p & 1) * 64 : 64 * (p < 50 ? p - 40 : p - 50); }
__device__ __forceinline__ int mod_col(int p) { return mod_ch(p) + 640 * (p < 40 ? 0x4210 >> (2 * (p & 6)) & 7 : p < 50 ? 3 : 5); }
__device__ __forceinline__ uint32_t mod_sum(uint2 v) { return pack_bf16(0.f, __uint_as_float(v.x) + __uint_as_float(v.y)); }
#define UVS 5
#define XP 2
#define GA 3
#define GB 1
#define HL 0
#define EH 0
#define MG 4
#define SG 0x88
#define LAG2 38
#define NP 8
__device__ __forceinline__ int nib(uint32_t t, int i) { return (t >> (4 * i)) & 15; }
__device__ __forceinline__ int w_block(int up, int m) { return m < 2 ? 2 * up + m : 4 + up; }
__host__ __device__ constexpr int w2_at(int v) { return UNIT * (v == 1 ? 0 : 0x0811030C18ull >> (v - (v > 1)) % 5 * 8 & 255); }
__host__ __device__ constexpr int hid_at(int m, int g) { return UNIT * ((g ? 0x0200150710ull : 0x010B14060Full) >> m % 5 * 8 & 255); }
__host__ __device__ constexpr int x1_at(int k) { return k < 4 ? 22 * UNIT + 4096 * k : OFF_BX + UNIT; }
__host__ __device__ constexpr uint32_t w2_desc(int v) { return (DB + w2_at(v)) >> 4 | UNIT << 12; }
__host__ __device__ constexpr int a_at(int n) { return WSLOT * (0x54323251041032ull >> 4 * n & 15); }
__host__ __device__ constexpr int second(int v) { return 0xDCBA657498ull >> 4 * v & 15; }

#define ORDER "k1v1f0q0q1q2q3q4k2v2f1k3v3f2k4v4f3w0f4"
constexpr int NL = sizeof(ORDER) / 2, NG = 2, TA = 16, M8 = 3 << TA / 8;
__host__ __device__ constexpr int load_bar(int e) { return e < 0 ? B_KV : ORDER[2 * e + 1] - '0' + (ORDER[2 * e] == 'q' ? B_Q : ORDER[2 * e] == 'f' ? B_FRAW : ORDER[2 * e] == 'w' ? B_WM : B_KV); }
template <int E> __device__ __forceinline__ void loads(const Ptrs& P, const Maps& maps, uint32_t base) {
  if constexpr (E < NL) {
    constexpr int r = ORDER[2 * E + 1] - '0';
    constexpr char x = ORDER[2 * E];
    const int c0 = 128 * r + 64 * (blockIdx.x & 1), c1 = 2 * (blockIdx.x & 126);
    const uint32_t g = P.gate[E / 4] >> 8 * (E & 3) & 255;
    if (E >= NG) mbar_wait(BAR(opaque(g >> 1)), g & 1);
    if (elect()) {
      if (x == 'k') { tma3d(base + tab(T_KV, r), &maps.km, c0, c1, 0, BAR(B_KV + r)); tma3d(base + tab(T_KV, r) + KV_H, &maps.kh, c0, c1 - 1, 5, BAR(B_KV + r)); }
      if (x == 'v') tma3d(base + tab(T_KV, r) + KV_V, &maps.v, c0, c1, 0, BAR(B_KV + r));
      if (x == 'q') tma3d(base + OFF_Q + 4096 * r, &maps.q, c0, c1, 0, BAR(B_Q + r));
      if (x == 'f') tma3d(base + tab(T_F, r) + F_E, &maps.fm, 0, 0, 128 * r + blockIdx.x, BAR(B_FRAW + r));
      if (x == 'w') tma3d(base + OFF_WM, &maps.wmp, mod_col(TA + (blockIdx.x >> 3)), 80 * (blockIdx.x & 7), 0, BAR(B_WM));
    }
    loads<E + 1>(P, maps, base);
  }
}

template <int U> __device__ __forceinline__ void cstep(float* acc, const uint32_t* A, uint64_t db) {
  const uint32_t* a = A + 4 * U;
  const uint64_t d = db + 16 * U;
  if (U == 4) { wg_rs64_0(acc + 96, A, db + 192, 0); wg_rs48_0(acc + 96, A + 4, db + 208, 1); wg_rs32_0(acc + 96, A + 8, db + 224, 1); wg_rs16_0(acc + 96, A + 12, db + 240, 1); }
  if (U <= 4) wg_rs192_0(acc, a, d, U);
  if (U == 5) wg_rs176_0(acc, a, d, 1);
  if (U == 6) wg_rs160_0(acc, a, d, 1);
  if (U == 7) wg_rs144_0(acc, a, d, 1);
  if (U == 8) wg_rs128_0(acc, a, d, 1);
  if (U == 9) wg_rs112_0(acc, a, d, 1);
  if (U == 10) wg_rs96_0(acc, a, d, 1);
  if (U == 11) wg_rs80_0(acc, a, d, 1);
  if (U == 12) wg_rs64_0(acc, a, d, 1);
  if (U == 13) wg_rs48_0(acc, a, d, 1);
  if (U == 14) wg_rs32_0(acc, a, d, 1);
  if (U == 15) wg_rs16_0(acc, a, d, 1);
}
template <int U0, int U1> __device__ __forceinline__ void csteps(float* acc, const uint32_t* A, uint64_t db) {
  cstep<U0>(acc, A, db);
  if constexpr (U0 > U1) csteps<U0 - 1, U1>(acc, A, db);
}
template <int U0, int U1> __device__ __forceinline__ void cload(uint32_t* A, uint32_t fa) {
  asm volatile("{ld.shared.b32 %0, [%4+%5]; ld.shared.b32 %1, [%4+%5+128]; ld.shared.b32 %2, [%4+%5+16]; ld.shared.b32 %3, [%4+%5+144];}"
               : "=r"(A[4 * U0]), "=r"(A[4 * U0 + 1]), "=r"(A[4 * U0 + 2]), "=r"(A[4 * U0 + 3]) : "r"(fa), "n"(256 * U0) : "memory");
  if constexpr (U0 > U1) cload<U0 - 1, U1>(A, fa);
}

template <int NK> __device__ __forceinline__ void mod_gemv(Scratch* G, uint32_t wm, int p, int part, int w, int lane, uint32_t par) {
  float d[4] = {};
  fence_regs(d);
  wg_fence();
#pragma unroll 1
  for (int k = 0; k < NK; k += 5) {
#pragma unroll
    for (int i = 0; i < 5; i++) wg_ss8_10(d, mkdesc(DB + wm + 2048 * (k + i), 16, 1024, 1), mkdesc(DB + OFF_CV + 32 * (k + i), 16, 128, 0), 1);
  }
  wg_commit();
  const int ch = mod_ch(p) + 16 * w + (lane >> 2);
  uint32_t* dst = (p < 40 ? &G->modc[ch & 127][p >> 3][4 * (p & 6)] : (uint32_t*)&G->modv[p >= 50][ch]) + part;
  wg_wait<0>();
  fence_regs(d);
  if (!(lane & 3)) {
    publish(dst, (__float_as_uint(d[0]) & ~1u) | par);
    publish(dst + (p < 40 ? 1280 : 16), (__float_as_uint(d[2]) & ~1u) | par);
    if (NK == 20 && p < 40 && (p & 6) == 6) {
      dst = (uint32_t*)&G->modv[2][ch] + part;
      publish(dst, (__float_as_uint(d[0]) & ~1u) | par);
      publish(dst + 16, (__float_as_uint(d[2]) & ~1u) | par);
    }
  }
}
__device__ __forceinline__ void mod_fetch(Scratch* G, uint32_t base, uint32_t epoch, uint32_t m8, uint32_t c, uint32_t c1) {
  REGION_IDS;
  const uint32_t* mp = &G->modc[bid][0][lane];
  auto unused = [&]() { return (lane & 6) && !(m8 >> c & 1); };
#pragma unroll 1
  for (int it = 0; c < c1 && it < SPIN_LIMIT; it++) {
    uint32_t m = ld_relaxed32(mp + 32 * c);
    const uint32_t m1 = ld_relaxed32(mp + 32 * min(c + 1, c1 - 1));
#pragma unroll 1
    for (int k = 0; k < 2 && c < c1 && __all_sync(~0u, unused() || !((m ^ epoch) & 1)); k++) {
      float x = unused() ? 0.f : __uint_as_float(m);
      x += __shfl_xor_sync(~0u, x, 1); x += __shfl_xor_sync(~0u, x, 2); x += __shfl_xor_sync(~0u, x, 4);
      const uint32_t y = __byte_perm(badd2(pack_bf16(0.f, x), (lane & 8) * 0x07F00000u), 0, 0x3232), ga = __shfl_sync(~0u, y, 16);
      sts32(base + OFF_MODR + 16 * c + 4 * (lane >> 3), lane < 16 ? bmul2(y, ga) : y);
      arrive1(BAR(B_MODR + c));
      if (lane >= 30 && (m8 >> c & 1)) publish((uint32_t*)&G->modv[2][128 * c + bid] + (lane & 1), ((lane & 1 ? 0 : __float_as_uint(x)) & ~1u) | (epoch & 1));
      m = m1;
      c++;
    }
  }
}
__device__ __forceinline__ void add4(uint4& y, const uint4& z) { y.x = badd2(y.x, z.x); y.y = badd2(y.y, z.y); y.z = badd2(y.z, z.z); y.w = badd2(y.w, z.w); }
template <bool FIRST> __device__ __forceinline__ void e_round(Scratch* G, uint32_t base, uint32_t sa, uint4*& gp, uint4* q, int c, int w, uint32_t tag, uint32_t epoch) {
  constexpr int QO = -D_ * 256;
  mbar_wait(BAR(B_MODR + c));
  const uint4 co = lds128(base + OFF_MODR + 16 * c);
  mbar_wait(BAR(B_PFULL + c));
  const uint32_t pb = sa + tab(T_P, c);
  uint4 l[2][6];
  auto load = [&](int hf, int k) { l[hf][k] = lds128((k < 4 ? pb + 4096 * k : sa + OFF_MR + 4096 * (k - 4)) + 2048 * hf); };
#pragma unroll
  for (int hf = 0; hf < 2; hf++) {
    uint4 &y = l[hf][0], &z = l[hf][4], &m = l[hf][5];
    load(hf, 0);
    if (!FIRST) {
      load(hf, 1);
      add4(y, l[hf][1]);
      load(hf, 2); load(hf, 3);
      add4(l[hf][2], l[hf][3]);
      add4(y, l[hf][2]);
    }
    load(hf, 4); load(hf, 5);
    if (FIRST) {
#pragma unroll 1
      for (int it = 0; __any_sync(~0u, ((z.x >> 15 ^ epoch) | (m.x ^ epoch)) & tag) && it < SPIN_LIMIT; it++) {
        const uint4* sp = (const uint4*)G->st1 + (opaque(sa) - base >> 4) + 128 * hf;
        z = ld_relaxed128(sp);
        m = ld_relaxed128(sp + 256);
        sts128(sa + OFF_MR + 2048 * hf, z.x, z.y, z.z, z.w);
        sts128(sa + OFF_MR + 2048 * hf + 4096, m.x, m.y, m.z, m.w);
      }
      z.x &= 0xFFFF7FFFu;
      sts32(sa + OFF_MR + 2048 * hf, z.x);
    }
#pragma unroll 1
    for (int it = 0; __any_sync(~0u, (q[hf].x ^ epoch) & tag) && it < SPIN_LIMIT; it++) {
      q[hf] = ld_relaxed128(gp + QO + 128 * hf);
    }
    y.x = bfma2(bfma2(bfma2(q[hf].x, z.x, m.x), co.y, co.x), y.x, q[hf].x);
    auto hint = [&]() {
      __syncwarp();
      asm volatile("{.reg .pred p; elect.sync _|p, 0xffffffff; @p red.relaxed.gpu.global.add.u32 [%0], 1; @p mbarrier.arrive.shared::cta.b64 _, [%1];}"
                   ::"l"(G->xsh[c][2 * w + (blockIdx.x >> 6)]), "r"(BAR(B_PEMPTY + c)), "r"(y.x) : "memory");
    };
    if (hf && !EH) hint();
    y.y = bfma2(bfma2(bfma2(q[hf].y, z.y, m.y), co.y, co.x), y.y, q[hf].y);
    y.z = bfma2(bfma2(bfma2(q[hf].z, z.z, m.z), co.y, co.x), y.z, q[hf].z);
    y.w = bfma2(bfma2(bfma2(q[hf].w, z.w, m.w), co.y, co.x), y.w, q[hf].w);
    st_relaxed128(gp + 128 * hf, set_tag(bmul2(y.x, co.w), tag, epoch), bmul2(y.y, co.w), bmul2(y.z, co.w), bmul2(y.w, co.w));
    if (hf && EH == 1) hint();
    asm volatile("{.reg .pred p; .reg .b32 t; setp.ne.u32 p, %5, 0; max.u32 t, %1, 1; @!p st.relaxed.gpu.global.v4.u32 [%0+%6], {t,%2,%3,%4}; @p st.relaxed.gpu.global.v4.u32 [%0+%7], {t,%2,%3,%4};}"
                 ::"l"(gp + 128 * hf), "r"(y.x), "r"(y.y), "r"(y.z), "r"(y.w), "r"(epoch & 1), "n"(D_ * 4096), "n"(D_ * 8192) : "memory");
    if (hf && EH == 2) hint();
    if (c < 4) q[hf] = ld_relaxed128(gp + QO + 32768 + 128 * hf);
  }
  gp += 32768;
}
__device__ __forceinline__ void q_stats(uint32_t base, int w) {
  REGION_IDS;
  float s0 = 0.f, s1 = 0.f, q0 = 0.f, q1 = 0.f;
  const uint32_t a = OFF_Q + 1024 * w + 128 * (lane & 7) + (((lane >> 3) ^ (lane & 7)) << 4);
  const uint32_t ra = mapa(base + OFF_ST + 128 * (bid & 1) + 64 * (lane & 1) + 16 * w + 8 * (lane >> 2), lane >> 1 & 1), rb = mapa(BAR(B_ST1), lane >> 1 & 1);
  if (w == 3 && elect()) mbar_expect_tx(BAR(B_ST1), 256);
#pragma unroll 1
  for (int k = 0; k < 5; k++) {
    mbar_wait(BAR(B_Q + k));
    const uint32_t o = opaque(base + 4096 * k);
    const uint4 x = lds128(o + a), y = lds128(o + (a ^ 64));
    const uint32_t e[8] = {x.x, x.y, x.z, x.w, y.x, y.y, y.z, y.w};
#pragma unroll
    for (int i = 0; i < 8; i++) { const float lo = bf_lo(e[i]), hi = bf_hi(e[i]); s0 += lo; s1 += hi; q0 = fmaf(lo, lo, q0); q1 = fmaf(hi, hi, q1); }
  }
  s0 += s1; q0 += q1;
  arrive1(BAR(B_STD));
  s0 += __shfl_xor_sync(~0u, s0, 8); q0 += __shfl_xor_sync(~0u, q0, 8);
  s0 += __shfl_xor_sync(~0u, s0, 16); q0 += __shfl_xor_sync(~0u, q0, 16);
  if (lane < 8) asm volatile("st.async.shared::cluster.mbarrier::complete_tx::bytes.v2.b32 [%0], {%1,%2}, [%3];" ::"r"(ra), "r"(__float_as_uint(s0)), "r"(__float_as_uint(q0)), "r"(rb) : "memory");
}
__device__ __forceinline__ void short_conv(Scratch* G, uint32_t base, int s, int w, uint32_t par, uint32_t xh) {
  REGION_IDS;
  const uint32_t a = base + tab(T_KV, s) + 128 * (lane & 3) + ((w ^ (lane & 3)) << 4) + 4 * (lane & 16) + (lane & 12), keep = ~(lane & 1);
  uint4* dst = G->xr + (128 * s + 64 * (bid & 1) + 8 * w + 2 * (lane & 16) + (lane >> 1 & 6)) * 256 + 255 - 4 * (bid >> 1) - (lane & 3);
  mbar_wait(BAR(B_KV));
  mbar_wait(BAR(B_KV + s));
  const uint4 wv = lds128(base + OFF_TAP + 512 * s + 64 * w + 16 * (lane & 16) + 4 * (lane & 12));
  uint32_t kk[11], r[8];
#pragma unroll
  for (int k = 0; k < 11; k++) kk[k] = k < 3 ? lds32((a ^ (64 * (k & 1))) + KV_H + 512 * k) : lds32((a ^ (64 * (~k & 1))) + 512 * (k - 3));
  if (xh == 0 && elect()) red_hint(G->hint[s][4 * (bid & 1) + w]);
#pragma unroll
  for (int k = 0; k < 8; k++) r[k] = lds32((a ^ (64 * (k & 1))) + KV_V + 512 * k);
  arrive1(BAR(B_SC + s));
  const uint32_t w0 = __byte_perm(wv.x, wv.z, 0x5410), w1 = __byte_perm(wv.x, wv.z, 0x7632),
                 w2 = __byte_perm(wv.y, wv.w, 0x5410), w3 = __byte_perm(wv.y, wv.w, 0x7632);
#pragma unroll
  for (int k = 0; k < 8; k++) r[k] = bmul2(bfma2(kk[k + 3], w0, bfma2(kk[k + 2], w1, bfma2(kk[k + 1], w2, bmul2(kk[k], w3)))), r[k]);
  const uint32_t bit = ~par >> 7 & lane & 1;
  if (xh == 1 && elect()) red_hint(G->hint[s][4 * (bid & 1) + w]);
  st_relaxed128(dst, (__byte_perm(r[7], r[6], 0x5410) & keep) | bit, __byte_perm(r[5], r[4], 0x5410), __byte_perm(r[3], r[2], 0x5410), __byte_perm(r[1], r[0], 0x5410));
  st_relaxed128(dst + 256, (__byte_perm(r[7], r[6], 0x7632) & keep) | bit, __byte_perm(r[5], r[4], 0x7632), __byte_perm(r[3], r[2], 0x7632), __byte_perm(r[1], r[0], 0x7632));
  if (xh == 2 && elect()) red_hint(G->hint[s][4 * (bid & 1) + w]);
}
__device__ __forceinline__ void silu_vector(const bf16* c, int n, uint32_t base) {
  REGION_IDS;
  if (tid < n) {
    const uint32_t x = ldg32(c + 2 * tid);
    sts32(base + OFF_CV + 4 * tid, pack_bf16(silu_f(bf_lo(x)), silu_f(bf_hi(x))));
  }
  fence_async_smem();
}

template <int FIRST> __global__ void __cluster_dims__(2, 1, 1) __launch_bounds__(512, 1) k_fused(const __grid_constant__ Ptrs P, const __grid_constant__ Maps maps) {
  Scratch* const G = P.g;
  extern __shared__ __align__(1024) uint8_t smem_raw[];
  const uint32_t t_start = clock();
  const uint32_t base = __shfl_sync(~0u, smem_u32(smem_raw), 0);
  if (threadIdx.x == 416 && blockIdx.x + FIRST < 128) {
    const int c0 = 64 * (blockIdx.x & 1), c1 = 2 * (blockIdx.x & 126);
    mbar_init<1>(BAR(B_KV), 1);
    mbar_expect_tx(BAR(B_KV), 12288);
    tma3d(base + tab(T_KV, 0), &maps.km, c0, c1, 0, BAR(B_KV));
    tma3d(base + tab(T_KV, 0) + KV_V, &maps.v, c0, c1, 0, BAR(B_KV));
    tma3d(base + tab(T_KV, 0) + KV_H, &maps.kh, c0, c1 - 1, 5, BAR(B_KV));
    tma3d(base + OFF_TAP, &maps.tap, 0, blockIdx.x & 1, 0, BAR(B_KV));
  }
  if ((base & 0xFFFFFFu) != DB) __trap();
  const int wid = __shfl_sync(~0u, threadIdx.x >> 5, 0), wg = wid >> 2, w = wid & 3;
  if (blockIdx.x + FIRST >= 128) {
    REGION_IDS;
    auto unit = [&](int n) { return 4 * (P.hl[n >> 2] >> 8 * (n & 3) & 255) + (bid & 3); };
    auto fetch = [&](int n, int b) {
      if (unit(n) < 120 && elect()) {
        mbar_expect_tx(BAR(n), 40960);
#pragma unroll 1
        for (int k = 0; k < 5; k++) tma3d(base + 40960 * b + 8192 * k, &maps.wm, mod_col(unit(n) >> 1), 320 * (bid & 1) + 64 * k, 0, BAR(n));
      }
    };
    if (wid == 0) {
      mbar_init<4>(BAR(0), 1);
#pragma unroll 1
      for (int n = 0; n < 4; n++) { wait_clock(t_start + (P.hstart & 0xFFFF) + n * (P.hstart >> 16)); fetch(n, n); }
      mbar_init<28>(BAR(4), 1);
    }
    const uint32_t par = ~ld_relaxed32(G->hint[7][0]) >> 7 & 1;
    silu_vector(P.c + 320 * (bid & 1), 160, base);
    __syncthreads();
#pragma unroll 1
    for (int n = wg; unit(n) < 120; n += 4) {
      mbar_wait(BAR(n));
      mod_gemv<20>(G, 40960 * (n % 5), unit(n) >> 1, bid & 1, w, lane, par);
      named_bar(1 + wg, 128);
      if (w == 0) {
        wait_clock(t_start + P.hpause);
        if (n == 0) fetch(4, 4);
        fetch(n + 5, n % 5);
      }
    }
    return;
  }
  mbar_init<3>(BAR(wid < 15 ? 4 * wid + 1 : B_SC + 1), wid < 8 ? 1 : 4);
  mbar_init<1>(BAR(!wid ? B_SC + 4 : wid < 15 ? 4 * wid : B_SC), wid && wid < 8 ? 1 : 4);
  if (wid == 0) mbar_init<2>(BAR(B_SC + 5), 4);
  asm volatile("fence.mbarrier_init.release.cluster; bar.sync 0, 512;" ::: "memory");
  asm volatile("barrier.cluster.arrive.relaxed.aligned;" ::: "memory");
#define LAUNCHES const uint32_t launches = ld_relaxed32(G->hint[7][blockIdx.x >> 4])
#define EPOCH ((__shfl_sync(~0u, launches, 0) >> 7) + 1)
  if (wg < 2) {
    asm volatile("setmaxnreg.inc.sync.aligned.u32 224;");
    LAUNCHES;
    uint32_t par = launches;
    {
      float acc[128];
      uint32_t A[64];
#pragma unroll
      for (int i = 0; i < 64; i++) asm volatile("" : "=r"(A[i]));
      int c = wg;
#pragma unroll 1
      for (uint64_t prog = P.prog[wg]; prog; prog >>= 8) {
        REGION_IDS;
        const int s = prog & 7;
        if (s < 5) short_conv(G, base, s, w, par, P.xh);
        if (prog == P.prog[wg]) cluster_wait();
        if (prog & 16) {
          mbar_wait(BAR(B_QTD));
          mbar_wait(BAR(B_WM));
          mod_gemv<5>(G, OFF_WM, TA + (bid >> 3), bid & 7, w, lane, ~par >> 7 & 1);
          arrive1(BAR(B_G));
        }
        if (prog & 8) q_stats(base, w);
        if (prog & 32) {
          const int L = 16 * w + (lane >> 2) + 2 * (lane & 3) - 7;
          const uint32_t fo = base + ((L & 1) ? F_O + 2 * (L + 1) : F_E + 2 * L);
          mbar_wait(BAR(B_FRDY + c));
          cload<0, 0>(A, fo + tab(T_F, c));
          cload<15, 1>(A, fo + tab(T_F, c));
          arrive1(BAR(B_FL + c));
        }
        if (!(prog & 64)) continue;
        uint32_t xo;
#pragma unroll 1
        for (int it = 0; it < SPIN_LIMIT; it++) {
          xo = tab(T_X, opaque(c));
          mbar_wait(BAR(B_XR + c), it & 1);
          const uint32_t tag = lds32(base + xo + 32 * i0);
          wg_fence();
          csteps<0, 0>(acc, A, mkdesc(DB + xo, 16, 128, 0));
          csteps<15, 6>(acc, A, mkdesc(DB + xo, 16, 128, 0));
          wg_commit();
          if (bar_all(1 + wg, (tag ^ par >> 7) & 1)) break;
          wg_wait<0>();
          if (w == 0 && elect()) { mbar_expect_tx(BAR(B_XR + c), 4096); bulk_load(base + xo, G->xr + (128 * c + bid) * 256, 4096, BAR(B_XR + c)); }
        }
        wg_fence();
        csteps<5, 1>(acc, A, mkdesc(DB + tab(T_X, opaque(c)), 16, 128, 0));
        wg_commit();
        mbar_wait(BAR(B_SC + (c == 2 ? 3 : c)));
        wg_wait<0>();
        fence_regs(acc);
        const uint32_t pb = base + tab(T_P, c) + 4096 * w;
#pragma unroll
        for (int k = 0; k < 8; k++) {
          uint32_t p[4];
#pragma unroll
          for (int e = 0; e < 4; e++) { const int i = 4 * k + e; p[e] = i < 31 ? pack_bf16(acc[4 * i] + acc[4 * i + 6], acc[4 * i + 1] + acc[4 * i + 7]) : pack_bf16(acc[124], acc[125]); }
          if (k == 0 && (lane & 3) < w) p[0] = 0;
          stmatrix_x4_t(k == 0 ? pb + 16 * ((255 - lane + 2 * w) & 255) : pb + 16 * (255 - lane + 2 * w) - 512 * k, p[0], p[1], p[2], p[3]);
        }
        arrive1(BAR(B_PFULL + c));
        c += 2;
      }
    }
    par = ~par >> 7 & 1;
    uint32_t ck;
    { REGION_IDS; ck = base + wg * UNIT + lane * 128 + (((2 * w) ^ (lane & 7)) << 4); }
    const uint32_t abd = DB + wg * UNIT;
    auto tags = [&](int as, bool first) { return (lds32(ck + as) ^ par) | (lds32(ck + as + (first ? 4096 : 256)) ^ par); };
    int role;
    { int h, j, r; ffn_role(h, j, r); role = (2 * r + (h ^ wg)) * 8 + 4 * h + j; }
    auto a_tile = [&](int as, int n, bool first) {
#pragma unroll 1
      for (int it = 0; __any_sync(~0u, tags(as, first) & 1) && it < SPIN_LIMIT; it++) {
        if (elect()) {
          mbar_expect_tx(BAR(B_RETRY + wid), UNIT);
          if (first) tma2d(base + wg * UNIT + as, &maps.xs, 8 * role & ~63, 64 * n, BAR(B_RETRY + wid));
          else bulk_load(base + as, G->hh + ((role & ~3) + ((role + n) & 3)) * 1536 + (n >> 2) * 512, UNIT, BAR(B_RETRY + wid));
        }
        mbar_wait(BAR(B_RETRY + wid), par >> 1);
        par ^= 2;
      }
    };
    float acc[128], acb[64];
    int ws = 0;
    float d[8];
    uint32_t *ud0, *ud1;
    unsigned* uh;
    {
      REGION_IDS;
      const int r = role >> 4, row = (r & 14) + (lane >> 2 & 1);
      ud0 = &G->uv[role & 7][32 * row + 4 * ((2 * w ^ row) & 7) + (lane & 3)];
      ud1 = ud0 + 512 * w_block(r & 1, 2);
      ud0 += 512 * w_block(r & 1, wg);
      uh = G->hint[8][role & 7];
      asm volatile("" : "+l"(ud0), "+l"(ud1), "+l"(uh));
    }
    auto step = [&](int n, int uv) {
      const int as = a_at(n);
      const uint64_t da = mkdesc(abd + as, 16, 1024, 1), db = mkdesc(DB + OFF_R + ws, 4096, 1024, 1);
      mbar_wait(BAR(B_FULL + 2 * n));
      a_tile(as, n, true);
      if (uv == 1) { mbar_wait(BAR(B_UVB)); mbar_wait(BAR(B_CO)); }
      wg_fence();
#pragma unroll
      for (int k = 0; k < 4; k++) {
        wg_ss64_11(acc + 96, da + 128 * k, db + 768 + 128 * (k & 1) + 1024 * (k >> 1), k ? 1 : n);
        if (k == GA - 1) { wg_commit(); wg_wait<1>(); if (elect()) mbar_arrive(BAR(B_EMPTY + 2 * n - 1)); if (uv == 2) fence_regs(d); }
      }
      if (uv == 1) {
#pragma unroll
        for (int k = 0; k < 5; k++) {
          wg_ss8_10(d, mkdesc(DB + OFF_UV + 2048 * wg + 6144 * k, 16, 1024, 1), mkdesc(DB + OFF_CO + 64 * k, 32, 128, 0), k);
        }
        if (!wg) {
#pragma unroll
          for (int k = 0; k < 5; k++) wg_ss8_10(d + 4, mkdesc(DB + OFF_UV + 4096 + 6144 * k, 16, 1024, 1), mkdesc(DB + OFF_CO + 64 * k, 32, 128, 0), k);
        }
      }
#pragma unroll
      for (int k = 0; k < 4; k++) wg_ss192_11(acc, da + 128 * k, db + 128 * (k & 1) + 1024 * (k >> 1), k ? 1 : n);
      wg_commit();
      ws = ws == 4 * WSLOT ? 0 : ws + 2 * WSLOT;
      if (uv == 2) {
        split(P.ulo, 30);
        REGION_IDS;
        const uint32_t tag = !(lane & 3);
        if (elect()) red_hint(uh);
        uint32_t x[4];
#pragma unroll
        for (int k = 0; k < 4; k++) asm volatile("movmatrix.sync.aligned.m8n8.trans.b16 %0, %1;" : "=r"(x[k]) : "r"(pack_bf16(d[2 * k], d[2 * k + 1])));
        const uint32_t y1 = __shfl_up_sync(~0u, x[1], 8), y3 = __shfl_up_sync(~0u, x[3], 8);
        if (lane < 16) {
          st_relaxed32((uint32_t*)((uint64_t)ud0 ^ 2 * (lane & 8)), set_tag(lane < 8 ? x[0] : y1, tag, par));
          if (!wg) st_relaxed32((uint32_t*)((uint64_t)ud1 ^ 2 * (lane & 8)), set_tag(lane < 8 ? x[2] : y3, tag, par));
        }
      }
    };
#pragma unroll 1
    for (int n = 0; n < UVS; n++) step(n, 0);
    step(UVS, 1);
    step(UVS + 1, 2);
#pragma unroll 1
    for (int n = UVS + 2; n < 10; n++) step(n, 0);
    float o[80];
    uint32_t fr[3][16], bo;
    {
      REGION_IDS;
      float r0, r1, s0, s1;
      const int id = role, j = role;
      uint4* const hdst = G->hh + id * 1536 + 128 * w + (lane ^ lane >> 3);
      const uint32_t keep = ~(~lane & 1), bit = par & ~keep;
      bo = 1024 + ((j & 1) << 23);
      auto own = [&](int i) { wg_rs160_1(o, fr[i >> 2] + 4 * (i & 3), mkdesc(DB + w2_at(i / 4) + (i & 3) * 2048, UNIT, bo, 1), i); };
      auto hint = [&](int v) { asm volatile("{.reg .pred p; setp.eq.u32 p, %1, 0; @p red.relaxed.gpu.global.add.u32 [%0], 1;}" ::"l"(&G->hhf[id * 8 + v]), "r"(lane) : "memory"); };
      auto put = [&](int v, int k) {
        uint32_t* x = fr[v] + 2 * k;
        const uint32_t t0 = (x[k / 2] & keep) | bit, t1 = (x[5 + k / 2] & keep) | bit;
        x[k / 2] = t0; x[5 + k / 2] = t1;
        st_relaxed128(hdst + 512 * v + 8 * k, x[0], x[2], x[4], x[6]);
        st_relaxed128(hdst + 512 * v + 8 * k + 64, x[1], x[3], x[5], x[7]);
      };
      auto move = [&](uint32_t* x, int n) {
#pragma unroll
        for (int k = 0; k < n; k++) asm volatile("mul.rn.f32 %0, %0, %1;" : "+r"(x[k]) : "f"(P.one));
      };
      auto act = [&](int i) {
        const int v = i >> 3, k = 7 - (i & 7);
        const float *g = v < 2 ? acc + 32 * v + 4 * k : acb + 4 * k, *up = g + (v < 2 ? 64 : 32);
        fr[v][2 * k] = pack_bf16(silu2(g[0], r0, s0) * up[0], silu2(g[1], r0, s0) * up[1]);
        fr[v][2 * k + 1] = pack_bf16(silu2(g[2], r1, s1) * up[2], silu2(g[3], r1, s1) * up[3]);
        if (!(k & 3)) { put(v, k); if (!k && !(HL >> v & 1)) hint(v); if (i == 15) { move(fr[0], 16); } }
        else pin(P.ulo, fr[v][2 * k] ^ fr[v][2 * k + 1]);
      };
#pragma unroll
      for (int v = 0; v < 10; v++) {
        mbar_wait(BAR(B_FULL + 20 + v));
        if (v == XP) {
          mbar_wait(BAR(B_EXT));
          wg_fence();
          wg_ss192_01(acc, mkdesc(DB + OFF_AX + 1024 * opaque(wg), 0, 128, 0), mkdesc(DB + OFF_BX, 2048, 1024, 1), 1);
          wg_ss64_01(acc + 96, mkdesc(DB + OFF_AX + 1024 * opaque(wg), 0, 128, 0), mkdesc(DB + OFF_BX + 6144, 2048, 1024, 1), 1);
          wg_commit();
          r0 = 0.5f * __uint_as_float(lds32(base + OFF_RT + 256 * wg + 64 * w + (lane & 28)));
          r1 = 0.5f * __uint_as_float(lds32(base + OFF_RT + 256 * wg + 64 * w + 32 + (lane & 28)));
          s0 = 2.f * r0 * r0;
          s1 = 2.f * r1 * r1;
        }
        wg_fence();
#pragma unroll
        for (int k = 0; k < 4; k++) {
          wg_ss128_11(acb, mkdesc(opaque(abd) + a_at(second(v)) + k * 2048, 16, 1024, 1), mkdesc(DB + OFF_R + WSLOT * ((v + 2) % 6) + k * 2048, UNIT, 1024, 1), v + k);
          if (k == GB - 1) { wg_commit(); wg_wait<1>(); if (v == XP) fence_regs(acc); if (elect()) mbar_arrive(BAR(B_EMPTY + 19 + v)); }
        }
        if (v == 9) wg_ss128_01(acb, mkdesc(DB + OFF_AX + 1024 * opaque(wg), 0, 128, 0), mkdesc(DB + OFF_BX + UNIT, 2048, 1024, 1), 1);
        wg_commit();
        split(P.ulo, v);
        if (v == XP + NP / 2 && (HL & 1)) hint(0);
        if (v == XP + NP && (HL & 2)) hint(1);
#pragma unroll
        for (int i = 0; i < 16; i++) if (v >= XP && i * NP / 16 == v - XP) act(i);
      }
#pragma unroll
      for (int v = 0; v < 3; v++) {
        mbar_wait(BAR(B_FULL + 30 + v));
        wg_fence();
#pragma unroll
        for (int i = 0; i < 4; i++) {
          own(4 * v + i);
          if (i == GB - 1) { wg_commit(); wg_wait<1>(); if (v == 0) fence_regs(acb); if (elect()) mbar_arrive(BAR(B_EMPTY + 29 + v)); }
        }
        wg_commit();
        split(P.ulo, 10 + v);
        if (v == 0 && XP + NP == 10 && (HL & 2)) hint(1);
        if (v == 2 && (HL & 4)) hint(2);
#pragma unroll
        for (int i = 0; i < 4; i++) if (v < 2) act(16 + 4 * v + i);
      }
      ck = base + 2048 * w + 516 * (lane >> 3) + 144 * (lane >> 2 & 1) + 32 * (lane & 3);
    }
    uint32_t x1[40], gb[20];
    if (!wg) {
      REGION_IDS;
      mbar_wait(BAR(B_GB));
#pragma unroll
      for (int k = 0; k < 5; k++) {
        const uint4 g = lds128(base + OFF_GB + 80 * (lane & 3) + 16 * k);
        gb[4 * k] = g.x; gb[4 * k + 1] = g.y; gb[4 * k + 2] = g.z; gb[4 * k + 3] = g.w;
      }
    }
#pragma unroll 1
    for (int u = 33; u < 42; u++) {
      const int x = P.hid[wg][u - 33], as = x & ~15;
      const uint64_t wd = mkdesc(0, 0, bo, 1) | P.w2t[u - 30].x;
      mbar_wait(BAR(B_FULL + u));
      a_tile(as, x & 15, false);
      if (wg || u < LAG2) {
        wg_fence();
#pragma unroll
        for (int kk = 0; kk < 4; kk++) {
          wg_ss160_01(o, mkdesc(DB + as + kk / 2 * 512 + (kk & 1) * 32, 16, 1024, 2), wd + kk * 128, 1);
          if (kk == GB - 1) { wg_commit(); wg_wait<1>(); if (elect()) mbar_arrive(BAR(B_EMPTY + u - 1)); }
        }
        wg_commit();
        if (u == 41 && elect()) mbar_arrive(BAR(B_LAG));
      }
      if (u == LAG2 - 1 && !wg) {
        REGION_IDS;
        const uint32_t xa = base + (lane >> 4) * 1024 + (lane & 7) * 128 + (((2 * w + ((lane >> 3) & 1)) ^ (lane & 7)) << 4);
        mbar_wait(BAR(B_FULL + 42));
        wg_wait<0>();
        if (elect()) mbar_arrive(BAR(B_EMPTY + LAG2 - 1));
#pragma unroll
        for (int k = 0; k < 10; k++) ldmatrix_x4_t(x1 + 4 * k, xa + x1_at(k / 2) + (k & 1) * 2048);
      }
    }
    REGION_IDS;
    const int h = role >> 2 & 1, j = role & 3;
    const uint32_t xb = base + OFF_XCH + 5120 * w;
    if (wg) {
      const uint32_t rdst = mapa(xb + 16 * lane, h ^ 1), rbar = mapa(BAR(B_FULL + 1), h ^ 1);
      mbar_wait(BAR(B_XFREE));
      wg_wait<0>();
      fence_regs(o);
#pragma unroll
      for (int k = 0; k < 10; k++)
        asm volatile("st.async.shared::cluster.mbarrier::complete_tx::bytes.v4.b32 [%0], {%1,%2,%3,%4}, [%5];" ::"r"(rdst + 512 * k), "r"(pack_bf16(o[8 * k], o[8 * k + 1])),
                     "r"(pack_bf16(o[8 * k + 2], o[8 * k + 3])), "r"(pack_bf16(o[8 * k + 4], o[8 * k + 5])), "r"(pack_bf16(o[8 * k + 6], o[8 * k + 7])), "r"(rbar + 16 * (k / 4)) : "memory");
    } else {
      mbar_wait(BAR(B_LAG));
      wg_fence();
#pragma unroll
      for (int i = 4 * LAG2; i < 168; i++) wg_ss160_01(o, mkdesc(DB + hid_at(i / 4 - 33, 0) + (i & 2) * 256 + (i & 1) * 32, 16, 1024, 2), mkdesc(DB + w2_at(i / 4 - 30) + (i & 3) * 2048, UNIT, bo, 1), 1);
      wg_commit();
      const int row = (8 * role & ~63) + 16 * w;
      auto merge = [&](int e0, int e1) {
#pragma unroll
        for (int e = e0; e < e1; e++) {
          if (e % 4 == 0) mbar_wait_cluster(BAR(B_FULL + 1 + e / 2));
          const uint4 p = lds128(xb + 16 * lane + 512 * e);
          x1[4 * e] = bfma2(gb[2 * e], p.x, x1[4 * e]); x1[4 * e + 1] = bfma2(gb[2 * e], p.y, x1[4 * e + 1]);
          x1[4 * e + 2] = bfma2(gb[2 * e + 1], p.z, x1[4 * e + 2]); x1[4 * e + 3] = bfma2(gb[2 * e + 1], p.w, x1[4 * e + 3]);
        }
        __syncwarp();
      };
      merge(0, MG);
      wg_wait<0>();
      fence_regs(o);
#pragma unroll
      for (int k = 0; k < 10; k++) {
        if (k >= MG && k % 4 == 0) merge(k, k < 8 ? k + 4 : 10);
        uint32_t y[4];
#pragma unroll
        for (int e = 0; e < 4; e++) y[e] = bfma2(gb[2 * k + e / 2], pack_bf16(o[8 * k + 2 * e], o[8 * k + 2 * e + 1]), x1[4 * k + e]);
        stmatrix_x4(k < 8 ? xb + 2048 * (k >> 2) + (lane & 15) * 128 + (((2 * (k & 3) + (lane >> 4)) ^ (lane & 7) ^ 4 * (j & 1)) << 4)
                          : xb + 4096 + (lane & 15) * 64 + (((2 * (k & 1) + (lane >> 4)) ^ (lane >> 1 & 3)) << 4), y[0], y[1], y[2], y[3]);
        if ((SG >> k & 1) || k == 9) {
          fence_async_smem();
          __syncwarp();
#pragma unroll
          for (int b = 0; b < 3; b++) {
            const int e = b < 2 ? 4 * b + 3 : 9;
            if (e <= k && !(SG & ((1 << k) - 1) & ~((1 << e) - 1)) && lane == 0) tma2d_store(b < 2 ? &maps.outa : &maps.outb, b < 2 ? 128 * j + 64 * b : 512 + 32 * j, row, xb + 2048 * b);
          }
        }
      }
      if (lane == 0) { bulk_commit(); bulk_wait_read(); }
    }
  } else if (wg == 2) {
    asm volatile("setmaxnreg.dec.sync.aligned.u32 40;");
    mbar_init<15>(BAR(B_FULL + 15 * w), 1);
    mbar_init<11>(BAR(B_EMPTY - 1 + 11 * w), 8);
    asm volatile("fence.mbarrier_init.release.cluster;" ::: "memory");
    LAUNCHES;
    silu_vector(P.c + 80 * (blockIdx.x & 7) - 512, 296, base - 1024);
    const uint32_t epoch = EPOCH;
    if (w == 2) rank_pair(G, base, epoch, true);
    cluster_wait();
    {
      REGION_IDS;
      const uint32_t tag = opaque(~lane & 1);
      auto q_t = [&]() {
        const int tr = 4 * (lane & 1) + (lane >> 1 & 3);
        uint32_t a = base + OFF_Q + 128 * ((lane & 24) + tr) + ((w ^ tr) << 4);
        uint4* dst = G->qt + (64 * (bid & 1) + 8 * w + (lane >> 2)) * 256 + 4 * (bid >> 1) + (lane & 3);
#pragma unroll 1
        for (int c = 0; c < 5; c++) {
          mbar_wait(BAR(B_Q + c));
#pragma unroll
          for (int k = 0; k < 2; k++) {
            uint32_t x[4];
            ldmatrix_x4_t(x, a ^ (64 * k));
            st_relaxed128(dst + 8192 * k, set_tag(x[0], tag, epoch), x[1], x[2], x[3]);
          }
          a += 4096;
          dst += 32768;
        }
        arrive1(BAR(B_QTD));
      };
      q_t();
      if (w == 3) {
        mbar_wait_cluster(BAR(B_ST1));
        if (lane < 8) red_hint(G->hint[5][lane]);
        const uint2 x = lds64(base + OFF_ST + 8 * (lane & 15)), y = lds64(base + OFF_ST + 128 + 8 * (lane & 15));
        float m, sd;
        ln_final(__uint_as_float(x.x) + __uint_as_float(y.x), __uint_as_float(x.y) + __uint_as_float(y.y), m, sd);
        sd = rbf(rcpf(sd));
        const uint32_t mr = pack_bf16(sd, -rbf(m) * sd), tg = lane & 7 ? 0 : lane & 8 ? 1 : 0x8000;
        const uint32_t o = __byte_perm(__shfl_sync(~0u, mr, 2 * lane & 14), __shfl_sync(~0u, mr, (2 * lane & 14) + 1), (lane & 8) ? 0x7632 : 0x5410);
        if (lane < 16) st_relaxed32(&G->st1[lane >> 3][8 * bid + (lane & 7)], (o & ~tg) | ((epoch & 1) * tg));
      }
      if (w == 2) rank_pair(G, base, epoch, false);
      if (w == 1) mod_fetch(G, base, epoch, M8, 0, 1);
    }
    {
      REGION_IDS;
      const uint32_t tag = opaque(~lane & 1), sa = opaque(base + 16 * i0);
      uint4 q[2];
      mbar_wait(BAR(B_PFULL));
#pragma unroll 1
      for (uint32_t a = sa + tab(T_P, 0); a < sa + tab(T_P, 0) + 4096; a += 2048) {
        uint4 y = lds128(a), z = lds128(a + 4096), u = lds128(a + 8192);
        const uint4 v = lds128(a + 12288);
        add4(y, z); add4(u, v); add4(y, u);
        sts128(a, y.x, y.y, y.z, y.w);
      }
      uint4* gp = G->xs + 256 * bid + (sa - base >> 4);
      q[0] = ld_relaxed128(gp - D_ * 256);
      q[1] = ld_relaxed128(gp - D_ * 256 + 128);
      mbar_wait(BAR(B_MR));
      e_round<true>(G, base, sa, gp, q, 0, w, tag, epoch);
#pragma unroll 1
      for (int c = 1; c < 5; c++) e_round<false>(G, base, sa, gp, q, c, w, tag, epoch);
    }
    int h, j, r;
    ffn_role(h, j, r);
    arrive1(BAR(B_ED));
    {
      REGION_IDS;
      float s0 = 0.f, q0 = 0.f, s1 = 0.f, q1 = 0.f;
#pragma unroll 1
      for (int c = 2; c < 5; c++) {
        const uint32_t buf = base + OFF_SX + 4096 * (c - 2), b = BAR(B_SX + c);
        uint32_t x[8];
#pragma unroll 1
        for (int it = 0; it < SPIN_LIMIT; it++) {
          mbar_wait(b, it & 1);
#pragma unroll
          for (int i = 0; i < 8; i++) x[i] = lds32(buf + 1024 * w + 4 * lane + 128 * i);
          if (bar_all(3, (lane & 7) || min(min(min(x[0], x[1]), min(x[2], x[3])), min(min(x[4], x[5]), min(x[6], x[7]))))) break;
          if (w == 0 && elect()) { mbar_expect_tx(b, 4096); tma2d(buf, &maps.x1s, 128 * r + 64 * h, D_ * (epoch & 1) + 128 * c + 32 * j, b); }
        }
#pragma unroll
        for (int i = 0; i < 8; i++) { const float lo = bf_lo(x[i]), hi = bf_hi(x[i]); s0 += lo; q0 = fmaf(lo, lo, q0); s1 += hi; q1 = fmaf(hi, hi, q1); }
      }
      sts128(base + OFF_MR + 1024 * w + 16 * lane, __float_as_uint(s0), __float_as_uint(q0), __float_as_uint(s1), __float_as_uint(q1));
      arrive1(BAR(B_S2));
    }
    {
      REGION_IDS;
      const uint32_t* sp = &G->st2[2 * r + (h ^ (w >> 1))][0][2 * (i0 & 63)];
      uint2 x[4];
      int it;
#pragma unroll 1
      for (it = 0; it < SPIN_LIMIT; it++) {
        mbar_wait(BAR(B_BX), it & 1);
        uint32_t y = 0;
#pragma unroll
        for (int k = 0; k < 3; k++) y |= lds32(base + OFF_BX + 32 * i0 + 4096 * k) ^ epoch;
        if (bar_all(3, !(y & 1))) break;
        if (w == 0 && elect()) { mbar_expect_tx(BAR(B_BX), 12288); bulk_load(base + OFF_BX, G->uv[4 * h + j], 12288, BAR(B_BX)); }
      }
      it = 0;
#pragma unroll 1
      do {
#pragma unroll
        for (int k = 0; k < 4; k++) x[k] = ld_relaxed64(sp + 128 * k);
      } while (__any_sync(~0u, ((x[0].x ^ epoch) | (x[1].x ^ epoch) | (x[2].x ^ epoch) | (x[3].x ^ epoch)) & 1) && ++it < SPIN_LIMIT);
      float m, sd;
      ln_final((__uint_as_float(x[0].x) + __uint_as_float(x[1].x)) + (__uint_as_float(x[2].x) + __uint_as_float(x[3].x)),
               (__uint_as_float(x[0].y) + __uint_as_float(x[1].y)) + (__uint_as_float(x[2].y) + __uint_as_float(x[3].y)), m, sd);
      const uint32_t e = pack_bf16(-m, sd);
      sts128(base + OFF_AX + 16 * i0, e, e, e, e);
      sts32(base + OFF_RT + 4 * i0, __float_as_uint(rcpf(sd)));
      fence_async_smem();
      arrive1(BAR(B_EXT));
      {
        uint2 g0, g1;
        int it = 0;
#pragma unroll 1
        do {
          g0 = ld_relaxed64(&G->modv[1][128 * j + i0]);
          g1 = ld_relaxed64(&G->modv[1][512 + 32 * j + lane]);
        } while (__any_sync(~0u, ((g0.x ^ epoch) | (g0.y ^ epoch) | (g1.x ^ epoch) | (g1.y ^ epoch)) & 1) && ++it < SPIN_LIMIT);
        const uint32_t a = base + OFF_GB + 40 * (lane & 6) + 2 * (lane & 1) + (lane >> 3) * 4;
        asm volatile("st.shared.u16 [%0], %1; st.shared.u16 [%2], %3;" ::"r"(a + 16 * (w ^ (j & 1))), "h"((uint16_t)(mod_sum(g0) >> 16)), "r"(a + 64), "h"((uint16_t)(mod_sum(g1) >> 16)) : "memory");
        arrive1(BAR(B_GB));
      }
      const int id = 16 * r + 4 * h + ((j + 1 + w) & 3);
#pragma unroll 1
      for (int q = w == 3 ? 3 : 0; q < 3; q++) {
        const int m = 3 * q + w;
        const uint4* src = G->hh + id * 1536 + 512 * q;
        it = 0;
#pragma unroll 1
        while (__any_sync(~0u, ld_relaxed32(&G->hhf[8 * id + 64 * (lane & 1) + q]) != 4 * epoch) && ++it < SPIN_LIMIT);
        mbar_wait(BAR(P.hid[2][m]));
        if (elect()) {
          bulk_load(base + (P.hid[h][m] & ~15), src, UNIT, BAR(B_FULL + 33 + m));
          bulk_load(base + (P.hid[h ^ 1][m] & ~15), src + 8 * 1536, UNIT, BAR(B_FULL + 33 + m));
        }
      }
    }
  } else {
    asm volatile("setmaxnreg.dec.sync.aligned.u32 24;");
    if (w >= 2) {
      LAUNCHES;
      uint32_t epoch;
      {
        REGION_IDS;
        uint32_t dv;
        asm volatile("ld.global.nc.u16 %0, [%1];" : "=r"(dv) : "l"(P.ssmd + 128 * (lane & 7) % D_ + bid));
        if (lane < 5) sts128(base + tab(T_F, lane) + (w & 1) * (F_O - F_E) + F_E - 16, 0, 0, 0, 0);
        epoch = EPOCH;
        __syncwarp();
#pragma unroll 1
        for (int c = 0; c < 5; c++) {
          const float d = i0 == 64 ? bf_lo(dv) : 0.f;
          dv = __shfl_down_sync(~0u, dv, 1);
          const uint32_t a = base + tab(T_F, c) + 16 * (i0 - 64);
          mbar_wait(BAR(B_FRAW + c));
#pragma unroll
          for (int k = 0; k < 4; k++) {
            uint4 x = lds128(a + F_E + 1024 * k);
            const uint32_t pv = lds32(a + F_E - 4 + 1024 * k);
            if (k == 0) { x.x = pack_bf16(bf_lo(x.x) + d, bf_hi(x.x)); sts32(a + F_E, x.x); }
            sts128(a + F_O + 1024 * k, __byte_perm(pv, x.x, 0x5432), __byte_perm(x.x, x.y, 0x5432), __byte_perm(x.y, x.z, 0x5432), __byte_perm(x.z, x.w, 0x5432));
          }
          __syncwarp();
          if (elect()) mbar_arrive2(BAR(B_FRDY + c));
          if (c == 0 && w == 3) {
#pragma unroll 1
            for (int k = 0; k < 13; k++) prefetch_map(&maps.w1a + k);
          }
        }
      }
      REGION_IDS;
      int h, j, r;
      ffn_role(h, j, r);
      cluster_wait();
      if (w == 2) {
        const unsigned* fp = G->xsh[lane < 10 ? lane >> 1 : 0][(r & 6) + (lane & 1)];
        uint32_t rdy = 0;
        mbar_wait(BAR(B_SC + 4));
#pragma unroll 1
        for (int e = 0; e < 14; e++) {
          const uint32_t x = P.adep[e], n = x >> 21 & 15, s = base + (x >> 25 << 13), b = BAR(B_FULL + (x >> 16 & 31));
          mbar_wait(BAR(opaque(x & 255)));
          mbar_wait(BAR(opaque(x >> 8 & 255)));
#pragma unroll 1
          for (int it = 0; !(rdy >> n & 1) && it < SPIN_LIMIT; it++) rdy = __ballot_sync(~0u, ld_relaxed32(fp) == 64 * epoch);
          if (elect()) {
            tma2d(s, &maps.xs, 128 * r + 64 * h, 64 * n, b);
            tma2d(s + UNIT, &maps.xs, 128 * r + 64 - 64 * h, 64 * n, b);
          }
        }
#pragma unroll 1
        for (int v = 0; v < 12; v++) {
          const int q = v * 11 >> 5, e = v - 3 * q, k32 = 24 * h + (q ? 6 * ((j + 1 + e) & 3) + 2 * q - 2 : 6 * j + 2 * e);
          const uint2 x = P.w2t[v];
          mbar_wait(BAR(x.y));
          if (elect()) {
            mbar_expect_tx(BAR(B_FULL + 30 + v), q ? W2TILE + 2 * UNIT : W2TILE);
#pragma unroll
            for (int k = 0; k < 3; k++) tma5d(base - DB + 16 * (x.x & 0xFFFF) + UNIT * k, &maps.w2a + (q > 0), k < 2 ? 128 * j + 64 * k : 512 + 32 * (j & 2), k32, BAR(B_FULL + 30 + v));
          }
        }
      } else {
        float s0 = 0.f, q0 = 0.f, s1 = 0.f, q1 = 0.f;
        uint32_t nl = 0, np = 0, ph = 0;
#pragma unroll 1
        for (uint32_t seq = 0x94; seq > 1; seq >>= 1) {
          const uint32_t c = seq & 1 ? np : nl, buf = base + OFF_SX + 4096 * (c < 4 ? c & 1 : 2), b = BAR(opaque(B_SX + c));
          int it = 0;
          if (seq & 1) {
            mbar_wait(b, ph >> c & 1);
            ph ^= 1 << c;
            const uint32_t a = buf + 32 * lane;
            if (__all_sync(~0u, min(min(lds32(a), lds32(a + 1024)), min(lds32(a + 2048), lds32(a + 3072)))) || ph > SPIN_LIMIT) {
#pragma unroll 1
              for (uint32_t o = buf + 4 * lane; o < buf + 4096; o += 1024) {
                uint32_t x[8];
#pragma unroll
                for (int i = 0; i < 8; i++) x[i] = lds32(o + 128 * i);
#pragma unroll
                for (int i = 0; i < 8; i++) { const float lo = bf_lo(x[i]), hi = bf_hi(x[i]); s0 += lo; q0 = fmaf(lo, lo, q0); s1 += hi; q1 = fmaf(hi, hi, q1); }
              }
              np++;
              continue;
            }
            ph += 4;
            seq = 2 * seq + 1;
          } else {
#pragma unroll 1
            while (__any_sync(~0u, ld_relaxed32(G->xsh[c][(r & 6) + (j >> 1)]) != 64 * epoch) && ++it < SPIN_LIMIT);
            if (++nl == 5) mbar_wait(BAR(B_PEMPTY + 4));
          }
          if (elect()) { mbar_expect_tx(b, 4096); tma2d(buf, &maps.x1s, 128 * r + 64 * h, D_ * (epoch & 1) + 128 * c + 32 * j, b); }
        }
        mbar_wait(BAR(B_S2));
#pragma unroll
        for (int k = 0; k < 4; k++) {
          const uint4 x = lds128(base + OFF_MR + 1024 * k + 16 * lane);
          s0 += __uint_as_float(x.x); q0 += __uint_as_float(x.y); s1 += __uint_as_float(x.z); q1 += __uint_as_float(x.w);
        }
        asm volatile("{.reg .b128 t, x; .reg .b64 a, b; mov.b64 a, {%1,%2}; mov.b64 b, {%3,%4}; mov.b128 x, {a,b}; atom.relaxed.gpu.global.exch.b128 t, [%0], x;}"
                     ::"l"(&G->st2[2 * r + h][j][4 * lane]), "r"((__float_as_uint(s0) & ~1u) | (epoch & 1)), "f"(q0), "r"((__float_as_uint(s1) & ~1u) | (epoch & 1)), "f"(q1) : "memory");
        mbar_wait(BAR(B_EMPTY + 2 * UVS + 1));
        sts128(base + OFF_CO + 16 * lane, 0, 0, 0, 0);
        fence_async_smem();
        __syncwarp();
        if (elect()) {
#pragma unroll 1
          for (int k = 0; k < 40; k++) asm volatile("cp.async.bulk.global.shared::cta.bulk_group [%0], [%1], 512;" ::"l"(G->x1[~epoch & 1] + 1280 * blockIdx.x + 32 * k), "r"(base + OFF_CO) : "memory");
          bulk_commit();
          bulk_wait_read();
        }
      }
    } else if (w == 0) {
      LAUNCHES;
      uint32_t epoch;
      {
        REGION_IDS;
        const unsigned* hp = G->hint[0][4 * (bid >> 6) + (bid >> 3 & 3)];
        uint32_t v = ld_relaxed32(hp + 256 * min(lane, 5));
        if (lane < 3) sts128(base + tab(T_X, lane) + 4096, 0, 0, 0, 0);
        if (lane && lane <= B_WM) mbar_expect_tx(BAR(lane), lane < B_FRAW ? 9728 : lane == B_WM ? 10240 : 4096);
        epoch = EPOCH;
        fence_async_smem();
        const uint32_t rdy = __ballot_sync(~0u, v == epoch << 6) & 31;
        uint32_t nx = 0, mr = 1;
#pragma unroll 1
        for (int it = 0; (nx < 5 || mr) && it < SPIN_LIMIT; it++) {
          const bool second = nx == 5 || (lane && mr && nx >= P.mq);
          if (!(rdy >> nx & 1)) v = ld_relaxed32(hp + 256 * (second ? 5 : nx));
          const uint32_t ok = __ballot_sync(~0u, v == epoch << (second ? 7 : 6)) | (rdy >> nx & 1);
          if (nx < 5 && (ok & 1)) {
            if (nx >= 3) mbar_wait(BAR(B_PFULL - 3 + nx));
            if (elect()) { mbar_expect_tx(BAR(B_XR + nx), 4096); bulk_load(base + tab(T_X, nx), G->xr + (128 * nx + bid) * 256, 4096, BAR(B_XR + nx)); }
          }
          if (mr && (nx == 5 || nx >= P.mq) && (ok & 2) && !(rdy >> nx & 1)) {
            if (elect()) { mbar_expect_tx(BAR(B_MR), 8192); bulk_load(base + OFF_MR, G->st1, 8192, BAR(B_MR)); mbar_arrive(BAR(B_QTOK)); }
            mr = 0;
          }
          if (nx < 5) nx += ok & 1;
        }
        mod_fetch(G, base, epoch, M8, 2, 5);
      }
      REGION_IDS;
      int h, j, r;
      ffn_role(h, j, r);
      cluster_wait();
      if (elect()) mbar_expect_tx(BAR(B_UVB), 30720);
#pragma unroll 1
      for (int k = 0; k < 5; k++) {
        mbar_wait(BAR(opaque(B_EMPTY + nib(P.uvd, k))));
        if (elect()) tma3d(base + OFF_UV + 6144 * k, &maps.w1u + (r & 1), 0, 40 * (r & 14) + 16 * k, 3 * (4 * h + j), BAR(B_UVB));
      }
      mbar_wait(BAR(B_G));
      {
        const uint2* mp = &G->modv[lane & 4 ? 0 : 2][40 * (r & 14) + (lane & 24) + 2 * (lane & 3)];
        uint4 v[3];
        int it = 0;
#pragma unroll 1
        do {
          v[0] = ld_relaxed128(mp); v[1] = ld_relaxed128(mp + 32); v[2] = ld_relaxed128(mp + 64 - (lane & 16));
        } while (__any_sync(~0u, ((v[0].x ^ epoch) | (v[0].y ^ epoch) | (v[0].z ^ epoch) | (v[0].w ^ epoch) | (v[1].x ^ epoch) | (v[1].y ^ epoch) | (v[1].z ^ epoch) | (v[1].w ^ epoch) |
                                  (v[2].x ^ epoch) | (v[2].y ^ epoch) | (v[2].z ^ epoch) | (v[2].w ^ epoch)) & 1) && ++it < SPIN_LIMIT);
#pragma unroll
        for (int i = 0; i < 3; i++)
          sts32(base + OFF_CO + 128 * i + 4 * lane, badd2(pack_bf16(__uint_as_float(v[i].x) + __uint_as_float(v[i].y), __uint_as_float(v[i].z) + __uint_as_float(v[i].w)), lane & 4 ? 0 : 0x3F803F80u));
      }
      fence_async_smem();
      arrive1(BAR(B_CO));
      ffn_role(h, j, r);
      mbar_wait(BAR(B_ED));
      int it = 0;
#pragma unroll 1
      while (__any_sync(~0u, ld_relaxed32(G->hint[8][4 * h + j]) != 128 * epoch) && ++it < SPIN_LIMIT);
      if (elect()) { mbar_expect_tx(BAR(B_BX), 12288); bulk_load(base + OFF_BX, G->uv[4 * h + j], 12288, BAR(B_BX)); }
      asm volatile("fence.acq_rel.gpu;" ::: "memory");
      if (lane < 8) red_hint(G->hint[7][lane]);
      unsigned x;
      it = 0;
#pragma unroll 1
      do { asm volatile("ld.acquire.gpu.global.u32 %0, [%1];" : "=r"(x) : "l"(G->hint[7][bid >> 4]) : "memory"); } while (__any_sync(~0u, x != 128 * epoch) && ++it < SPIN_LIMIT);
      fence_async_all();
      const int ch = D_ * (epoch & 1);
      mbar_wait(BAR(P.xdep));
      if (elect()) {
        mbar_expect_tx(BAR(B_FULL + 42), 20480);
#pragma unroll
        for (int k = 0; k < 4; k++) tma2d(base + x1_at(k), &maps.x1b, 128 * r + 64 * h, ch + 128 * j + 32 * (k ^ (j & 1)), BAR(B_FULL + 42));
        tma2d(base + x1_at(4), &maps.x1b, 128 * r + 64 * h, ch + 512 + 32 * j, BAR(B_FULL + 42));
        mbar_expect_tx(BAR(B_FULL + 1), 8192); mbar_expect_tx(BAR(B_FULL + 3), 8192); mbar_expect_tx(BAR(B_FULL + 5), 4096);
      }
      mbar_wait(BAR(B_EMPTY + 37));
      if (elect()) mbar_arrive_remote(mapa(BAR(B_XFREE), h ^ 1));
    } else {
      LAUNCHES;
      {
        REGION_IDS;
        loads<0>(P, maps, base);
      }
      cluster_wait();
      int h, j, r;
      ffn_role(h, j, r);
      mbar_wait(BAR(B_QTD));
      mbar_wait(BAR(B_STD));
      mbar_wait(BAR(B_SC));
      mbar_wait(BAR(B_SC + 2));
      mbar_wait(BAR(B_FL));
#pragma unroll 1
      for (int u = 0; u < 30; u++) {
        if (u == P.mpos) mod_fetch(G, base, EPOCH, M8, 1, 2);
        if (u < 6) wait_clock(t_start + P.wt0 + u * P.wpace);
        const uint32_t x = P.wdep[u], b = x >> 8 & 1;
        uint32_t s = base + OFF_R + WSLOT * (x >> 9 & 7), f = BAR(B_FULL + (b ? u : u & ~1)), n = x & 0xC000, y = x >> 16, z = 3 * (4 * h + j) + 2 * b;
        const CUtensorMap* m = &maps.w1a + 5 * b;
        asm volatile("{.reg .pred p, q; .reg .b32 i, t; .reg .b64 m; mov.u32 i, 0; add.u32 t, %0, 8192; add.u64 m, %1, 128; elect.sync _|q, 0xffffffff;"
                     "W: mbarrier.try_wait.parity.shared::cta.b64 p, [%6], 0; @p bra.uni D; add.u32 i, i, 1; setp.lt.u32 p, i, %7; @p bra.uni W; D:"
                     "setp.ne.and.u32 p, %3, 0, q; @p mbarrier.arrive.expect_tx.shared::cta.b64 _, [%2], %3;"
                     "@q cp.async.bulk.tensor.3d.shared::cluster.global.mbarrier::complete_tx::bytes [%0], [%1, {0,%4,%5}], [%2];"
                     "@q cp.async.bulk.tensor.3d.shared::cluster.global.mbarrier::complete_tx::bytes [t], [m, {0,%4,%5}], [%2];}"
                     ::"r"(s), "l"(m), "r"(f), "r"(n), "r"(y), "r"(z), "r"(BAR(opaque(x & 255))), "n"(SPIN_LIMIT) : "memory");
      }
    }
  }
}

typedef CUresult (*EncFn)(CUtensorMap*, CUtensorMapDataType, cuuint32_t, void*, const cuuint64_t*, const cuuint64_t*, const cuuint32_t*,
                          const cuuint32_t*, CUtensorMapInterleave, CUtensorMapSwizzle, CUtensorMapL2promotion, CUtensorMapFloatOOBfill);
static int enc_err = 0;
static void enc(EncFn fn, CUtensorMap* m, const void* p, int rank, const cuuint64_t* gd, const cuuint64_t* gs, const cuuint32_t* bd, CUtensorMapSwizzle sw) {
  cuuint32_t es[5] = {1, 1, 1, 1, 1};
  enc_err = 2 * enc_err + (fn(m, CU_TENSOR_MAP_DATA_TYPE_BFLOAT16, rank, (void*)p, gd, gs, bd, es, CU_TENSOR_MAP_INTERLEAVE_NONE, sw,
                              CU_TENSOR_MAP_L2_PROMOTION_L2_128B, CU_TENSOR_MAP_FLOAT_OOB_FILL_NONE) != CUDA_SUCCESS);
}

extern "C" void kernel_launch(void* const* d_in, const int* in_sizes, int n_in, void* d_out, int out_size) {
  const bf16 *q = (const bf16*)d_in[0], *k = (const bf16*)d_in[1], *v = (const bf16*)d_in[2], *shift = (const bf16*)d_in[3],
             *ssmk = (const bf16*)d_in[4], *ssmd = (const bf16*)d_in[5], *w1 = (const bf16*)d_in[7], *w3 = (const bf16*)d_in[8],
             *w2 = (const bf16*)d_in[9], *c = (const bf16*)d_in[10], *wmod = (const bf16*)d_in[11];
  EncFn fn = nullptr;
  cudaDriverEntryPointQueryResult qr;
  cudaGetDriverEntryPoint("cuTensorMapEncodeTiled", (void**)&fn, cudaEnableDefault, &qr);
  Scratch* pg;
  cudaGetSymbolAddress((void**)&pg, g_s);
  Maps maps;
  enc_err = 0;
  const CUtensorMapSwizzle S128 = CU_TENSOR_MAP_SWIZZLE_128B;
  { cuuint64_t gd[3] = {D_, S_ / 8, 8}, gs[2] = {D_ * 16, D_ * 2}; cuuint32_t b[3] = {64, 4, 8};
    enc(fn, &maps.km, k, 3, gd, gs, b, S128);
    enc(fn, &maps.v, v, 3, gd, gs, b, S128);
    enc(fn, &maps.q, q, 3, gd, gs, b, S128);
    b[2] = 3;
    enc(fn, &maps.kh, k, 3, gd, gs, b, S128); }
  { cuuint64_t gd[3] = {256, 8, D_}, gs[2] = {512, 4096}; cuuint32_t b[3] = {256, 8, 1};
    enc(fn, &maps.fm, ssmk, 3, gd, gs, b, CU_TENSOR_MAP_SWIZZLE_NONE); }
  { cuuint64_t gd[3] = {256, 2, 5}, gs[2] = {512, 1024}; cuuint32_t b[3] = {256, 1, 5};
    enc(fn, &maps.tap, shift, 3, gd, gs, b, CU_TENSOR_MAP_SWIZZLE_NONE); }
  { cuuint64_t gd[3] = {6 * D_, D_, 1}, gs[2] = {6 * D_ * 2, 6 * D_ * 2 * D_}; cuuint32_t b[3] = {64, 64, 1};
    enc(fn, &maps.wm, wmod, 3, gd, gs, b, S128);
    b[1] = 80;
    enc(fn, &maps.wmp, wmod, 3, gd, gs, b, S128); }
  { cuuint64_t gd[3] = {64, D_, F_ / 64}, gs[2] = {F_ * 2, 128}; cuuint32_t b[3] = {64, 16, 3};
    enc(fn, &maps.w1u, w1, 3, gd, gs, b, S128);
    enc(fn, &maps.w3u, w3, 3, gd, gs, b, S128);
    b[1] = 32; b[2] = 2;
    enc(fn, &maps.w1a, w1, 3, gd, gs, b, S128);
    enc(fn, &maps.w3a, w3, 3, gd, gs, b, S128);
    b[1] = 64; b[2] = 1;
    enc(fn, &maps.w1b, w1, 3, gd, gs, b, S128);
    enc(fn, &maps.w3b, w3, 3, gd, gs, b, S128); }
  { cuuint64_t gd[2] = {S_, D_}, gs[1] = {S_ * 2}; cuuint32_t b1[2] = {64, 64}, b2[2] = {64, 32};
    enc(fn, &maps.xs, pg->xs, 2, gd, gs, b1, S128);
    gd[1] = 2 * D_;
    enc(fn, &maps.x1b, pg->x1, 2, gd, gs, b2, S128);
    enc(fn, &maps.x1s, pg->x1, 2, gd, gs, b2, CU_TENSOR_MAP_SWIZZLE_NONE); }
  { cuuint64_t gd[5] = {D_, 2, 4, 4, 48}, gs[4] = {D_ * 2, D_ * 4, D_ * 16, D_ * 64}; cuuint32_t b[5] = {64, 2, 4, 4, 2};
    enc(fn, &maps.w2a, w2, 5, gd, gs, b, S128);
    gs[1] = D_ * 16; gs[2] = D_ * 4;
    enc(fn, &maps.w2b, w2, 5, gd, gs, b, S128); }
  { cuuint64_t gd[2] = {D_, S_}, gs[1] = {D_ * 2}; cuuint32_t b1[2] = {64, 16}, b2[2] = {32, 16};
    enc(fn, &maps.outa, d_out, 2, gd, gs, b1, S128);
    enc(fn, &maps.outb, d_out, 2, gd, gs, b2, CU_TENSOR_MAP_SWIZZLE_64B); }
  if (enc_err) return;
  cudaFuncSetAttribute(k_fused<0>, cudaFuncAttributeMaxDynamicSharedMemorySize, SMEM_BYTES);
  cudaFuncSetAttribute(k_fused<128>, cudaFuncAttributeMaxDynamicSharedMemorySize, SMEM_BYTES);
  cudaLaunchConfig_t cfg = {132, 512, SMEM_BYTES};
  cudaLaunchAttribute at = {cudaLaunchAttributeClusterDimension};
  at.val.clusterDim.x = 2; at.val.clusterDim.y = at.val.clusterDim.z = 1;
  cfg.attrs = &at; cfg.numAttrs = 1;
  int nc = 0;
  cudaOccupancyMaxActiveClusters(&nc, k_fused<0>, &cfg);
  Ptrs P = {c, ssmd, pg, {0x676360, 0x57246209}, {}, 32, 2, 0, B_EMPTY + 32, 0 | 0 << 16, 0, {}, 0x55311, 1, 11600, 900, 1.f};
  const char *win = "4444444444444444444", *ho = "abcdefghijklmnopqrstuvwxyz{|}~";
  memset(P.hl, 255, sizeof(P.hl));
  for (int k = 0, n = 0; k < 30; k++) {
    const int i = ho[k] - 'a';
    if (i >= 20 || !(M8 >> i / 4 & 1)) ((uint8_t*)P.hl)[n++] = i;
  }
  for (int e = 0; e < NL; e++) {
    auto size = [](int i) { return i < 0 ? 8 : ORDER[2 * i] == 'w' ? 10 : 4; };
    int i = e, sum = 0, g = 2 * load_bar(e) + 1;
    while (i >= -1 && sum + size(i) <= 4 * (win[e] - '0')) sum += size(i--);
    for (; i >= -1; i--) {
      bool ok = i < e;
      for (int k = e; k < NL; k++) ok = ok && load_bar(k) != load_bar(i);
      if (ok) { g = 2 * load_bar(i); break; }
    }
    ((uint8_t*)P.gate)[e] = g;
  }
  for (int u = 0; u < 30; u++) P.wdep[u] = (u < 4 ? B_FL + 1 + u / 3 : u < 6 ? B_G : B_EMPTY + (u < 26 ? (u - 6) | 1 : u - 6)) | (u >= 20) << 8 | u % 6 << 9 | (u < 20 ? 3 * (~u & 1) : 1 + (u >= 26)) << 14 | (u < 20 ? 32 * u : 64 * (second(u - 20) % 10)) << 16;
  const int adep[14] = {B_PEMPTY, B_PEMPTY, B_PFULL + 4, B_PEMPTY + 1, B_PEMPTY + 2, B_EMPTY + 5, B_EMPTY + 7, B_PEMPTY + 3, B_EMPTY + 2 * UVS + 1, B_EMPTY + 2 * UVS + 1, B_EMPTY + 20, B_EMPTY + 21, B_EMPTY + 22, B_EMPTY + 23};
  const char *ad = "--*--df-jhvxwy", *wd = "55677:;<>?\?A", *hd = "679;;>?@A";
  for (int n = 0; n < 14; n++) P.adep[n] = adep[n] | (ad[n] == '-' ? adep[n] : ad[n] == '*' ? B_PFULL + 3 : B_EMPTY + ad[n] - 'a') << 8 | (n < 10 ? 2 * n : n + 16) << 16 | n % 10 << 21 | a_at(n) / UNIT << 25;
  for (int v = 0; v < 12; v++) P.w2t[v] = make_uint2(w2_desc(v), B_EMPTY + 20 + wd[v] - '0');
  for (int m = 0; m < 9; m++) { P.hid[0][m] = hid_at(m, 0) | m / 3 * 4 | (m % 3 + 1); P.hid[1][m] = hid_at(m, 1) | m / 3 * 4 | (m % 3 + 1); P.hid[2][m] = B_EMPTY + 20 + hd[m] - '0'; }
  if (nc < 66) k_fused<128><<<4, 512, SMEM_BYTES, cudaStreamPerThread>>>(P, maps);
  k_fused<0><<<nc < 66 ? 128 : 132, 512, SMEM_BYTES, cudaStreamPerThread>>>(P, maps);
}
```

```cpp
#include <cuda_runtime.h>
#include <cuda.h>
#include <cuda_bf16.h>
#include <stdint.h>
#include <stdlib.h>
#include <string.h>

typedef __nv_bfloat16 bf16;
constexpr int S_ = 2048, D_ = 640, F_ = 1536;

struct Scratch {
  uint32_t st1[2][1024];
  uint32_t st2[32][4][128];
  uint32_t modc[128][5][32];
  uint2 modv[3][D_];
  uint32_t uv[8][3072];
  unsigned hint[9][8][32];
  unsigned xsh[5][8][32], hhf[256 * 8], key[256];
  uint4 xr[D_ * 256];
  uint4 qt[D_ * 256];
  uint4 xs[D_ * 256];
  uint4 x1[2][D_ * 256];
  uint4 hh[32 * 8 * 1536];
};
__device__ __align__(1024) Scratch g_s;

__device__ __forceinline__ uint32_t smem_u32(const void* p) { return (uint32_t)__cvta_generic_to_shared(p); }
__device__ __forceinline__ void mbar_expect_tx(uint32_t b, uint32_t n) { asm volatile("mbarrier.arrive.expect_tx.shared::cta.b64 _, [%0], %1;" ::"r"(b), "r"(n) : "memory"); }
__device__ __forceinline__ void mbar_arrive(uint32_t b) { asm volatile("mbarrier.arrive.shared::cta.b64 _, [%0];" ::"r"(b) : "memory"); }
__device__ __forceinline__ void mbar_arrive2(uint32_t b) { asm volatile("mbarrier.arrive.shared::cta.b64 _, [%0], 2;" ::"r"(b) : "memory"); }
__device__ __forceinline__ uint32_t mapa(uint32_t a, uint32_t cta) { uint32_t r; asm volatile("mapa.shared::cluster.u32 %0, %1, %2;" : "=r"(r) : "r"(a), "r"(cta)); return r; }
__device__ __forceinline__ void mbar_arrive_remote(uint32_t rb) { asm volatile("mbarrier.arrive.shared::cluster.b64 _, [%0];" ::"r"(rb) : "memory"); }
constexpr int SPIN_LIMIT = 1 << 16;
template <int N> __device__ __forceinline__ void mbar_init(uint32_t b, uint32_t count) {
#pragma unroll
  for (int i = 0; i < N; i++) asm volatile("mbarrier.init.shared::cta.b64 [%0], %1;" ::"r"(b + 8 * i), "r"(count) : "memory");
}
__device__ __forceinline__ bool elect() { uint32_t p; asm volatile("{.reg .pred q; elect.sync _|q, 0xffffffff; selp.u32 %0, 1, 0, q;}" : "=r"(p)); return p; }
__device__ __forceinline__ void arrive1(uint32_t b) { __syncwarp(); if (elect()) mbar_arrive(b); }
__device__ __forceinline__ bool mbar_test(uint32_t b) {
  uint32_t ok;
  asm volatile("{.reg .pred p; mbarrier.test_wait.parity.shared::cta.b64 p, [%1], 0; selp.u32 %0,1,0,p;}" : "=r"(ok) : "r"(b) : "memory");
  return ok;
}
#define WAIT_LOOP(sem) "{.reg .pred p; mov.u32 %0, 0; W: mbarrier.try_wait.parity" sem ".shared::cta.b64 p, [%1], %2; @p bra.uni D; add.u32 %0, %0, 1; setp.lt.u32 p, %0, %3; @p bra.uni W; D:}"
__device__ __forceinline__ void mbar_wait(uint32_t b, uint32_t ph = 0) {
  int it;
  asm volatile(WAIT_LOOP("") : "=&r"(it) : "r"(b), "r"(ph), "n"(SPIN_LIMIT) : "memory");
}
__device__ __forceinline__ void mbar_wait_cluster(uint32_t b, uint32_t ph = 0) {
  int it;
  asm volatile(WAIT_LOOP(".acquire.cluster") : "=&r"(it) : "r"(b), "r"(ph), "n"(SPIN_LIMIT) : "memory");
}
__device__ __forceinline__ void wait_clock(uint32_t t) {
  asm volatile("{.reg .pred p; .reg .s32 d; W: mov.u32 d, %%clock; sub.s32 d, d, %0; setp.lt.s32 p, d, 0; @p bra.uni W;}" ::"r"(t) : "memory");
}
__device__ __forceinline__ void tma2d(uint32_t dst, const CUtensorMap* m, int c0, int c1, uint32_t bar) {
  asm volatile("cp.async.bulk.tensor.2d.shared::cluster.global.mbarrier::complete_tx::bytes [%0], [%1, {%3,%4}], [%2];" ::"r"(dst), "l"(m), "r"(bar), "r"(c0), "r"(c1) : "memory");
}
__device__ __forceinline__ void tma3d(uint32_t dst, const CUtensorMap* m, int c0, int c1, int c2, uint32_t bar) {
  asm volatile("cp.async.bulk.tensor.3d.shared::cluster.global.mbarrier::complete_tx::bytes [%0], [%1, {%3,%4,%5}], [%2];" ::"r"(dst), "l"(m), "r"(bar), "r"(c0), "r"(c1), "r"(c2) : "memory");
}
__device__ __forceinline__ void tma5d(uint32_t dst, const CUtensorMap* m, int c0, int c4, uint32_t bar) {
  asm volatile("cp.async.bulk.tensor.5d.shared::cluster.global.mbarrier::complete_tx::bytes [%0], [%1, {%4,%3,%3,%3,%5}], [%2];" ::"r"(dst), "l"(m), "r"(bar), "r"(0), "r"(c0), "r"(c4) : "memory");
}
__device__ __forceinline__ void tma2d_store(const CUtensorMap* m, int c0, int c1, uint32_t src) {
  asm volatile("cp.async.bulk.tensor.2d.global.shared::cta.bulk_group [%0, {%2,%3}], [%1];" ::"l"(m), "r"(src), "r"(c0), "r"(c1) : "memory");
}
__device__ __forceinline__ void bulk_load(uint32_t dst, const void* src, uint32_t bytes, uint32_t bar) {
  asm volatile("cp.async.bulk.shared::cluster.global.mbarrier::complete_tx::bytes [%0], [%1], %2, [%3];" ::"r"(dst), "l"(src), "r"(bytes), "r"(bar) : "memory");
}
__device__ __forceinline__ void prefetch_map(const CUtensorMap* m) { asm volatile("prefetch.tensormap [%0];" ::"l"(m) : "memory"); }
__device__ __forceinline__ void bulk_commit() { asm volatile("cp.async.bulk.commit_group;" ::: "memory"); }
__device__ __forceinline__ void bulk_wait_read() { asm volatile("cp.async.bulk.wait_group.read 0;" ::: "memory"); }
__device__ __forceinline__ void fence_async_smem() { asm volatile("fence.proxy.async.shared::cta;" ::: "memory"); }
__device__ __forceinline__ void fence_async_all() { asm volatile("fence.proxy.async.global;" ::: "memory"); }
__device__ __forceinline__ void named_bar(int id, int n) { asm volatile("bar.sync %0, %1;" ::"r"(id), "r"(n) : "memory"); }
__device__ __forceinline__ bool bar_all(int id, bool v) {
  uint32_t r;
  asm volatile("{.reg .pred p, q; setp.ne.u32 p, %2, 0; bar.red.and.pred q, %1, 128, p; selp.u32 %0, 1, 0, q;}" : "=r"(r) : "r"(id), "r"((uint32_t)v) : "memory");
  return __all_sync(~0u, r);
}
__device__ __forceinline__ void cluster_wait() { asm volatile("barrier.cluster.wait.aligned;" ::: "memory"); }
__device__ __forceinline__ void wg_fence() { asm volatile("wgmma.fence.sync.aligned;" ::: "memory"); }
__device__ __forceinline__ void wg_commit() { asm volatile("wgmma.commit_group.sync.aligned;" ::: "memory"); }
template <int N> __device__ __forceinline__ void wg_wait() { asm volatile("wgmma.wait_group.sync.aligned %0;" ::"n"(N) : "memory"); }
template <int N> __device__ __forceinline__ void fence_regs(float (&a)[N]) {
#pragma unroll
  for (int i = 0; i < N; i++) asm volatile("" : "+f"(a[i])::"memory");
}
__device__ __forceinline__ uint64_t mkdesc(uint32_t addr, uint32_t lbo, uint32_t sbo, uint32_t swz) {
  uint32_t lo = (addr >> 4) | ((lbo >> 4) << 16), hi = (sbo >> 4) | (swz << 30);
  return ((uint64_t)hi << 32) | lo;
}
__device__ __forceinline__ void stmatrix_x4(uint32_t a, uint32_t r0, uint32_t r1, uint32_t r2, uint32_t r3) {
  asm volatile("stmatrix.sync.aligned.m8n8.x4.shared.b16 [%0], {%1,%2,%3,%4};" ::"r"(a), "r"(r0), "r"(r1), "r"(r2), "r"(r3) : "memory");
}
__device__ __forceinline__ void stmatrix_x4_t(uint32_t a, uint32_t r0, uint32_t r1, uint32_t r2, uint32_t r3) {
  asm volatile("stmatrix.sync.aligned.m8n8.x4.trans.shared.b16 [%0], {%1,%2,%3,%4};" ::"r"(a), "r"(r0), "r"(r1), "r"(r2), "r"(r3) : "memory");
}
__device__ __forceinline__ void ldmatrix_x4_t(uint32_t* r, uint32_t a) {
  asm volatile("ldmatrix.sync.aligned.m8n8.x4.trans.shared.b16 {%0,%1,%2,%3}, [%4];" : "=r"(r[0]), "=r"(r[1]), "=r"(r[2]), "=r"(r[3]) : "r"(a) : "memory");
}
__device__ __forceinline__ uint32_t lds32(uint32_t a) { uint32_t v; asm volatile("ld.shared.b32 %0, [%1];" : "=r"(v) : "r"(a) : "memory"); return v; }
__device__ __forceinline__ uint2 lds64(uint32_t a) { uint2 v; asm volatile("ld.shared.v2.b32 {%0,%1}, [%2];" : "=r"(v.x), "=r"(v.y) : "r"(a) : "memory"); return v; }
__device__ __forceinline__ uint4 lds128(uint32_t a) { uint4 v; asm volatile("ld.shared.v4.b32 {%0,%1,%2,%3}, [%4];" : "=r"(v.x), "=r"(v.y), "=r"(v.z), "=r"(v.w) : "r"(a) : "memory"); return v; }
__device__ __forceinline__ void sts32(uint32_t a, uint32_t v) { asm volatile("st.shared.b32 [%0], %1;" ::"r"(a), "r"(v) : "memory"); }
__device__ __forceinline__ void sts64(uint32_t a, uint32_t x, uint32_t y) { asm volatile("st.shared.v2.b32 [%0], {%1,%2};" ::"r"(a), "r"(x), "r"(y) : "memory"); }
__device__ __forceinline__ void sts128(uint32_t a, uint32_t x, uint32_t y, uint32_t z, uint32_t w) { asm volatile("st.shared.v4.b32 [%0], {%1,%2,%3,%4};" ::"r"(a), "r"(x), "r"(y), "r"(z), "r"(w) : "memory"); }
__device__ __forceinline__ uint4 ld_relaxed128(const void* p) { uint4 v; asm volatile("ld.relaxed.gpu.global.v4.u32 {%0,%1,%2,%3}, [%4];" : "=r"(v.x), "=r"(v.y), "=r"(v.z), "=r"(v.w) : "l"(p) : "memory"); return v; }
__device__ __forceinline__ uint2 ld_relaxed64(const void* p) { uint2 v; asm volatile("ld.relaxed.gpu.global.v2.u32 {%0,%1}, [%2];" : "=r"(v.x), "=r"(v.y) : "l"(p) : "memory"); return v; }
__device__ __forceinline__ uint32_t ld_relaxed32(const void* p) { uint32_t v; asm volatile("ld.relaxed.gpu.global.u32 %0, [%1];" : "=r"(v) : "l"(p) : "memory"); return v; }
__device__ __forceinline__ void st_relaxed128(void* p, uint32_t x, uint32_t y, uint32_t z, uint32_t w) { asm volatile("st.relaxed.gpu.global.v4.u32 [%0], {%1,%2,%3,%4};" ::"l"(p), "r"(x), "r"(y), "r"(z), "r"(w) : "memory"); }
__device__ __forceinline__ void st_relaxed32(void* p, uint32_t x) { asm volatile("st.relaxed.gpu.global.u32 [%0], %1;" ::"l"(p), "r"(x) : "memory"); }
__device__ __forceinline__ void red_hint(unsigned* p) { asm volatile("red.relaxed.gpu.global.add.u32 [%0], 1;" ::"l"(p) : "memory"); }
__device__ __forceinline__ void publish(uint32_t* p, uint32_t x) { asm volatile("{.reg .b32 t; atom.relaxed.gpu.global.exch.b32 t, [%0], %1;}" ::"l"(p), "r"(x) : "memory"); }
__device__ __forceinline__ uint32_t ldg32(const void* p) { uint32_t v; asm volatile("ld.global.nc.L1::no_allocate.b32 %0, [%1];" : "=r"(v) : "l"(p)); return v; }
__device__ __forceinline__ uint32_t pack_bf16(float lo, float hi) { uint32_t r; asm("cvt.rn.bf16x2.f32 %0, %1, %2;" : "=r"(r) : "f"(hi), "f"(lo)); return r; }
__device__ __forceinline__ float bf_lo(uint32_t v) { return __uint_as_float(v << 16); }
__device__ __forceinline__ float bf_hi(uint32_t v) { return __uint_as_float(v & 0xFFFF0000u); }
__device__ __forceinline__ uint32_t bmul2(uint32_t a, uint32_t b) { uint32_t r; asm("mul.rn.bf16x2 %0, %1, %2;" : "=r"(r) : "r"(a), "r"(b)); return r; }
__device__ __forceinline__ uint32_t badd2(uint32_t a, uint32_t b) { uint32_t r; asm("add.rn.bf16x2 %0, %1, %2;" : "=r"(r) : "r"(a), "r"(b)); return r; }
__device__ __forceinline__ uint32_t bfma2(uint32_t a, uint32_t b, uint32_t c) { uint32_t r; asm("fma.rn.bf16x2 %0, %1, %2, %3;" : "=r"(r) : "r"(a), "r"(b), "r"(c)); return r; }
__device__ __forceinline__ uint32_t set_tag(uint32_t x, uint32_t mask, uint32_t e) { uint32_t r; asm("lop3.b32 %0, %1, %2, %3, 0xB8;" : "=r"(r) : "r"(x), "r"(mask), "r"(e)); return r; }
__device__ __forceinline__ uint32_t opaque(uint32_t x) { asm volatile("" : "+r"(x)); return x; }
__device__ __forceinline__ float rbf(float x) { return __bfloat162float(__float2bfloat16(x)); }
__device__ __forceinline__ float silu_f(float x) {
  float e, r;
  asm("ex2.approx.ftz.f32 %0, %1;" : "=f"(e) : "f"(x * -1.4426950408889634f));
  asm("rcp.approx.ftz.f32 %0, %1;" : "=f"(r) : "f"(1.f + e));
  return x * r;
}
__device__ __forceinline__ float silu2(float g, float a, float b) {
  float t;
  asm("tanh.approx.f32 %0, %1;" : "=f"(t) : "f"(g * a));
  return fmaf(g * b, t, g * b);
}
__device__ __forceinline__ void pin(int off, uint32_t x) { asm volatile("{.reg .pred p; setp.lt.s32 p, %0, 0; @p st.shared.b32 [%0], %1;}" ::"r"(off), "r"(x) : "memory"); }
__device__ __forceinline__ void pin4(int off, const uint32_t* x) { asm volatile("{.reg .pred p; setp.lt.s32 p, %0, 0; @p st.shared.v4.b32 [%0], {%1,%2,%3,%4};}" ::"r"(off), "r"(x[0]), "r"(x[1]), "r"(x[2]), "r"(x[3]) : "memory"); }
__device__ __forceinline__ void split(int x, int n) { asm volatile("{.reg .pred p; setp.eq.s32 p, %0, %1; @p trap;}" ::"r"(x), "r"(~n) : "memory"); }
__device__ __forceinline__ void ln_final(float s, float q, float& m, float& sd) {
  m = s * (1.f / D_);
  asm("sqrt.approx.f32 %0, %1;" : "=f"(sd) : "f"(rbf(rbf(fmaxf(fmaf(-m, m, q * (1.f / D_)), 0.f)) + 1e-5f)));
  sd = rbf(sd);
}
__device__ __forceinline__ float rcpf(float x) { float r; asm("rcp.approx.f32 %0, %1;" : "=f"(r) : "f"(x)); return r; }

__device__ __forceinline__ void wg_rs16_0(float* d, const uint32_t* a, uint64_t db, int sc) {
  asm volatile("{.reg .pred p; setp.ne.b32 p, %13, 0; wgmma.mma_async.sync.aligned.m64n16k16.f32.bf16.bf16 {%0,%1,%2,%3,%4,%5,%6,%7}, {%8,%9,%10,%11}, %12, p, 1, 1, 0;}"
    : "+f"(d[0]),"+f"(d[1]),"+f"(d[2]),"+f"(d[3]),"+f"(d[4]),"+f"(d[5]),"+f"(d[6]),"+f"(d[7]) : "r"(a[0]),"r"(a[1]),"r"(a[2]),"r"(a[3]),"l"(db),"r"(sc));
}
__device__ __forceinline__ void wg_rs32_0(float* d, const uint32_t* a, uint64_t db, int sc) {
  asm volatile("{.reg .pred p; setp.ne.b32 p, %21, 0; wgmma.mma_async.sync.aligned.m64n32k16.f32.bf16.bf16 {%0,%1,%2,%3,%4,%5,%6,%7,%8,%9,%10,%11,%12,%13,%14,%15}, {%16,%17,%18,%19}, %20, p, 1, 1, 0;}"
    : "+f"(d[0]),"+f"(d[1]),"+f"(d[2]),"+f"(d[3]),"+f"(d[4]),"+f"(d[5]),"+f"(d[6]),"+f"(d[7]),"+f"(d[8]),"+f"(d[9]),"+f"(d[10]),"+f"(d[11]),"+f"(d[12]),"+f"(d[13]),"+f"(d[14]),"+f"(d[15]) : "r"(a[0]),"r"(a[1]),"r"(a[2]),"r"(a[3]),"l"(db),"r"(sc));
}
__device__ __forceinline__ void wg_rs48_0(float* d, const uint32_t* a, uint64_t db, int sc) {
  asm volatile("{.reg .pred p; setp.ne.b32 p, %29, 0; wgmma.mma_async.sync.aligned.m64n48k16.f32.bf16.bf16 {%0,%1,%2,%3,%4,%5,%6,%7,%8,%9,%10,%11,%12,%13,%14,%15,%16,%17,%18,%19,%20,%21,%22,%23}, {%24,%25,%26,%27}, %28, p, 1, 1, 0;}"
    : "+f"(d[0]),"+f"(d[1]),"+f"(d[2]),"+f"(d[3]),"+f"(d[4]),"+f"(d[5]),"+f"(d[6]),"+f"(d[7]),"+f"(d[8]),"+f"(d[9]),"+f"(d[10]),"+f"(d[11]),"+f"(d[12]),"+f"(d[13]),"+f"(d[14]),"+f"(d[15]),"+f"(d[16]),"+f"(d[17]),"+f"(d[18]),"+f"(d[19]),"+f"(d[20]),"+f"(d[21]),"+f"(d[22]),"+f"(d[23]) : "r"(a[0]),"r"(a[1]),"r"(a[2]),"r"(a[3]),"l"(db),"r"(sc));
}
__device__ __forceinline__ void wg_rs64_0(float* d, const uint32_t* a, uint64_t db, int sc) {
  asm volatile("{.reg .pred p; setp.ne.b32 p, %37, 0; wgmma.mma_async.sync.aligned.m64n64k16.f32.bf16.bf16 {%0,%1,%2,%3,%4,%5,%6,%7,%8,%9,%10,%11,%12,%13,%14,%15,%16,%17,%18,%19,%20,%21,%22,%23,%24,%25,%26,%27,%28,%29,%30,%31}, {%32,%33,%34,%35}, %36, p, 1, 1, 0;}"
    : "+f"(d[0]),"+f"(d[1]),"+f"(d[2]),"+f"(d[3]),"+f"(d[4]),"+f"(d[5]),"+f"(d[6]),"+f"(d[7]),"+f"(d[8]),"+f"(d[9]),"+f"(d[10]),"+f"(d[11]),"+f"(d[12]),"+f"(d[13]),"+f"(d[14]),"+f"(d[15]),"+f"(d[16]),"+f"(d[17]),"+f"(d[18]),"+f"(d[19]),"+f"(d[20]),"+f"(d[21]),"+f"(d[22]),"+f"(d[23]),"+f"(d[24]),"+f"(d[25]),"+f"(d[26]),"+f"(d[27]),"+f"(d[28]),"+f"(d[29]),"+f"(d[30]),"+f"(d[31]) : "r"(a[0]),"r"(a[1]),"r"(a[2]),"r"(a[3]),"l"(db),"r"(sc));
}
__device__ __forceinline__ void wg_rs80_0(float* d, const uint32_t* a, uint64_t db, int sc) {
  asm volatile("{.reg .pred p; setp.ne.b32 p, %45, 0; wgmma.mma_async.sync.aligned.m64n80k16.f32.bf16.bf16 {%0,%1,%2,%3,%4,%5,%6,%7,%8,%9,%10,%11,%12,%13,%14,%15,%16,%17,%18,%19,%20,%21,%22,%23,%24,%25,%26,%27,%28,%29,%30,%31,%32,%33,%34,%35,%36,%37,%38,%39}, {%40,%41,%42,%43}, %44, p, 1, 1, 0;}"
    : "+f"(d[0]),"+f"(d[1]),"+f"(d[2]),"+f"(d[3]),"+f"(d[4]),"+f"(d[5]),"+f"(d[6]),"+f"(d[7]),"+f"(d[8]),"+f"(d[9]),"+f"(d[10]),"+f"(d[11]),"+f"(d[12]),"+f"(d[13]),"+f"(d[14]),"+f"(d[15]),"+f"(d[16]),"+f"(d[17]),"+f"(d[18]),"+f"(d[19]),"+f"(d[20]),"+f"(d[21]),"+f"(d[22]),"+f"(d[23]),"+f"(d[24]),"+f"(d[25]),"+f"(d[26]),"+f"(d[27]),"+f"(d[28]),"+f"(d[29]),"+f"(d[30]),"+f"(d[31]),"+f"(d[32]),"+f"(d[33]),"+f"(d[34]),"+f"(d[35]),"+f"(d[36]),"+f"(d[37]),"+f"(d[38]),"+f"(d[39]) : "r"(a[0]),"r"(a[1]),"r"(a[2]),"r"(a[3]),"l"(db),"r"(sc));
}
__device__ __forceinline__ void wg_rs96_0(float* d, const uint32_t* a, uint64_t db, int sc) {
  asm volatile("{.reg .pred p; setp.ne.b32 p, %53, 0; wgmma.mma_async.sync.aligned.m64n96k16.f32.bf16.bf16 {%0,%1,%2,%3,%4,%5,%6,%7,%8,%9,%10,%11,%12,%13,%14,%15,%16,%17,%18,%19,%20,%21,%22,%23,%24,%25,%26,%27,%28,%29,%30,%31,%32,%33,%34,%35,%36,%37,%38,%39,%40,%41,%42,%43,%44,%45,%46,%47}, {%48,%49,%50,%51}, %52, p, 1, 1, 0;}"
    : "+f"(d[0]),"+f"(d[1]),"+f"(d[2]),"+f"(d[3]),"+f"(d[4]),"+f"(d[5]),"+f"(d[6]),"+f"(d[7]),"+f"(d[8]),"+f"(d[9]),"+f"(d[10]),"+f"(d[11]),"+f"(d[12]),"+f"(d[13]),"+f"(d[14]),"+f"(d[15]),"+f"(d[16]),"+f"(d[17]),"+f"(d[18]),"+f"(d[19]),"+f"(d[20]),"+f"(d[21]),"+f"(d[22]),"+f"(d[23]),"+f"(d[24]),"+f"(d[25]),"+f"(d[26]),"+f"(d[27]),"+f"(d[28]),"+f"(d[29]),"+f"(d[30]),"+f"(d[31]),"+f"(d[32]),"+f"(d[33]),"+f"(d[34]),"+f"(d[35]),"+f"(d[36]),"+f"(d[37]),"+f"(d[38]),"+f"(d[39]),"+f"(d[40]),"+f"(d[41]),"+f"(d[42]),"+f"(d[43]),"+f"(d[44]),"+f"(d[45]),"+f"(d[46]),"+f"(d[47]) : "r"(a[0]),"r"(a[1]),"r"(a[2]),"r"(a[3]),"l"(db),"r"(sc));
}
__device__ __forceinline__ void wg_rs112_0(float* d, const uint32_t* a, uint64_t db, int sc) {
  asm volatile("{.reg .pred p; setp.ne.b32 p, %61, 0; wgmma.mma_async.sync.aligned.m64n112k16.f32.bf16.bf16 {%0,%1,%2,%3,%4,%5,%6,%7,%8,%9,%10,%11,%12,%13,%14,%15,%16,%17,%18,%19,%20,%21,%22,%23,%24,%25,%26,%27,%28,%29,%30,%31,%32,%33,%34,%35,%36,%37,%38,%39,%40,%41,%42,%43,%44,%45,%46,%47,%48,%49,%50,%51,%52,%53,%54,%55}, {%56,%57,%58,%59}, %60, p, 1, 1, 0;}"
    : "+f"(d[0]),"+f"(d[1]),"+f"(d[2]),"+f"(d[3]),"+f"(d[4]),"+f"(d[5]),"+f"(d[6]),"+f"(d[7]),"+f"(d[8]),"+f"(d[9]),"+f"(d[10]),"+f"(d[11]),"+f"(d[12]),"+f"(d[13]),"+f"(d[14]),"+f"(d[15]),"+f"(d[16]),"+f"(d[17]),"+f"(d[18]),"+f"(d[19]),"+f"(d[20]),"+f"(d[21]),"+f"(d[22]),"+f"(d[23]),"+f"(d[24]),"+f"(d[25]),"+f"(d[26]),"+f"(d[27]),"+f"(d[28]),"+f"(d[29]),"+f"(d[30]),"+f"(d[31]),"+f"(d[32]),"+f"(d[33]),"+f"(d[34]),"+f"(d[35]),"+f"(d[36]),"+f"(d[37]),"+f"(d[38]),"+f"(d[39]),"+f"(d[40]),"+f"(d[41]),"+f"(d[42]),"+f"(d[43]),"+f"(d[44]),"+f"(d[45]),"+f"(d[46]),"+f"(d[47]),"+f"(d[48]),"+f"(d[49]),"+f"(d[50]),"+f"(d[51]),"+f"(d[52]),"+f"(d[53]),"+f"(d[54]),"+f"(d[55]) : "r"(a[0]),"r"(a[1]),"r"(a[2]),"r"(a[3]),"l"(db),"r"(sc));
}
__device__ __forceinline__ void wg_rs128_0(float* d, const uint32_t* a, uint64_t db, int sc) {
  asm volatile("{.reg .pred p; setp.ne.b32 p, %69, 0; wgmma.mma_async.sync.aligned.m64n128k16.f32.bf16.bf16 {%0,%1,%2,%3,%4,%5,%6,%7,%8,%9,%10,%11,%12,%13,%14,%15,%16,%17,%18,%19,%20,%21,%22,%23,%24,%25,%26,%27,%28,%29,%30,%31,%32,%33,%34,%35,%36,%37,%38,%39,%40,%41,%42,%43,%44,%45,%46,%47,%48,%49,%50,%51,%52,%53,%54,%55,%56,%57,%58,%59,%60,%61,%62,%63}, {%64,%65,%66,%67}, %68, p, 1, 1, 0;}"
    : "+f"(d[0]),"+f"(d[1]),"+f"(d[2]),"+f"(d[3]),"+f"(d[4]),"+f"(d[5]),"+f"(d[6]),"+f"(d[7]),"+f"(d[8]),"+f"(d[9]),"+f"(d[10]),"+f"(d[11]),"+f"(d[12]),"+f"(d[13]),"+f"(d[14]),"+f"(d[15]),"+f"(d[16]),"+f"(d[17]),"+f"(d[18]),"+f"(d[19]),"+f"(d[20]),"+f"(d[21]),"+f"(d[22]),"+f"(d[23]),"+f"(d[24]),"+f"(d[25]),"+f"(d[26]),"+f"(d[27]),"+f"(d[28]),"+f"(d[29]),"+f"(d[30]),"+f"(d[31]),"+f"(d[32]),"+f"(d[33]),"+f"(d[34]),"+f"(d[35]),"+f"(d[36]),"+f"(d[37]),"+f"(d[38]),"+f"(d[39]),"+f"(d[40]),"+f"(d[41]),"+f"(d[42]),"+f"(d[43]),"+f"(d[44]),"+f"(d[45]),"+f"(d[46]),"+f"(d[47]),"+f"(d[48]),"+f"(d[49]),"+f"(d[50]),"+f"(d[51]),"+f"(d[52]),"+f"(d[53]),"+f"(d[54]),"+f"(d[55]),"+f"(d[56]),"+f"(d[57]),"+f"(d[58]),"+f"(d[59]),"+f"(d[60]),"+f"(d[61]),"+f"(d[62]),"+f"(d[63]) : "r"(a[0]),"r"(a[1]),"r"(a[2]),"r"(a[3]),"l"(db),"r"(sc));
}
__device__ __forceinline__ void wg_rs144_0(float* d, const uint32_t* a, uint64_t db, int sc) {
  asm volatile("{.reg .pred p; setp.ne.b32 p, %77, 0; wgmma.mma_async.sync.aligned.m64n144k16.f32.bf16.bf16 {%0,%1,%2,%3,%4,%5,%6,%7,%8,%9,%10,%11,%12,%13,%14,%15,%16,%17,%18,%19,%20,%21,%22,%23,%24,%25,%26,%27,%28,%29,%30,%31,%32,%33,%34,%35,%36,%37,%38,%39,%40,%41,%42,%43,%44,%45,%46,%47,%48,%49,%50,%51,%52,%53,%54,%55,%56,%57,%58,%59,%60,%61,%62,%63,%64,%65,%66,%67,%68,%69,%70,%71}, {%72,%73,%74,%75}, %76, p, 1, 1, 0;}"
    : "+f"(d[0]),"+f"(d[1]),"+f"(d[2]),"+f"(d[3]),"+f"(d[4]),"+f"(d[5]),"+f"(d[6]),"+f"(d[7]),"+f"(d[8]),"+f"(d[9]),"+f"(d[10]),"+f"(d[11]),"+f"(d[12]),"+f"(d[13]),"+f"(d[14]),"+f"(d[15]),"+f"(d[16]),"+f"(d[17]),"+f"(d[18]),"+f"(d[19]),"+f"(d[20]),"+f"(d[21]),"+f"(d[22]),"+f"(d[23]),"+f"(d[24]),"+f"(d[25]),"+f"(d[26]),"+f"(d[27]),"+f"(d[28]),"+f"(d[29]),"+f"(d[30]),"+f"(d[31]),"+f"(d[32]),"+f"(d[33]),"+f"(d[34]),"+f"(d[35]),"+f"(d[36]),"+f"(d[37]),"+f"(d[38]),"+f"(d[39]),"+f"(d[40]),"+f"(d[41]),"+f"(d[42]),"+f"(d[43]),"+f"(d[44]),"+f"(d[45]),"+f"(d[46]),"+f"(d[47]),"+f"(d[48]),"+f"(d[49]),"+f"(d[50]),"+f"(d[51]),"+f"(d[52]),"+f"(d[53]),"+f"(d[54]),"+f"(d[55]),"+f"(d[56]),"+f"(d[57]),"+f"(d[58]),"+f"(d[59]),"+f"(d[60]),"+f"(d[61]),"+f"(d[62]),"+f"(d[63]),"+f"(d[64]),"+f"(d[65]),"+f"(d[66]),"+f"(d[67]),"+f"(d[68]),"+f"(d[69]),"+f"(d[70]),"+f"(d[71]) : "r"(a[0]),"r"(a[1]),"r"(a[2]),"r"(a[3]),"l"(db),"r"(sc));
}
__device__ __forceinline__ void wg_rs160_0(float* d, const uint32_t* a, uint64_t db, int sc) {
  asm volatile("{.reg .pred p; setp.ne.b32 p, %85, 0; wgmma.mma_async.sync.aligned.m64n160k16.f32.bf16.bf16 {%0,%1,%2,%3,%4,%5,%6,%7,%8,%9,%10,%11,%12,%13,%14,%15,%16,%17,%18,%19,%20,%21,%22,%23,%24,%25,%26,%27,%28,%29,%30,%31,%32,%33,%34,%35,%36,%37,%38,%39,%40,%41,%42,%43,%44,%45,%46,%47,%48,%49,%50,%51,%52,%53,%54,%55,%56,%57,%58,%59,%60,%61,%62,%63,%64,%65,%66,%67,%68,%69,%70,%71,%72,%73,%74,%75,%76,%77,%78,%79}, {%80,%81,%82,%83}, %84, p, 1, 1, 0;}"
    : "+f"(d[0]),"+f"(d[1]),"+f"(d[2]),"+f"(d[3]),"+f"(d[4]),"+f"(d[5]),"+f"(d[6]),"+f"(d[7]),"+f"(d[8]),"+f"(d[9]),"+f"(d[10]),"+f"(d[11]),"+f"(d[12]),"+f"(d[13]),"+f"(d[14]),"+f"(d[15]),"+f"(d[16]),"+f"(d[17]),"+f"(d[18]),"+f"(d[19]),"+f"(d[20]),"+f"(d[21]),"+f"(d[22]),"+f"(d[23]),"+f"(d[24]),"+f"(d[25]),"+f"(d[26]),"+f"(d[27]),"+f"(d[28]),"+f"(d[29]),"+f"(d[30]),"+f"(d[31]),"+f"(d[32]),"+f"(d[33]),"+f"(d[34]),"+f"(d[35]),"+f"(d[36]),"+f"(d[37]),"+f"(d[38]),"+f"(d[39]),"+f"(d[40]),"+f"(d[41]),"+f"(d[42]),"+f"(d[43]),"+f"(d[44]),"+f"(d[45]),"+f"(d[46]),"+f"(d[47]),"+f"(d[48]),"+f"(d[49]),"+f"(d[50]),"+f"(d[51]),"+f"(d[52]),"+f"(d[53]),"+f"(d[54]),"+f"(d[55]),"+f"(d[56]),"+f"(d[57]),"+f"(d[58]),"+f"(d[59]),"+f"(d[60]),"+f"(d[61]),"+f"(d[62]),"+f"(d[63]),"+f"(d[64]),"+f"(d[65]),"+f"(d[66]),"+f"(d[67]),"+f"(d[68]),"+f"(d[69]),"+f"(d[70]),"+f"(d[71]),"+f"(d[72]),"+f"(d[73]),"+f"(d[74]),"+f"(d[75]),"+f"(d[76]),"+f"(d[77]),"+f"(d[78]),"+f"(d[79]) : "r"(a[0]),"r"(a[1]),"r"(a[2]),"r"(a[3]),"l"(db),"r"(sc));
}
__device__ __forceinline__ void wg_rs176_0(float* d, const uint32_t* a, uint64_t db, int sc) {
  asm volatile("{.reg .pred p; setp.ne.b32 p, %93, 0; wgmma.mma_async.sync.aligned.m64n176k16.f32.bf16.bf16 {%0,%1,%2,%3,%4,%5,%6,%7,%8,%9,%10,%11,%12,%13,%14,%15,%16,%17,%18,%19,%20,%21,%22,%23,%24,%25,%26,%27,%28,%29,%30,%31,%32,%33,%34,%35,%36,%37,%38,%39,%40,%41,%42,%43,%44,%45,%46,%47,%48,%49,%50,%51,%52,%53,%54,%55,%56,%57,%58,%59,%60,%61,%62,%63,%64,%65,%66,%67,%68,%69,%70,%71,%72,%73,%74,%75,%76,%77,%78,%79,%80,%81,%82,%83,%84,%85,%86,%87}, {%88,%89,%90,%91}, %92, p, 1, 1, 0;}"
    : "+f"(d[0]),"+f"(d[1]),"+f"(d[2]),"+f"(d[3]),"+f"(d[4]),"+f"(d[5]),"+f"(d[6]),"+f"(d[7]),"+f"(d[8]),"+f"(d[9]),"+f"(d[10]),"+f"(d[11]),"+f"(d[12]),"+f"(d[13]),"+f"(d[14]),"+f"(d[15]),"+f"(d[16]),"+f"(d[17]),"+f"(d[18]),"+f"(d[19]),"+f"(d[20]),"+f"(d[21]),"+f"(d[22]),"+f"(d[23]),"+f"(d[24]),"+f"(d[25]),"+f"(d[26]),"+f"(d[27]),"+f"(d[28]),"+f"(d[29]),"+f"(d[30]),"+f"(d[31]),"+f"(d[32]),"+f"(d[33]),"+f"(d[34]),"+f"(d[35]),"+f"(d[36]),"+f"(d[37]),"+f"(d[38]),"+f"(d[39]),"+f"(d[40]),"+f"(d[41]),"+f"(d[42]),"+f"(d[43]),"+f"(d[44]),"+f"(d[45]),"+f"(d[46]),"+f"(d[47]),"+f"(d[48]),"+f"(d[49]),"+f"(d[50]),"+f"(d[51]),"+f"(d[52]),"+f"(d[53]),"+f"(d[54]),"+f"(d[55]),"+f"(d[56]),"+f"(d[57]),"+f"(d[58]),"+f"(d[59]),"+f"(d[60]),"+f"(d[61]),"+f"(d[62]),"+f"(d[63]),"+f"(d[64]),"+f"(d[65]),"+f"(d[66]),"+f"(d[67]),"+f"(d[68]),"+f"(d[69]),"+f"(d[70]),"+f"(d[71]),"+f"(d[72]),"+f"(d[73]),"+f"(d[74]),"+f"(d[75]),"+f"(d[76]),"+f"(d[77]),"+f"(d[78]),"+f"(d[79]),"+f"(d[80]),"+f"(d[81]),"+f"(d[82]),"+f"(d[83]),"+f"(d[84]),"+f"(d[85]),"+f"(d[86]),"+f"(d[87]) : "r"(a[0]),"r"(a[1]),"r"(a[2]),"r"(a[3]),"l"(db),"r"(sc));
}
__device__ __forceinline__ void wg_rs192_0(float* d, const uint32_t* a, uint64_t db, int sc) {
  asm volatile("{.reg .pred p; setp.ne.b32 p, %101, 0; wgmma.mma_async.sync.aligned.m64n192k16.f32.bf16.bf16 {%0,%1,%2,%3,%4,%5,%6,%7,%8,%9,%10,%11,%12,%13,%14,%15,%16,%17,%18,%19,%20,%21,%22,%23,%24,%25,%26,%27,%28,%29,%30,%31,%32,%33,%34,%35,%36,%37,%38,%39,%40,%41,%42,%43,%44,%45,%46,%47,%48,%49,%50,%51,%52,%53,%54,%55,%56,%57,%58,%59,%60,%61,%62,%63,%64,%65,%66,%67,%68,%69,%70,%71,%72,%73,%74,%75,%76,%77,%78,%79,%80,%81,%82,%83,%84,%85,%86,%87,%88,%89,%90,%91,%92,%93,%94,%95}, {%96,%97,%98,%99}, %100, p, 1, 1, 0;}"
    : "+f"(d[0]),"+f"(d[1]),"+f"(d[2]),"+f"(d[3]),"+f"(d[4]),"+f"(d[5]),"+f"(d[6]),"+f"(d[7]),"+f"(d[8]),"+f"(d[9]),"+f"(d[10]),"+f"(d[11]),"+f"(d[12]),"+f"(d[13]),"+f"(d[14]),"+f"(d[15]),"+f"(d[16]),"+f"(d[17]),"+f"(d[18]),"+f"(d[19]),"+f"(d[20]),"+f"(d[21]),"+f"(d[22]),"+f"(d[23]),"+f"(d[24]),"+f"(d[25]),"+f"(d[26]),"+f"(d[27]),"+f"(d[28]),"+f"(d[29]),"+f"(d[30]),"+f"(d[31]),"+f"(d[32]),"+f"(d[33]),"+f"(d[34]),"+f"(d[35]),"+f"(d[36]),"+f"(d[37]),"+f"(d[38]),"+f"(d[39]),"+f"(d[40]),"+f"(d[41]),"+f"(d[42]),"+f"(d[43]),"+f"(d[44]),"+f"(d[45]),"+f"(d[46]),"+f"(d[47]),"+f"(d[48]),"+f"(d[49]),"+f"(d[50]),"+f"(d[51]),"+f"(d[52]),"+f"(d[53]),"+f"(d[54]),"+f"(d[55]),"+f"(d[56]),"+f"(d[57]),"+f"(d[58]),"+f"(d[59]),"+f"(d[60]),"+f"(d[61]),"+f"(d[62]),"+f"(d[63]),"+f"(d[64]),"+f"(d[65]),"+f"(d[66]),"+f"(d[67]),"+f"(d[68]),"+f"(d[69]),"+f"(d[70]),"+f"(d[71]),"+f"(d[72]),"+f"(d[73]),"+f"(d[74]),"+f"(d[75]),"+f"(d[76]),"+f"(d[77]),"+f"(d[78]),"+f"(d[79]),"+f"(d[80]),"+f"(d[81]),"+f"(d[82]),"+f"(d[83]),"+f"(d[84]),"+f"(d[85]),"+f"(d[86]),"+f"(d[87]),"+f"(d[88]),"+f"(d[89]),"+f"(d[90]),"+f"(d[91]),"+f"(d[92]),"+f"(d[93]),"+f"(d[94]),"+f"(d[95]) : "r"(a[0]),"r"(a[1]),"r"(a[2]),"r"(a[3]),"l"(db),"r"(sc));
}
__device__ __forceinline__ void wg_ss192_11(float* d, uint64_t da, uint64_t db, int sc) {
  asm volatile("{.reg .pred p; setp.ne.b32 p, %98, 0; wgmma.mma_async.sync.aligned.m64n192k16.f32.bf16.bf16 {%0,%1,%2,%3,%4,%5,%6,%7,%8,%9,%10,%11,%12,%13,%14,%15,%16,%17,%18,%19,%20,%21,%22,%23,%24,%25,%26,%27,%28,%29,%30,%31,%32,%33,%34,%35,%36,%37,%38,%39,%40,%41,%42,%43,%44,%45,%46,%47,%48,%49,%50,%51,%52,%53,%54,%55,%56,%57,%58,%59,%60,%61,%62,%63,%64,%65,%66,%67,%68,%69,%70,%71,%72,%73,%74,%75,%76,%77,%78,%79,%80,%81,%82,%83,%84,%85,%86,%87,%88,%89,%90,%91,%92,%93,%94,%95}, %96, %97, p, 1, 1, 1, 1;}"
    : "+f"(d[0]),"+f"(d[1]),"+f"(d[2]),"+f"(d[3]),"+f"(d[4]),"+f"(d[5]),"+f"(d[6]),"+f"(d[7]),"+f"(d[8]),"+f"(d[9]),"+f"(d[10]),"+f"(d[11]),"+f"(d[12]),"+f"(d[13]),"+f"(d[14]),"+f"(d[15]),"+f"(d[16]),"+f"(d[17]),"+f"(d[18]),"+f"(d[19]),"+f"(d[20]),"+f"(d[21]),"+f"(d[22]),"+f"(d[23]),"+f"(d[24]),"+f"(d[25]),"+f"(d[26]),"+f"(d[27]),"+f"(d[28]),"+f"(d[29]),"+f"(d[30]),"+f"(d[31]),"+f"(d[32]),"+f"(d[33]),"+f"(d[34]),"+f"(d[35]),"+f"(d[36]),"+f"(d[37]),"+f"(d[38]),"+f"(d[39]),"+f"(d[40]),"+f"(d[41]),"+f"(d[42]),"+f"(d[43]),"+f"(d[44]),"+f"(d[45]),"+f"(d[46]),"+f"(d[47]),"+f"(d[48]),"+f"(d[49]),"+f"(d[50]),"+f"(d[51]),"+f"(d[52]),"+f"(d[53]),"+f"(d[54]),"+f"(d[55]),"+f"(d[56]),"+f"(d[57]),"+f"(d[58]),"+f"(d[59]),"+f"(d[60]),"+f"(d[61]),"+f"(d[62]),"+f"(d[63]),"+f"(d[64]),"+f"(d[65]),"+f"(d[66]),"+f"(d[67]),"+f"(d[68]),"+f"(d[69]),"+f"(d[70]),"+f"(d[71]),"+f"(d[72]),"+f"(d[73]),"+f"(d[74]),"+f"(d[75]),"+f"(d[76]),"+f"(d[77]),"+f"(d[78]),"+f"(d[79]),"+f"(d[80]),"+f"(d[81]),"+f"(d[82]),"+f"(d[83]),"+f"(d[84]),"+f"(d[85]),"+f"(d[86]),"+f"(d[87]),"+f"(d[88]),"+f"(d[89]),"+f"(d[90]),"+f"(d[91]),"+f"(d[92]),"+f"(d[93]),"+f"(d[94]),"+f"(d[95]) : "l"(da),"l"(db),"r"(sc));
}
__device__ __forceinline__ void wg_ss192_01(float* d, uint64_t da, uint64_t db, int sc) {
  asm volatile("{.reg .pred p; setp.ne.b32 p, %98, 0; wgmma.mma_async.sync.aligned.m64n192k16.f32.bf16.bf16 {%0,%1,%2,%3,%4,%5,%6,%7,%8,%9,%10,%11,%12,%13,%14,%15,%16,%17,%18,%19,%20,%21,%22,%23,%24,%25,%26,%27,%28,%29,%30,%31,%32,%33,%34,%35,%36,%37,%38,%39,%40,%41,%42,%43,%44,%45,%46,%47,%48,%49,%50,%51,%52,%53,%54,%55,%56,%57,%58,%59,%60,%61,%62,%63,%64,%65,%66,%67,%68,%69,%70,%71,%72,%73,%74,%75,%76,%77,%78,%79,%80,%81,%82,%83,%84,%85,%86,%87,%88,%89,%90,%91,%92,%93,%94,%95}, %96, %97, p, 1, 1, 0, 1;}"
    : "+f"(d[0]),"+f"(d[1]),"+f"(d[2]),"+f"(d[3]),"+f"(d[4]),"+f"(d[5]),"+f"(d[6]),"+f"(d[7]),"+f"(d[8]),"+f"(d[9]),"+f"(d[10]),"+f"(d[11]),"+f"(d[12]),"+f"(d[13]),"+f"(d[14]),"+f"(d[15]),"+f"(d[16]),"+f"(d[17]),"+f"(d[18]),"+f"(d[19]),"+f"(d[20]),"+f"(d[21]),"+f"(d[22]),"+f"(d[23]),"+f"(d[24]),"+f"(d[25]),"+f"(d[26]),"+f"(d[27]),"+f"(d[28]),"+f"(d[29]),"+f"(d[30]),"+f"(d[31]),"+f"(d[32]),"+f"(d[33]),"+f"(d[34]),"+f"(d[35]),"+f"(d[36]),"+f"(d[37]),"+f"(d[38]),"+f"(d[39]),"+f"(d[40]),"+f"(d[41]),"+f"(d[42]),"+f"(d[43]),"+f"(d[44]),"+f"(d[45]),"+f"(d[46]),"+f"(d[47]),"+f"(d[48]),"+f"(d[49]),"+f"(d[50]),"+f"(d[51]),"+f"(d[52]),"+f"(d[53]),"+f"(d[54]),"+f"(d[55]),"+f"(d[56]),"+f"(d[57]),"+f"(d[58]),"+f"(d[59]),"+f"(d[60]),"+f"(d[61]),"+f"(d[62]),"+f"(d[63]),"+f"(d[64]),"+f"(d[65]),"+f"(d[66]),"+f"(d[67]),"+f"(d[68]),"+f"(d[69]),"+f"(d[70]),"+f"(d[71]),"+f"(d[72]),"+f"(d[73]),"+f"(d[74]),"+f"(d[75]),"+f"(d[76]),"+f"(d[77]),"+f"(d[78]),"+f"(d[79]),"+f"(d[80]),"+f"(d[81]),"+f"(d[82]),"+f"(d[83]),"+f"(d[84]),"+f"(d[85]),"+f"(d[86]),"+f"(d[87]),"+f"(d[88]),"+f"(d[89]),"+f"(d[90]),"+f"(d[91]),"+f"(d[92]),"+f"(d[93]),"+f"(d[94]),"+f"(d[95]) : "l"(da),"l"(db),"r"(sc));
}
__device__ __forceinline__ void wg_ss64_11(float* d, uint64_t da, uint64_t db, int sc) {
  asm volatile("{.reg .pred p; setp.ne.b32 p, %34, 0; wgmma.mma_async.sync.aligned.m64n64k16.f32.bf16.bf16 {%0,%1,%2,%3,%4,%5,%6,%7,%8,%9,%10,%11,%12,%13,%14,%15,%16,%17,%18,%19,%20,%21,%22,%23,%24,%25,%26,%27,%28,%29,%30,%31}, %32, %33, p, 1, 1, 1, 1;}"
    : "+f"(d[0]),"+f"(d[1]),"+f"(d[2]),"+f"(d[3]),"+f"(d[4]),"+f"(d[5]),"+f"(d[6]),"+f"(d[7]),"+f"(d[8]),"+f"(d[9]),"+f"(d[10]),"+f"(d[11]),"+f"(d[12]),"+f"(d[13]),"+f"(d[14]),"+f"(d[15]),"+f"(d[16]),"+f"(d[17]),"+f"(d[18]),"+f"(d[19]),"+f"(d[20]),"+f"(d[21]),"+f"(d[22]),"+f"(d[23]),"+f"(d[24]),"+f"(d[25]),"+f"(d[26]),"+f"(d[27]),"+f"(d[28]),"+f"(d[29]),"+f"(d[30]),"+f"(d[31]) : "l"(da),"l"(db),"r"(sc));
}
__device__ __forceinline__ void wg_ss64_01(float* d, uint64_t da, uint64_t db, int sc) {
  asm volatile("{.reg .pred p; setp.ne.b32 p, %34, 0; wgmma.mma_async.sync.aligned.m64n64k16.f32.bf16.bf16 {%0,%1,%2,%3,%4,%5,%6,%7,%8,%9,%10,%11,%12,%13,%14,%15,%16,%17,%18,%19,%20,%21,%22,%23,%24,%25,%26,%27,%28,%29,%30,%31}, %32, %33, p, 1, 1, 0, 1;}"
    : "+f"(d[0]),"+f"(d[1]),"+f"(d[2]),"+f"(d[3]),"+f"(d[4]),"+f"(d[5]),"+f"(d[6]),"+f"(d[7]),"+f"(d[8]),"+f"(d[9]),"+f"(d[10]),"+f"(d[11]),"+f"(d[12]),"+f"(d[13]),"+f"(d[14]),"+f"(d[15]),"+f"(d[16]),"+f"(d[17]),"+f"(d[18]),"+f"(d[19]),"+f"(d[20]),"+f"(d[21]),"+f"(d[22]),"+f"(d[23]),"+f"(d[24]),"+f"(d[25]),"+f"(d[26]),"+f"(d[27]),"+f"(d[28]),"+f"(d[29]),"+f"(d[30]),"+f"(d[31]) : "l"(da),"l"(db),"r"(sc));
}
__device__ __forceinline__ void wg_ss128_11(float* d, uint64_t da, uint64_t db, int sc) {
  asm volatile("{.reg .pred p; setp.ne.b32 p, %66, 0; wgmma.mma_async.sync.aligned.m64n128k16.f32.bf16.bf16 {%0,%1,%2,%3,%4,%5,%6,%7,%8,%9,%10,%11,%12,%13,%14,%15,%16,%17,%18,%19,%20,%21,%22,%23,%24,%25,%26,%27,%28,%29,%30,%31,%32,%33,%34,%35,%36,%37,%38,%39,%40,%41,%42,%43,%44,%45,%46,%47,%48,%49,%50,%51,%52,%53,%54,%55,%56,%57,%58,%59,%60,%61,%62,%63}, %64, %65, p, 1, 1, 1, 1;}"
    : "+f"(d[0]),"+f"(d[1]),"+f"(d[2]),"+f"(d[3]),"+f"(d[4]),"+f"(d[5]),"+f"(d[6]),"+f"(d[7]),"+f"(d[8]),"+f"(d[9]),"+f"(d[10]),"+f"(d[11]),"+f"(d[12]),"+f"(d[13]),"+f"(d[14]),"+f"(d[15]),"+f"(d[16]),"+f"(d[17]),"+f"(d[18]),"+f"(d[19]),"+f"(d[20]),"+f"(d[21]),"+f"(d[22]),"+f"(d[23]),"+f"(d[24]),"+f"(d[25]),"+f"(d[26]),"+f"(d[27]),"+f"(d[28]),"+f"(d[29]),"+f"(d[30]),"+f"(d[31]),"+f"(d[32]),"+f"(d[33]),"+f"(d[34]),"+f"(d[35]),"+f"(d[36]),"+f"(d[37]),"+f"(d[38]),"+f"(d[39]),"+f"(d[40]),"+f"(d[41]),"+f"(d[42]),"+f"(d[43]),"+f"(d[44]),"+f"(d[45]),"+f"(d[46]),"+f"(d[47]),"+f"(d[48]),"+f"(d[49]),"+f"(d[50]),"+f"(d[51]),"+f"(d[52]),"+f"(d[53]),"+f"(d[54]),"+f"(d[55]),"+f"(d[56]),"+f"(d[57]),"+f"(d[58]),"+f"(d[59]),"+f"(d[60]),"+f"(d[61]),"+f"(d[62]),"+f"(d[63]) : "l"(da),"l"(db),"r"(sc));
}
__device__ __forceinline__ void wg_ss128_01(float* d, uint64_t da, uint64_t db, int sc) {
  asm volatile("{.reg .pred p; setp.ne.b32 p, %66, 0; wgmma.mma_async.sync.aligned.m64n128k16.f32.bf16.bf16 {%0,%1,%2,%3,%4,%5,%6,%7,%8,%9,%10,%11,%12,%13,%14,%15,%16,%17,%18,%19,%20,%21,%22,%23,%24,%25,%26,%27,%28,%29,%30,%31,%32,%33,%34,%35,%36,%37,%38,%39,%40,%41,%42,%43,%44,%45,%46,%47,%48,%49,%50,%51,%52,%53,%54,%55,%56,%57,%58,%59,%60,%61,%62,%63}, %64, %65, p, 1, 1, 0, 1;}"
    : "+f"(d[0]),"+f"(d[1]),"+f"(d[2]),"+f"(d[3]),"+f"(d[4]),"+f"(d[5]),"+f"(d[6]),"+f"(d[7]),"+f"(d[8]),"+f"(d[9]),"+f"(d[10]),"+f"(d[11]),"+f"(d[12]),"+f"(d[13]),"+f"(d[14]),"+f"(d[15]),"+f"(d[16]),"+f"(d[17]),"+f"(d[18]),"+f"(d[19]),"+f"(d[20]),"+f"(d[21]),"+f"(d[22]),"+f"(d[23]),"+f"(d[24]),"+f"(d[25]),"+f"(d[26]),"+f"(d[27]),"+f"(d[28]),"+f"(d[29]),"+f"(d[30]),"+f"(d[31]),"+f"(d[32]),"+f"(d[33]),"+f"(d[34]),"+f"(d[35]),"+f"(d[36]),"+f"(d[37]),"+f"(d[38]),"+f"(d[39]),"+f"(d[40]),"+f"(d[41]),"+f"(d[42]),"+f"(d[43]),"+f"(d[44]),"+f"(d[45]),"+f"(d[46]),"+f"(d[47]),"+f"(d[48]),"+f"(d[49]),"+f"(d[50]),"+f"(d[51]),"+f"(d[52]),"+f"(d[53]),"+f"(d[54]),"+f"(d[55]),"+f"(d[56]),"+f"(d[57]),"+f"(d[58]),"+f"(d[59]),"+f"(d[60]),"+f"(d[61]),"+f"(d[62]),"+f"(d[63]) : "l"(da),"l"(db),"r"(sc));
}
__device__ __forceinline__ void wg_ss96_01(float* d, uint64_t da, uint64_t db, int sc) {
  asm volatile("{.reg .pred p; setp.ne.b32 p, %50, 0; wgmma.mma_async.sync.aligned.m64n96k16.f32.bf16.bf16 {%0,%1,%2,%3,%4,%5,%6,%7,%8,%9,%10,%11,%12,%13,%14,%15,%16,%17,%18,%19,%20,%21,%22,%23,%24,%25,%26,%27,%28,%29,%30,%31,%32,%33,%34,%35,%36,%37,%38,%39,%40,%41,%42,%43,%44,%45,%46,%47}, %48, %49, p, 1, 1, 0, 1;}"
    : "+f"(d[0]),"+f"(d[1]),"+f"(d[2]),"+f"(d[3]),"+f"(d[4]),"+f"(d[5]),"+f"(d[6]),"+f"(d[7]),"+f"(d[8]),"+f"(d[9]),"+f"(d[10]),"+f"(d[11]),"+f"(d[12]),"+f"(d[13]),"+f"(d[14]),"+f"(d[15]),"+f"(d[16]),"+f"(d[17]),"+f"(d[18]),"+f"(d[19]),"+f"(d[20]),"+f"(d[21]),"+f"(d[22]),"+f"(d[23]),"+f"(d[24]),"+f"(d[25]),"+f"(d[26]),"+f"(d[27]),"+f"(d[28]),"+f"(d[29]),"+f"(d[30]),"+f"(d[31]),"+f"(d[32]),"+f"(d[33]),"+f"(d[34]),"+f"(d[35]),"+f"(d[36]),"+f"(d[37]),"+f"(d[38]),"+f"(d[39]),"+f"(d[40]),"+f"(d[41]),"+f"(d[42]),"+f"(d[43]),"+f"(d[44]),"+f"(d[45]),"+f"(d[46]),"+f"(d[47]) : "l"(da),"l"(db),"r"(sc));
}
__device__ __forceinline__ void wg_rs64_1(float* d, const uint32_t* a, uint64_t db, int sc) {
  asm volatile("{.reg .pred p; setp.ne.b32 p, %37, 0; wgmma.mma_async.sync.aligned.m64n64k16.f32.bf16.bf16 {%0,%1,%2,%3,%4,%5,%6,%7,%8,%9,%10,%11,%12,%13,%14,%15,%16,%17,%18,%19,%20,%21,%22,%23,%24,%25,%26,%27,%28,%29,%30,%31}, {%32,%33,%34,%35}, %36, p, 1, 1, 1;}"
    : "+f"(d[0]),"+f"(d[1]),"+f"(d[2]),"+f"(d[3]),"+f"(d[4]),"+f"(d[5]),"+f"(d[6]),"+f"(d[7]),"+f"(d[8]),"+f"(d[9]),"+f"(d[10]),"+f"(d[11]),"+f"(d[12]),"+f"(d[13]),"+f"(d[14]),"+f"(d[15]),"+f"(d[16]),"+f"(d[17]),"+f"(d[18]),"+f"(d[19]),"+f"(d[20]),"+f"(d[21]),"+f"(d[22]),"+f"(d[23]),"+f"(d[24]),"+f"(d[25]),"+f"(d[26]),"+f"(d[27]),"+f"(d[28]),"+f"(d[29]),"+f"(d[30]),"+f"(d[31]) : "r"(a[0]),"r"(a[1]),"r"(a[2]),"r"(a[3]),"l"(db),"r"(sc));
}
__device__ __forceinline__ void wg_rs96_1(float* d, const uint32_t* a, uint64_t db, int sc) {
  asm volatile("{.reg .pred p; setp.ne.b32 p, %53, 0; wgmma.mma_async.sync.aligned.m64n96k16.f32.bf16.bf16 {%0,%1,%2,%3,%4,%5,%6,%7,%8,%9,%10,%11,%12,%13,%14,%15,%16,%17,%18,%19,%20,%21,%22,%23,%24,%25,%26,%27,%28,%29,%30,%31,%32,%33,%34,%35,%36,%37,%38,%39,%40,%41,%42,%43,%44,%45,%46,%47}, {%48,%49,%50,%51}, %52, p, 1, 1, 1;}"
    : "+f"(d[0]),"+f"(d[1]),"+f"(d[2]),"+f"(d[3]),"+f"(d[4]),"+f"(d[5]),"+f"(d[6]),"+f"(d[7]),"+f"(d[8]),"+f"(d[9]),"+f"(d[10]),"+f"(d[11]),"+f"(d[12]),"+f"(d[13]),"+f"(d[14]),"+f"(d[15]),"+f"(d[16]),"+f"(d[17]),"+f"(d[18]),"+f"(d[19]),"+f"(d[20]),"+f"(d[21]),"+f"(d[22]),"+f"(d[23]),"+f"(d[24]),"+f"(d[25]),"+f"(d[26]),"+f"(d[27]),"+f"(d[28]),"+f"(d[29]),"+f"(d[30]),"+f"(d[31]),"+f"(d[32]),"+f"(d[33]),"+f"(d[34]),"+f"(d[35]),"+f"(d[36]),"+f"(d[37]),"+f"(d[38]),"+f"(d[39]),"+f"(d[40]),"+f"(d[41]),"+f"(d[42]),"+f"(d[43]),"+f"(d[44]),"+f"(d[45]),"+f"(d[46]),"+f"(d[47]) : "r"(a[0]),"r"(a[1]),"r"(a[2]),"r"(a[3]),"l"(db),"r"(sc));
}
__device__ __forceinline__ void wg_ss160_01(float* d, uint64_t da, uint64_t db, int sc) {
  asm volatile("{.reg .pred p; setp.ne.b32 p, %82, 0; wgmma.mma_async.sync.aligned.m64n160k16.f32.bf16.bf16 {%0,%1,%2,%3,%4,%5,%6,%7,%8,%9,%10,%11,%12,%13,%14,%15,%16,%17,%18,%19,%20,%21,%22,%23,%24,%25,%26,%27,%28,%29,%30,%31,%32,%33,%34,%35,%36,%37,%38,%39,%40,%41,%42,%43,%44,%45,%46,%47,%48,%49,%50,%51,%52,%53,%54,%55,%56,%57,%58,%59,%60,%61,%62,%63,%64,%65,%66,%67,%68,%69,%70,%71,%72,%73,%74,%75,%76,%77,%78,%79}, %80, %81, p, 1, 1, 0, 1;}"
    : "+f"(d[0]),"+f"(d[1]),"+f"(d[2]),"+f"(d[3]),"+f"(d[4]),"+f"(d[5]),"+f"(d[6]),"+f"(d[7]),"+f"(d[8]),"+f"(d[9]),"+f"(d[10]),"+f"(d[11]),"+f"(d[12]),"+f"(d[13]),"+f"(d[14]),"+f"(d[15]),"+f"(d[16]),"+f"(d[17]),"+f"(d[18]),"+f"(d[19]),"+f"(d[20]),"+f"(d[21]),"+f"(d[22]),"+f"(d[23]),"+f"(d[24]),"+f"(d[25]),"+f"(d[26]),"+f"(d[27]),"+f"(d[28]),"+f"(d[29]),"+f"(d[30]),"+f"(d[31]),"+f"(d[32]),"+f"(d[33]),"+f"(d[34]),"+f"(d[35]),"+f"(d[36]),"+f"(d[37]),"+f"(d[38]),"+f"(d[39]),"+f"(d[40]),"+f"(d[41]),"+f"(d[42]),"+f"(d[43]),"+f"(d[44]),"+f"(d[45]),"+f"(d[46]),"+f"(d[47]),"+f"(d[48]),"+f"(d[49]),"+f"(d[50]),"+f"(d[51]),"+f"(d[52]),"+f"(d[53]),"+f"(d[54]),"+f"(d[55]),"+f"(d[56]),"+f"(d[57]),"+f"(d[58]),"+f"(d[59]),"+f"(d[60]),"+f"(d[61]),"+f"(d[62]),"+f"(d[63]),"+f"(d[64]),"+f"(d[65]),"+f"(d[66]),"+f"(d[67]),"+f"(d[68]),"+f"(d[69]),"+f"(d[70]),"+f"(d[71]),"+f"(d[72]),"+f"(d[73]),"+f"(d[74]),"+f"(d[75]),"+f"(d[76]),"+f"(d[77]),"+f"(d[78]),"+f"(d[79]) : "l"(da),"l"(db),"r"(sc));
}
__device__ __forceinline__ void wg_rs160_1(float* d, const uint32_t* a, uint64_t db, int sc) {
  asm volatile("{.reg .pred p; setp.ne.b32 p, %85, 0; wgmma.mma_async.sync.aligned.m64n160k16.f32.bf16.bf16 {%0,%1,%2,%3,%4,%5,%6,%7,%8,%9,%10,%11,%12,%13,%14,%15,%16,%17,%18,%19,%20,%21,%22,%23,%24,%25,%26,%27,%28,%29,%30,%31,%32,%33,%34,%35,%36,%37,%38,%39,%40,%41,%42,%43,%44,%45,%46,%47,%48,%49,%50,%51,%52,%53,%54,%55,%56,%57,%58,%59,%60,%61,%62,%63,%64,%65,%66,%67,%68,%69,%70,%71,%72,%73,%74,%75,%76,%77,%78,%79}, {%80,%81,%82,%83}, %84, p, 1, 1, 1;}"
    : "+f"(d[0]),"+f"(d[1]),"+f"(d[2]),"+f"(d[3]),"+f"(d[4]),"+f"(d[5]),"+f"(d[6]),"+f"(d[7]),"+f"(d[8]),"+f"(d[9]),"+f"(d[10]),"+f"(d[11]),"+f"(d[12]),"+f"(d[13]),"+f"(d[14]),"+f"(d[15]),"+f"(d[16]),"+f"(d[17]),"+f"(d[18]),"+f"(d[19]),"+f"(d[20]),"+f"(d[21]),"+f"(d[22]),"+f"(d[23]),"+f"(d[24]),"+f"(d[25]),"+f"(d[26]),"+f"(d[27]),"+f"(d[28]),"+f"(d[29]),"+f"(d[30]),"+f"(d[31]),"+f"(d[32]),"+f"(d[33]),"+f"(d[34]),"+f"(d[35]),"+f"(d[36]),"+f"(d[37]),"+f"(d[38]),"+f"(d[39]),"+f"(d[40]),"+f"(d[41]),"+f"(d[42]),"+f"(d[43]),"+f"(d[44]),"+f"(d[45]),"+f"(d[46]),"+f"(d[47]),"+f"(d[48]),"+f"(d[49]),"+f"(d[50]),"+f"(d[51]),"+f"(d[52]),"+f"(d[53]),"+f"(d[54]),"+f"(d[55]),"+f"(d[56]),"+f"(d[57]),"+f"(d[58]),"+f"(d[59]),"+f"(d[60]),"+f"(d[61]),"+f"(d[62]),"+f"(d[63]),"+f"(d[64]),"+f"(d[65]),"+f"(d[66]),"+f"(d[67]),"+f"(d[68]),"+f"(d[69]),"+f"(d[70]),"+f"(d[71]),"+f"(d[72]),"+f"(d[73]),"+f"(d[74]),"+f"(d[75]),"+f"(d[76]),"+f"(d[77]),"+f"(d[78]),"+f"(d[79]) : "r"(a[0]),"r"(a[1]),"r"(a[2]),"r"(a[3]),"l"(db),"r"(sc));
}
__device__ __forceinline__ void wg_ss8_10(float* d, uint64_t da, uint64_t db, int sc) {
  asm volatile("{.reg .pred p; setp.ne.b32 p, %6, 0; wgmma.mma_async.sync.aligned.m64n8k16.f32.bf16.bf16 {%0,%1,%2,%3}, %4, %5, p, 1, 1, 1, 0;}"
    : "+f"(d[0]),"+f"(d[1]),"+f"(d[2]),"+f"(d[3]) : "l"(da),"l"(db),"r"(sc));
}
__device__ __forceinline__ void wg_ss8_if(float* d, uint64_t da, uint64_t db, int sc, int skip) {
  asm volatile("{.reg .pred p, q; setp.ne.b32 p, %6, 0; setp.eq.b32 q, %7, 0; @q wgmma.mma_async.sync.aligned.m64n8k16.f32.bf16.bf16 {%0,%1,%2,%3}, %4, %5, p, 1, 1, 1, 0;}"
    : "+f"(d[0]),"+f"(d[1]),"+f"(d[2]),"+f"(d[3]) : "l"(da),"l"(db),"r"(sc),"r"(skip));
}

constexpr uint32_t DB = 1024;
constexpr int UNIT = 8192, WSLOT = 16384, W2TILE = 24576, OFF_R = 12 * UNIT;
constexpr int OFF_PB = 26 * UNIT;
constexpr int OFF_CV = OFF_PB + 16384, OFF_ST = OFF_CV + 768, OFF_TS = OFF_ST + 256, OFF_MODR = OFF_TS + 512, OFF_ROLE = OFF_MODR + 80, OFF_BAR = OFF_ROLE + 16, SMEM_BYTES = OFF_BAR + 1368;
constexpr int OFF_BX = OFF_PB, OFF_AX = OFF_BX + 12288, OFF_RT = OFF_AX + 2048, OFF_GB = OFF_RT + 512, OFF_CO = OFF_CV;
constexpr int OFF_UV = 4 * UNIT, OFF_SX = 24 * UNIT, OFF_XCH = 12 * UNIT;
constexpr int OFF_Q = 99328, KV_V = 4096, KV_H = 8192, F_E = 128, F_O = 4288, OFF_WM = 20 * UNIT, OFF_TAP = 12672, OFF_MR = 25 * UNIT;
constexpr uint64_t pk5(int a, int b, int c, int d, int e) { return (uint64_t)(a / 128) | (uint64_t)(b / 128) << 12 | (uint64_t)(c / 128) << 24 | (uint64_t)(d / 128) << 36 | (uint64_t)(e / 128) << 48; }
constexpr uint64_t T_KV = pk5(119808, 16384, 130048, 65536, 49152), T_F = pk5(140288, 90368, 148736, 81920, OFF_PB), T_X = pk5(0, 4224, 8448, 0, 4224),
                   T_P = pk5(32768, 16384, 65536, 81920, OFF_PB);
__host__ __device__ __forceinline__ uint32_t tab(uint64_t t, int c) { return ((uint32_t)(t >> (12 * c)) & 0xFFF) << 7; }
enum { B_KV = 0, B_FRAW = 5, B_Q = 10, B_WM = 15, B_XR = 17, B_MR = B_XR + 5, B_QTOK, B_ST1, B_MODR, B_ROLE = B_MODR + 5, B_FL = 32, B_PFULL = B_FL + 5, B_PEMPTY = B_PFULL + 5, B_FRDY = B_PEMPTY + 5,
       B_G = B_FRDY + 5, B_EXT = B_G + 2, B_QTD, B_ED, B_S2 = B_ED + 2, B_GB, B_FULL = 60, B_RETRY = B_FULL + 43, B_XFREE = B_RETRY + 8, B_BX, B_UVB, B_CO, B_SX, B_EMPTY = 121, B_SC = 164, B_STD = B_SC + 5, B_LAG };
static_assert(B_ROLE < B_FL && B_GB < B_FULL && B_SX + 5 <= B_EMPTY - 1 && OFF_MR == OFF_SX + 8192 && SMEM_BYTES <= 232448, "barrier groups");
#define BAR(i) (base + OFF_BAR + 8 * (i))

struct Maps { CUtensorMap km, v, q, fm, wmp, kh, tap, wm, w1a, w3a, xs, w1u, w3u, w1b, w3b, x1s, x1b, w2a, w2b, outa, outb; };
struct Ptrs { const bf16 *c, *ssmd; Scratch* g; uint64_t prog[2]; uint32_t gate[5]; int ulo; uint32_t mq, xh, xdep, hstart, hpause, hl[8], uvd, mpos, wt0, wpace; float one; uint32_t wdep[30], adep[14]; uint2 w2t[12]; int hid[3][9]; };

#define REGION_IDS int tid, lane, bid; \
  asm volatile("mov.u32 %0, %%tid.x;" : "=r"(tid)); asm volatile("mov.u32 %0, %%laneid;" : "=r"(lane)); asm volatile("mov.u32 %0, %%ctaid.x;" : "=r"(bid)); \
  const int i0 = tid & 127; (void)i0; (void)lane; (void)bid

#define ffn_role(h, j, r) do { \
  mbar_wait(BAR(B_ROLE)); \
  r = __shfl_sync(~0u, lds32(base + OFF_ROLE), 0); \
  asm volatile("mov.u32 %0, %%ctaid.x;" : "=r"(h)); \
  h &= 1; j = r >> 4; r &= 15; } while (0)
__device__ __forceinline__ void rank_pair(Scratch* G, uint32_t base, uint32_t epoch, bool put) {
  REGION_IDS;
  uint32_t t;
  asm volatile("mov.u32 %0, %%smid;" : "=r"(t));
  t >>= 1;
  const uint32_t q = (t - 32) * 37 >> 8, g = t < 32 ? t & 7 : t < 60 ? t - 31 - 7 * q : t < 62 ? t - 54 : 0;
  const uint32_t key = epoch << 20 | (g & 3) << 18 | (g & 4) << 15 | (t & 127) << 6 | bid >> 1;
  if (put) {
    if (lane == (bid & 1) * 99) publish(&G->key[bid >> 1], key);
    return;
  }
  uint2 x;
  int it = 0;
#pragma unroll 1
  do x = ld_relaxed64(&G->key[2 * lane]); while (__any_sync(~0u, ((x.x ^ key) | (x.y ^ key)) >> 20) && ++it < SPIN_LIMIT);
  sts32(base + OFF_ROLE, __popc(__ballot_sync(~0u, x.x < key)) + __popc(__ballot_sync(~0u, x.y < key)));
  arrive1(BAR(B_ROLE));
}
__device__ __forceinline__ int mod_ch(int p) { return p < 40 ? (p >> 3) * 128 + (p & 1) * 64 : 64 * (p < 50 ? p - 40 : p - 50); }
__device__ __forceinline__ int mod_col(int p) { return mod_ch(p) + 640 * (p < 40 ? 0x4210 >> (2 * (p & 6)) & 7 : p < 50 ? 3 : 5); }
__device__ __forceinline__ uint32_t mod_sum(uint2 v) { return pack_bf16(0.f, __uint_as_float(v.x) + __uint_as_float(v.y)); }
#define UVS 5
#define XP 2
#define GA 3
#define GB 1
#define HL 0
#define EH 0
#define MG 4
#define SG 0x88
#define LAG2 38
#define NP 8
__device__ __forceinline__ int nib(uint32_t t, int i) { return (t >> (4 * i)) & 15; }
__device__ __forceinline__ int w_block(int up, int m) { return m < 2 ? 2 * up + m : 4 + up; }
__host__ __device__ constexpr int w2_at(int v) { return UNIT * (v == 1 ? 0 : 0x0811030C18ull >> (v - (v > 1)) % 5 * 8 & 255); }
__host__ __device__ constexpr int hid_at(int m, int g) { return UNIT * ((g ? 0x0200150710ull : 0x010B14060Full) >> m % 5 * 8 & 255); }
__host__ __device__ constexpr int x1_at(int k) { return k < 4 ? 22 * UNIT + 4096 * k : OFF_BX + UNIT; }
__host__ __device__ constexpr uint32_t w2_desc(int v) { return (DB + w2_at(v)) >> 4 | UNIT << 12; }
__host__ __device__ constexpr int a_at(int n) { return WSLOT * (0x54323251041032ull >> 4 * n & 15); }
__host__ __device__ constexpr int second(int v) { return 0xDCBA657498ull >> 4 * v & 15; }

#define ORDER "k1v1f0q0q1q2q3q4k2v2f1k3v3f2k4v4f3w0f4"
constexpr int NL = sizeof(ORDER) / 2, NG = 2, TA = 16, M8 = 3 << TA / 8;
__host__ __device__ constexpr int load_bar(int e) { return e < 0 ? B_KV : ORDER[2 * e + 1] - '0' + (ORDER[2 * e] == 'q' ? B_Q : ORDER[2 * e] == 'f' ? B_FRAW : ORDER[2 * e] == 'w' ? B_WM : B_KV); }
template <int E> __device__ __forceinline__ void loads(const Ptrs& P, const Maps& maps, uint32_t base) {
  if constexpr (E < NL) {
    constexpr int r = ORDER[2 * E + 1] - '0';
    constexpr char x = ORDER[2 * E];
    const int c0 = 128 * r + 64 * (blockIdx.x & 1), c1 = 2 * (blockIdx.x & 126);
    const uint32_t g = P.gate[E / 4] >> 8 * (E & 3) & 255;
    if (E >= NG) mbar_wait(BAR(opaque(g >> 1)), g & 1);
    if (elect()) {
      if (x == 'k') { tma3d(base + tab(T_KV, r), &maps.km, c0, c1, 0, BAR(B_KV + r)); tma3d(base + tab(T_KV, r) + KV_H, &maps.kh, c0, c1 - 1, 5, BAR(B_KV + r)); }
      if (x == 'v') tma3d(base + tab(T_KV, r) + KV_V, &maps.v, c0, c1, 0, BAR(B_KV + r));
      if (x == 'q') tma3d(base + OFF_Q + 4096 * r, &maps.q, c0, c1, 0, BAR(B_Q + r));
      if (x == 'f') tma3d(base + tab(T_F, r) + F_E, &maps.fm, 0, 0, 128 * r + blockIdx.x, BAR(B_FRAW + r));
      if (x == 'w') tma3d(base + OFF_WM, &maps.wmp, mod_col(TA + (blockIdx.x >> 3)), 80 * (blockIdx.x & 7), 0, BAR(B_WM));
    }
    loads<E + 1>(P, maps, base);
  }
}

template <int U> __device__ __forceinline__ void cstep(float* acc, const uint32_t* A, uint64_t db) {
  const uint32_t* a = A + 4 * U;
  const uint64_t d = db + 16 * U;
  if (U == 4) { wg_rs64_0(acc + 96, A, db + 192, 0); wg_rs48_0(acc + 96, A + 4, db + 208, 1); wg_rs32_0(acc + 96, A + 8, db + 224, 1); wg_rs16_0(acc + 96, A + 12, db + 240, 1); }
  if (U <= 4) wg_rs192_0(acc, a, d, U);
  if (U == 5) wg_rs176_0(acc, a, d, 1);
  if (U == 6) wg_rs160_0(acc, a, d, 1);
  if (U == 7) wg_rs144_0(acc, a, d, 1);
  if (U == 8) wg_rs128_0(acc, a, d, 1);
  if (U == 9) wg_rs112_0(acc, a, d, 1);
  if (U == 10) wg_rs96_0(acc, a, d, 1);
  if (U == 11) wg_rs80_0(acc, a, d, 1);
  if (U == 12) wg_rs64_0(acc, a, d, 1);
  if (U == 13) wg_rs48_0(acc, a, d, 1);
  if (U == 14) wg_rs32_0(acc, a, d, 1);
  if (U == 15) wg_rs16_0(acc, a, d, 1);
}
template <int U0, int U1> __device__ __forceinline__ void csteps(float* acc, const uint32_t* A, uint64_t db) {
  cstep<U0>(acc, A, db);
  if constexpr (U0 > U1) csteps<U0 - 1, U1>(acc, A, db);
}
template <int U0, int U1> __device__ __forceinline__ void cload(uint32_t* A, uint32_t fa) {
  asm volatile("{ld.shared.b32 %0, [%4+%5]; ld.shared.b32 %1, [%4+%5+128]; ld.shared.b32 %2, [%4+%5+16]; ld.shared.b32 %3, [%4+%5+144];}"
               : "=r"(A[4 * U0]), "=r"(A[4 * U0 + 1]), "=r"(A[4 * U0 + 2]), "=r"(A[4 * U0 + 3]) : "r"(fa), "n"(256 * U0) : "memory");
  if constexpr (U0 > U1) cload<U0 - 1, U1>(A, fa);
}

template <int NK> __device__ __forceinline__ void mod_gemv(Scratch* G, uint32_t wm, int p, int part, int w, int lane, uint32_t par) {
  float d[4] = {};
  fence_regs(d);
  wg_fence();
#pragma unroll 1
  for (int k = 0; k < NK; k += 5) {
#pragma unroll
    for (int i = 0; i < 5; i++) wg_ss8_10(d, mkdesc(DB + wm + 2048 * (k + i), 16, 1024, 1), mkdesc(DB + OFF_CV + 32 * (k + i), 16, 128, 0), 1);
  }
  wg_commit();
  const int ch = mod_ch(p) + 16 * w + (lane >> 2);
  uint32_t* dst = (p < 40 ? &G->modc[ch & 127][p >> 3][4 * (p & 6)] : (uint32_t*)&G->modv[p >= 50][ch]) + part;
  wg_wait<0>();
  fence_regs(d);
  if (!(lane & 3)) {
    publish(dst, (__float_as_uint(d[0]) & ~1u) | par);
    publish(dst + (p < 40 ? 1280 : 16), (__float_as_uint(d[2]) & ~1u) | par);
    if (NK == 20 && p < 40 && (p & 6) == 6) {
      dst = (uint32_t*)&G->modv[2][ch] + part;
      publish(dst, (__float_as_uint(d[0]) & ~1u) | par);
      publish(dst + 16, (__float_as_uint(d[2]) & ~1u) | par);
    }
  }
}
__device__ __forceinline__ void mod_fetch(Scratch* G, uint32_t base, uint32_t epoch, uint32_t m8, uint32_t c, uint32_t c1) {
  REGION_IDS;
  const uint32_t* mp = &G->modc[bid][0][lane];
  auto unused = [&]() { return (lane & 6) && !(m8 >> c & 1); };
#pragma unroll 1
  for (int it = 0; c < c1 && it < SPIN_LIMIT; it++) {
    uint32_t m = ld_relaxed32(mp + 32 * c);
    const uint32_t m1 = ld_relaxed32(mp + 32 * min(c + 1, c1 - 1));
#pragma unroll 1
    for (int k = 0; k < 2 && c < c1 && __all_sync(~0u, unused() || !((m ^ epoch) & 1)); k++) {
      float x = unused() ? 0.f : __uint_as_float(m);
      x += __shfl_xor_sync(~0u, x, 1); x += __shfl_xor_sync(~0u, x, 2); x += __shfl_xor_sync(~0u, x, 4);
      const uint32_t y = __byte_perm(badd2(pack_bf16(0.f, x), (lane & 8) * 0x07F00000u), 0, 0x3232), ga = __shfl_sync(~0u, y, 16);
      sts32(base + OFF_MODR + 16 * c + 4 * (lane >> 3), lane < 16 ? bmul2(y, ga) : y);
      arrive1(BAR(B_MODR + c));
      if (lane >= 30 && (m8 >> c & 1)) publish((uint32_t*)&G->modv[2][128 * c + bid] + (lane & 1), ((lane & 1 ? 0 : __float_as_uint(x)) & ~1u) | (epoch & 1));
      m = m1;
      c++;
    }
  }
}
__device__ __forceinline__ void add4(uint4& y, const uint4& z) { y.x = badd2(y.x, z.x); y.y = badd2(y.y, z.y); y.z = badd2(y.z, z.z); y.w = badd2(y.w, z.w); }
template <bool FIRST> __device__ __forceinline__ void e_round(Scratch* G, uint32_t base, uint32_t sa, uint4*& gp, uint4* q, int c, int w, uint32_t tag, uint32_t epoch) {
  constexpr int QO = -D_ * 256;
  mbar_wait(BAR(B_MODR + c));
  const uint4 co = lds128(base + OFF_MODR + 16 * c);
  mbar_wait(BAR(B_PFULL + c));
  const uint32_t pb = sa + tab(T_P, c);
  uint4 l[2][6];
  auto load = [&](int hf, int k) { l[hf][k] = lds128((k < 4 ? pb + 4096 * k : sa + OFF_MR + 4096 * (k - 4)) + 2048 * hf); };
#pragma unroll
  for (int hf = 0; hf < 2; hf++) {
    uint4 &y = l[hf][0], &z = l[hf][4], &m = l[hf][5];
    load(hf, 0);
    if (!FIRST) {
      load(hf, 1);
      add4(y, l[hf][1]);
      load(hf, 2); load(hf, 3);
      add4(l[hf][2], l[hf][3]);
      add4(y, l[hf][2]);
    }
    load(hf, 4); load(hf, 5);
    if (FIRST) {
#pragma unroll 1
      for (int it = 0; __any_sync(~0u, ((z.x >> 15 ^ epoch) | (m.x ^ epoch)) & tag) && it < SPIN_LIMIT; it++) {
        const uint4* sp = (const uint4*)G->st1 + (opaque(sa) - base >> 4) + 128 * hf;
        z = ld_relaxed128(sp);
        m = ld_relaxed128(sp + 256);
        sts128(sa + OFF_MR + 2048 * hf, z.x, z.y, z.z, z.w);
        sts128(sa + OFF_MR + 2048 * hf + 4096, m.x, m.y, m.z, m.w);
      }
      z.x &= 0xFFFF7FFFu;
      sts32(sa + OFF_MR + 2048 * hf, z.x);
    }
#pragma unroll 1
    for (int it = 0; __any_sync(~0u, (q[hf].x ^ epoch) & tag) && it < SPIN_LIMIT; it++) {
      q[hf] = ld_relaxed128(gp + QO + 128 * hf);
    }
    y.x = bfma2(bfma2(bfma2(q[hf].x, z.x, m.x), co.y, co.x), y.x, q[hf].x);
    auto hint = [&]() {
      __syncwarp();
      asm volatile("{.reg .pred p; elect.sync _|p, 0xffffffff; @p red.relaxed.gpu.global.add.u32 [%0], 1; @p mbarrier.arrive.shared::cta.b64 _, [%1];}"
                   ::"l"(G->xsh[c][2 * w + (blockIdx.x >> 6)]), "r"(BAR(B_PEMPTY + c)), "r"(y.x) : "memory");
    };
    if (hf && !EH) hint();
    y.y = bfma2(bfma2(bfma2(q[hf].y, z.y, m.y), co.y, co.x), y.y, q[hf].y);
    y.z = bfma2(bfma2(bfma2(q[hf].z, z.z, m.z), co.y, co.x), y.z, q[hf].z);
    y.w = bfma2(bfma2(bfma2(q[hf].w, z.w, m.w), co.y, co.x), y.w, q[hf].w);
    st_relaxed128(gp + 128 * hf, set_tag(bmul2(y.x, co.w), tag, epoch), bmul2(y.y, co.w), bmul2(y.z, co.w), bmul2(y.w, co.w));
    if (hf && EH == 1) hint();
    asm volatile("{.reg .pred p; .reg .b32 t; setp.ne.u32 p, %5, 0; max.u32 t, %1, 1; @!p st.relaxed.gpu.global.v4.u32 [%0+%6], {t,%2,%3,%4}; @p st.relaxed.gpu.global.v4.u32 [%0+%7], {t,%2,%3,%4};}"
                 ::"l"(gp + 128 * hf), "r"(y.x), "r"(y.y), "r"(y.z), "r"(y.w), "r"(epoch & 1), "n"(D_ * 4096), "n"(D_ * 8192) : "memory");
    if (hf && EH == 2) hint();
    if (c < 4) q[hf] = ld_relaxed128(gp + QO + 32768 + 128 * hf);
  }
  gp += 32768;
}
__device__ __forceinline__ void q_stats(uint32_t base, int w) {
  REGION_IDS;
  float s0 = 0.f, s1 = 0.f, q0 = 0.f, q1 = 0.f;
  const uint32_t a = OFF_Q + 1024 * w + 128 * (lane & 7) + (((lane >> 3) ^ (lane & 7)) << 4);
  const uint32_t ra = mapa(base + OFF_ST + 128 * (bid & 1) + 64 * (lane & 1) + 16 * w + 8 * (lane >> 2), lane >> 1 & 1), rb = mapa(BAR(B_ST1), lane >> 1 & 1);
  if (w == 3 && elect()) mbar_expect_tx(BAR(B_ST1), 256);
#pragma unroll 1
  for (int k = 0; k < 5; k++) {
    mbar_wait(BAR(B_Q + k));
    const uint32_t o = opaque(base + 4096 * k);
    const uint4 x = lds128(o + a), y = lds128(o + (a ^ 64));
    const uint32_t e[8] = {x.x, x.y, x.z, x.w, y.x, y.y, y.z, y.w};
#pragma unroll
    for (int i = 0; i < 8; i++) { const float lo = bf_lo(e[i]), hi = bf_hi(e[i]); s0 += lo; s1 += hi; q0 = fmaf(lo, lo, q0); q1 = fmaf(hi, hi, q1); }
  }
  s0 += s1; q0 += q1;
  arrive1(BAR(B_STD));
  s0 += __shfl_xor_sync(~0u, s0, 8); q0 += __shfl_xor_sync(~0u, q0, 8);
  s0 += __shfl_xor_sync(~0u, s0, 16); q0 += __shfl_xor_sync(~0u, q0, 16);
  if (lane < 8) asm volatile("st.async.shared::cluster.mbarrier::complete_tx::bytes.v2.b32 [%0], {%1,%2}, [%3];" ::"r"(ra), "r"(__float_as_uint(s0)), "r"(__float_as_uint(q0)), "r"(rb) : "memory");
}
__device__ __forceinline__ void short_conv(Scratch* G, uint32_t base, int s, int w, uint32_t par, uint32_t xh) {
  REGION_IDS;
  const uint32_t a = base + tab(T_KV, s) + 128 * (lane & 3) + ((w ^ (lane & 3)) << 4) + 4 * (lane & 16) + (lane & 12), keep = ~(lane & 1);
  uint4* dst = G->xr + (128 * s + 64 * (bid & 1) + 8 * w + 2 * (lane & 16) + (lane >> 1 & 6)) * 256 + 255 - 4 * (bid >> 1) - (lane & 3);
  mbar_wait(BAR(B_KV));
  mbar_wait(BAR(B_KV + s));
  const uint4 wv = lds128(base + OFF_TAP + 512 * s + 64 * w + 16 * (lane & 16) + 4 * (lane & 12));
  uint32_t kk[11], r[8];
#pragma unroll
  for (int k = 0; k < 11; k++) kk[k] = k < 3 ? lds32((a ^ (64 * (k & 1))) + KV_H + 512 * k) : lds32((a ^ (64 * (~k & 1))) + 512 * (k - 3));
  if (xh == 0 && elect()) red_hint(G->hint[s][4 * (bid & 1) + w]);
#pragma unroll
  for (int k = 0; k < 8; k++) r[k] = lds32((a ^ (64 * (k & 1))) + KV_V + 512 * k);
  arrive1(BAR(B_SC + s));
  const uint32_t w0 = __byte_perm(wv.x, wv.z, 0x5410), w1 = __byte_perm(wv.x, wv.z, 0x7632),
                 w2 = __byte_perm(wv.y, wv.w, 0x5410), w3 = __byte_perm(wv.y, wv.w, 0x7632);
#pragma unroll
  for (int k = 0; k < 8; k++) r[k] = bmul2(bfma2(kk[k + 3], w0, bfma2(kk[k + 2], w1, bfma2(kk[k + 1], w2, bmul2(kk[k], w3)))), r[k]);
  const uint32_t bit = ~par >> 7 & lane & 1;
  if (xh == 1 && elect()) red_hint(G->hint[s][4 * (bid & 1) + w]);
  st_relaxed128(dst, (__byte_perm(r[7], r[6], 0x5410) & keep) | bit, __byte_perm(r[5], r[4], 0x5410), __byte_perm(r[3], r[2], 0x5410), __byte_perm(r[1], r[0], 0x5410));
  st_relaxed128(dst + 256, (__byte_perm(r[7], r[6], 0x7632) & keep) | bit, __byte_perm(r[5], r[4], 0x7632), __byte_perm(r[3], r[2], 0x7632), __byte_perm(r[1], r[0], 0x7632));
  if (xh == 2 && elect()) red_hint(G->hint[s][4 * (bid & 1) + w]);
}
__device__ __forceinline__ void silu_vector(const bf16* c, int n, uint32_t base) {
  REGION_IDS;
  if (tid < n) {
    const uint32_t x = ldg32(c + 2 * tid);
    sts32(base + OFF_CV + 4 * tid, pack_bf16(silu_f(bf_lo(x)), silu_f(bf_hi(x))));
  }
  fence_async_smem();
}

template <int FIRST> __global__ void __cluster_dims__(2, 1, 1) __launch_bounds__(512, 1) k_fused(const __grid_constant__ Ptrs P, const __grid_constant__ Maps maps) {
  Scratch* const G = P.g;
  extern __shared__ __align__(1024) uint8_t smem_raw[];
  const uint32_t t_start = clock();
  const uint32_t base = __shfl_sync(~0u, smem_u32(smem_raw), 0);
  if (threadIdx.x == 416 && blockIdx.x + FIRST < 128) {
    const int c0 = 64 * (blockIdx.x & 1), c1 = 2 * (blockIdx.x & 126);
    mbar_init<1>(BAR(B_KV), 1);
    mbar_expect_tx(BAR(B_KV), 12288);
    tma3d(base + tab(T_KV, 0), &maps.km, c0, c1, 0, BAR(B_KV));
    tma3d(base + tab(T_KV, 0) + KV_V, &maps.v, c0, c1, 0, BAR(B_KV));
    tma3d(base + tab(T_KV, 0) + KV_H, &maps.kh, c0, c1 - 1, 5, BAR(B_KV));
    tma3d(base + OFF_TAP, &maps.tap, 0, blockIdx.x & 1, 0, BAR(B_KV));
  }
  if ((base & 0xFFFFFFu) != DB) __trap();
  const int wid = __shfl_sync(~0u, threadIdx.x >> 5, 0), wg = wid >> 2, w = wid & 3;
  if (blockIdx.x + FIRST >= 128) {
    REGION_IDS;
    auto unit = [&](int n) { return 4 * (P.hl[n >> 2] >> 8 * (n & 3) & 255) + (bid & 3); };
    auto fetch = [&](int n, int b) {
      if (unit(n) < 120 && elect()) {
        mbar_expect_tx(BAR(n), 40960);
#pragma unroll 1
        for (int k = 0; k < 5; k++) tma3d(base + 40960 * b + 8192 * k, &maps.wm, mod_col(unit(n) >> 1), 320 * (bid & 1) + 64 * k, 0, BAR(n));
      }
    };
    if (wid == 0) {
      mbar_init<4>(BAR(0), 1);
#pragma unroll 1
      for (int n = 0; n < 4; n++) { wait_clock(t_start + (P.hstart & 0xFFFF) + n * (P.hstart >> 16)); fetch(n, n); }
      mbar_init<28>(BAR(4), 1);
    }
    const uint32_t par = ~ld_relaxed32(G->hint[7][0]) >> 7 & 1;
    silu_vector(P.c + 320 * (bid & 1), 160, base);
    __syncthreads();
#pragma unroll 1
    for (int n = wg; unit(n) < 120; n += 4) {
      mbar_wait(BAR(n));
      mod_gemv<20>(G, 40960 * (n % 5), unit(n) >> 1, bid & 1, w, lane, par);
      named_bar(1 + wg, 128);
      if (w == 0) {
        wait_clock(t_start + P.hpause);
        if (n == 0) fetch(4, 4);
        fetch(n + 5, n % 5);
      }
    }
    return;
  }
  mbar_init<3>(BAR(wid < 15 ? 4 * wid + 1 : B_SC + 1), wid < 8 ? 1 : 4);
  mbar_init<1>(BAR(!wid ? B_SC + 4 : wid < 15 ? 4 * wid : B_SC), wid && wid < 8 ? 1 : 4);
  if (wid == 0) mbar_init<2>(BAR(B_SC + 5), 4);
  asm volatile("fence.mbarrier_init.release.cluster; bar.sync 0, 512;" ::: "memory");
  asm volatile("barrier.cluster.arrive.relaxed.aligned;" ::: "memory");
#define LAUNCHES const uint32_t launches = ld_relaxed32(G->hint[7][blockIdx.x >> 4])
#define EPOCH ((__shfl_sync(~0u, launches, 0) >> 7) + 1)
  if (wg < 2) {
    asm volatile("setmaxnreg.inc.sync.aligned.u32 224;");
    LAUNCHES;
    uint32_t par = launches;
    {
      float acc[128];
      uint32_t A[64];
#pragma unroll
      for (int i = 0; i < 64; i++) asm volatile("" : "=r"(A[i]));
      int c = wg;
#pragma unroll 1
      for (uint64_t prog = P.prog[wg]; prog; prog >>= 8) {
        REGION_IDS;
        const int s = prog & 7;
        if (s < 5) short_conv(G, base, s, w, par, P.xh);
        if (prog == P.prog[wg]) cluster_wait();
        if (prog & 16) {
          mbar_wait(BAR(B_QTD));
          mbar_wait(BAR(B_WM));
          mod_gemv<5>(G, OFF_WM, TA + (bid >> 3), bid & 7, w, lane, ~par >> 7 & 1);
          arrive1(BAR(B_G));
        }
        if (prog & 8) q_stats(base, w);
        if (prog & 32) {
          const int L = 16 * w + (lane >> 2) + 2 * (lane & 3) - 7;
          const uint32_t fo = base + ((L & 1) ? F_O + 2 * (L + 1) : F_E + 2 * L);
          mbar_wait(BAR(B_FRDY + c));
          cload<0, 0>(A, fo + tab(T_F, c));
          cload<15, 1>(A, fo + tab(T_F, c));
          arrive1(BAR(B_FL + c));
        }
        if (!(prog & 64)) continue;
        uint32_t xo;
#pragma unroll 1
        for (int it = 0; it < SPIN_LIMIT; it++) {
          xo = tab(T_X, opaque(c));
          mbar_wait(BAR(B_XR + c), it & 1);
          const uint32_t tag = lds32(base + xo + 32 * i0);
          wg_fence();
          csteps<0, 0>(acc, A, mkdesc(DB + xo, 16, 128, 0));
          csteps<15, 6>(acc, A, mkdesc(DB + xo, 16, 128, 0));
          wg_commit();
          if (bar_all(1 + wg, (tag ^ par >> 7) & 1)) break;
          wg_wait<0>();
          if (w == 0 && elect()) { mbar_expect_tx(BAR(B_XR + c), 4096); bulk_load(base + xo, G->xr + (128 * c + bid) * 256, 4096, BAR(B_XR + c)); }
        }
        wg_fence();
        csteps<5, 1>(acc, A, mkdesc(DB + tab(T_X, opaque(c)), 16, 128, 0));
        wg_commit();
        mbar_wait(BAR(B_SC + (c == 2 ? 3 : c)));
        wg_wait<0>();
        fence_regs(acc);
        const uint32_t pb = base + tab(T_P, c) + 4096 * w;
#pragma unroll
        for (int k = 0; k < 8; k++) {
          uint32_t p[4];
#pragma unroll
          for (int e = 0; e < 4; e++) { const int i = 4 * k + e; p[e] = i < 31 ? pack_bf16(acc[4 * i] + acc[4 * i + 6], acc[4 * i + 1] + acc[4 * i + 7]) : pack_bf16(acc[124], acc[125]); }
          if (k == 0 && (lane & 3) < w) p[0] = 0;
          stmatrix_x4_t(k == 0 ? pb + 16 * ((255 - lane + 2 * w) & 255) : pb + 16 * (255 - lane + 2 * w) - 512 * k, p[0], p[1], p[2], p[3]);
        }
        arrive1(BAR(B_PFULL + c));
        c += 2;
      }
    }
    par = ~par >> 7 & 1;
    const uint32_t ao = ((blockIdx.x ^ wg) & 1) * UNIT;
    uint32_t ck;
    { REGION_IDS; ck = base + ao + lane * 128 + (((2 * w) ^ (lane & 7)) << 4); }
    const uint32_t abd = DB + ao;
    auto tags = [&](int as, bool first) { return (lds32(ck + as) ^ par) | (lds32(ck + as + (first ? 4096 : 256)) ^ par); };
    int role;
    { int h, j, r; ffn_role(h, j, r); role = (2 * r + (h ^ wg)) * 8 + 4 * h + j; }
    auto a_tile = [&](int as, int n, bool first) {
#pragma unroll 1
      for (int it = 0; __any_sync(~0u, tags(as, first) & 1) && it < SPIN_LIMIT; it++) {
        if (elect()) {
          mbar_expect_tx(BAR(B_RETRY + wid), UNIT);
          if (first) tma2d(base + ao + as, &maps.xs, 8 * role & ~63, 64 * n, BAR(B_RETRY + wid));
          else bulk_load(base + as, G->hh + ((role & ~3) + ((role + n) & 3)) * 1536 + (n >> 2) * 512, UNIT, BAR(B_RETRY + wid));
        }
        mbar_wait(BAR(B_RETRY + wid), par >> 1);
        par ^= 2;
      }
    };
    float acc[128], acb[64];
    int ws = 0;
    float d[8];
    uint32_t *ud0, *ud1;
    unsigned* uh;
    {
      REGION_IDS;
      const int r = role >> 4, row = (r & 14) + (lane >> 2 & 1);
      ud0 = &G->uv[role & 7][32 * row + 4 * ((2 * w ^ row) & 7) + (lane & 3)];
      ud1 = ud0 + 512 * w_block(r & 1, 2);
      ud0 += 512 * w_block(r & 1, wg);
      uh = G->hint[8][role & 7];
      asm volatile("" : "+l"(ud0), "+l"(ud1), "+l"(uh));
    }
    auto step = [&](int n, int uv) {
      const int as = a_at(n);
      const uint64_t da = mkdesc(abd + as, 16, 1024, 1), db = mkdesc(DB + OFF_R + ws, 4096, 1024, 1);
      mbar_wait(BAR(B_FULL + 2 * n));
      a_tile(as, n, true);
      if (uv == 1) { mbar_wait(BAR(B_UVB)); mbar_wait(BAR(B_CO)); }
      wg_fence();
#pragma unroll
      for (int k = 0; k < 4; k++) {
        wg_ss64_11(acc + 96, da + 128 * k, db + 768 + 128 * (k & 1) + 1024 * (k >> 1), k ? 1 : n);
        if (k == GA - 1) { wg_commit(); wg_wait<1>(); if (elect()) mbar_arrive(BAR(B_EMPTY + 2 * n - 1)); if (uv == 2) fence_regs(d); }
      }
      if (uv == 1) {
#pragma unroll
        for (int k = 0; k < 5; k++) {
          wg_ss8_10(d, mkdesc(DB + OFF_UV + 2048 * wg + 6144 * k, 16, 1024, 1), mkdesc(DB + OFF_CO + 64 * k, 32, 128, 0), k);
        }
        if (!wg) {
#pragma unroll
          for (int k = 0; k < 5; k++) wg_ss8_10(d + 4, mkdesc(DB + OFF_UV + 4096 + 6144 * k, 16, 1024, 1), mkdesc(DB + OFF_CO + 64 * k, 32, 128, 0), k);
        }
      }
#pragma unroll
      for (int k = 0; k < 4; k++) wg_ss192_11(acc, da + 128 * k, db + 128 * (k & 1) + 1024 * (k >> 1), k ? 1 : n);
      wg_commit();
      ws = ws == 4 * WSLOT ? 0 : ws + 2 * WSLOT;
      if (uv == 2) {
        split(P.ulo, 30);
        REGION_IDS;
        const uint32_t tag = !(lane & 3);
        if (elect()) red_hint(uh);
        uint32_t x[4];
#pragma unroll
        for (int k = 0; k < 4; k++) asm volatile("movmatrix.sync.aligned.m8n8.trans.b16 %0, %1;" : "=r"(x[k]) : "r"(pack_bf16(d[2 * k], d[2 * k + 1])));
        const uint32_t y1 = __shfl_up_sync(~0u, x[1], 8), y3 = __shfl_up_sync(~0u, x[3], 8);
        if (lane < 16) {
          st_relaxed32((uint32_t*)((uint64_t)ud0 ^ 2 * (lane & 8)), set_tag(lane < 8 ? x[0] : y1, tag, par));
          if (!wg) st_relaxed32((uint32_t*)((uint64_t)ud1 ^ 2 * (lane & 8)), set_tag(lane < 8 ? x[2] : y3, tag, par));
        }
      }
    };
#pragma unroll 1
    for (int n = 0; n < UVS; n++) step(n, 0);
    step(UVS, 1);
    step(UVS + 1, 2);
#pragma unroll 1
    for (int n = UVS + 2; n < 10; n++) step(n, 0);
    float o[80];
    uint32_t fr[3][16], bo;
    {
      REGION_IDS;
      float r0, r1, s0, s1;
      const int id = role, j = role;
      uint4* const hdst = G->hh + id * 1536 + 128 * w + (lane ^ lane >> 3);
      const uint32_t keep = ~(~lane & 1), bit = par & ~keep;
      bo = 1024 + ((j & 1) << 23);
      auto own = [&](int i) { wg_rs160_1(o, fr[i >> 2] + 4 * (i & 3), mkdesc(DB + w2_at(i / 4) + (i & 3) * 2048, UNIT, bo, 1), i); };
      auto hint = [&](int v) { asm volatile("{.reg .pred p; setp.eq.u32 p, %1, 0; @p red.relaxed.gpu.global.add.u32 [%0], 1;}" ::"l"(&G->hhf[id * 8 + v]), "r"(lane) : "memory"); };
      auto put = [&](int v, int k) {
        uint32_t* x = fr[v] + 2 * k;
        const uint32_t t0 = (x[k / 2] & keep) | bit, t1 = (x[5 + k / 2] & keep) | bit;
        x[k / 2] = t0; x[5 + k / 2] = t1;
        st_relaxed128(hdst + 512 * v + 8 * k, x[0], x[2], x[4], x[6]);
        st_relaxed128(hdst + 512 * v + 8 * k + 64, x[1], x[3], x[5], x[7]);
      };
      auto move = [&](uint32_t* x, int n) {
#pragma unroll
        for (int k = 0; k < n; k++) asm volatile("mul.rn.f32 %0, %0, %1;" : "+r"(x[k]) : "f"(P.one));
      };
      auto act = [&](int i) {
        const int v = i >> 3, k = 7 - (i & 7);
        const float *g = v < 2 ? acc + 32 * v + 4 * k : acb + 4 * k, *up = g + (v < 2 ? 64 : 32);
        fr[v][2 * k] = pack_bf16(silu2(g[0], r0, s0) * up[0], silu2(g[1], r0, s0) * up[1]);
        fr[v][2 * k + 1] = pack_bf16(silu2(g[2], r1, s1) * up[2], silu2(g[3], r1, s1) * up[3]);
        if (!(k & 3)) { put(v, k); if (!k && !(HL >> v & 1)) hint(v); if (i == 15) { move(fr[0], 16); } }
        else pin(P.ulo, fr[v][2 * k] ^ fr[v][2 * k + 1]);
      };
#pragma unroll
      for (int v = 0; v < 10; v++) {
        mbar_wait(BAR(B_FULL + 20 + v));
        if (v == XP) {
          mbar_wait(BAR(B_EXT));
          wg_fence();
          wg_ss192_01(acc, mkdesc(DB + OFF_AX + 1024 * opaque(wg), 0, 128, 0), mkdesc(DB + OFF_BX, 2048, 1024, 1), 1);
          wg_ss64_01(acc + 96, mkdesc(DB + OFF_AX + 1024 * opaque(wg), 0, 128, 0), mkdesc(DB + OFF_BX + 6144, 2048, 1024, 1), 1);
          wg_commit();
          r0 = 0.5f * __uint_as_float(lds32(base + OFF_RT + 256 * wg + 64 * w + (lane & 28)));
          r1 = 0.5f * __uint_as_float(lds32(base + OFF_RT + 256 * wg + 64 * w + 32 + (lane & 28)));
          s0 = 2.f * r0 * r0;
          s1 = 2.f * r1 * r1;
        }
        wg_fence();
#pragma unroll
        for (int k = 0; k < 4; k++) {
          wg_ss128_11(acb, mkdesc(opaque(abd) + a_at(second(v)) + k * 2048, 16, 1024, 1), mkdesc(DB + OFF_R + WSLOT * ((v + 2) % 6) + k * 2048, UNIT, 1024, 1), v + k);
          if (k == GB - 1) { wg_commit(); wg_wait<1>(); if (v == XP) fence_regs(acc); if (elect()) mbar_arrive(BAR(B_EMPTY + 19 + v)); }
        }
        if (v == 9) wg_ss128_01(acb, mkdesc(DB + OFF_AX + 1024 * opaque(wg), 0, 128, 0), mkdesc(DB + OFF_BX + UNIT, 2048, 1024, 1), 1);
        wg_commit();
        split(P.ulo, v);
        if (v == XP + NP / 2 && (HL & 1)) hint(0);
        if (v == XP + NP && (HL & 2)) hint(1);
#pragma unroll
        for (int i = 0; i < 16; i++) if (v >= XP && i * NP / 16 == v - XP) act(i);
      }
#pragma unroll
      for (int v = 0; v < 3; v++) {
        mbar_wait(BAR(B_FULL + 30 + v));
        wg_fence();
#pragma unroll
        for (int i = 0; i < 4; i++) {
          own(4 * v + i);
          if (i == GB - 1) { wg_commit(); wg_wait<1>(); if (v == 0) fence_regs(acb); if (elect()) mbar_arrive(BAR(B_EMPTY + 29 + v)); }
        }
        wg_commit();
        split(P.ulo, 10 + v);
        if (v == 0 && XP + NP == 10 && (HL & 2)) hint(1);
        if (v == 2 && (HL & 4)) hint(2);
#pragma unroll
        for (int i = 0; i < 4; i++) if (v < 2) act(16 + 4 * v + i);
      }
      ck = base + 2048 * w + 516 * (lane >> 3) + 144 * (lane >> 2 & 1) + 32 * (lane & 3);
    }
    uint32_t x1[40], gb[20];
    if (!wg) {
      REGION_IDS;
      mbar_wait(BAR(B_GB));
#pragma unroll
      for (int k = 0; k < 5; k++) {
        const uint4 g = lds128(base + OFF_GB + 80 * (lane & 3) + 16 * k);
        gb[4 * k] = g.x; gb[4 * k + 1] = g.y; gb[4 * k + 2] = g.z; gb[4 * k + 3] = g.w;
      }
    }
#pragma unroll 1
    for (int u = 33; u < 42; u++) {
      const int x = P.hid[wg][u - 33], as = x & ~15;
      const uint64_t wd = mkdesc(0, 0, bo, 1) | P.w2t[u - 30].x;
      mbar_wait(BAR(B_FULL + u));
      a_tile(as, x & 15, false);
      if (wg || u < LAG2) {
        wg_fence();
#pragma unroll
        for (int kk = 0; kk < 4; kk++) {
          wg_ss160_01(o, mkdesc(DB + as + kk / 2 * 512 + (kk & 1) * 32, 16, 1024, 2), wd + kk * 128, 1);
          if (kk == GB - 1) { wg_commit(); wg_wait<1>(); if (elect()) mbar_arrive(BAR(B_EMPTY + u - 1)); }
        }
        wg_commit();
        if (u == 41 && elect()) mbar_arrive(BAR(B_LAG));
      }
      if (u == LAG2 - 1 && !wg) {
        REGION_IDS;
        const uint32_t xa = base + (lane >> 4) * 1024 + (lane & 7) * 128 + (((2 * w + ((lane >> 3) & 1)) ^ (lane & 7)) << 4);
        mbar_wait(BAR(B_FULL + 42));
        wg_wait<0>();
        if (elect()) mbar_arrive(BAR(B_EMPTY + LAG2 - 1));
#pragma unroll
        for (int k = 0; k < 10; k++) ldmatrix_x4_t(x1 + 4 * k, xa + x1_at(k / 2) + (k & 1) * 2048);
      }
    }
    REGION_IDS;
    const int h = role >> 2 & 1, j = role & 3;
    const uint32_t xb = base + OFF_XCH + 5120 * w;
    if (wg) {
      const uint32_t rdst = mapa(xb + 16 * lane, h ^ 1), rbar = mapa(BAR(B_FULL + 1), h ^ 1);
      mbar_wait(BAR(B_XFREE));
      wg_wait<0>();
      fence_regs(o);
#pragma unroll
      for (int k = 0; k < 10; k++)
        asm volatile("st.async.shared::cluster.mbarrier::complete_tx::bytes.v4.b32 [%0], {%1,%2,%3,%4}, [%5];" ::"r"(rdst + 512 * k), "r"(pack_bf16(o[8 * k], o[8 * k + 1])),
                     "r"(pack_bf16(o[8 * k + 2], o[8 * k + 3])), "r"(pack_bf16(o[8 * k + 4], o[8 * k + 5])), "r"(pack_bf16(o[8 * k + 6], o[8 * k + 7])), "r"(rbar + 16 * (k / 4)) : "memory");
    } else {
      mbar_wait(BAR(B_LAG));
      wg_fence();
#pragma unroll
      for (int i = 4 * LAG2; i < 168; i++) wg_ss160_01(o, mkdesc(DB + hid_at(i / 4 - 33, 0) + (i & 2) * 256 + (i & 1) * 32, 16, 1024, 2), mkdesc(DB + w2_at(i / 4 - 30) + (i & 3) * 2048, UNIT, bo, 1), 1);
      wg_commit();
      const int row = (8 * role & ~63) + 16 * w;
      auto merge = [&](int e0, int e1) {
#pragma unroll
        for (int e = e0; e < e1; e++) {
          if (e % 4 == 0) mbar_wait_cluster(BAR(B_FULL + 1 + e / 2));
          const uint4 p = lds128(xb + 16 * lane + 512 * e);
          x1[4 * e] = bfma2(gb[2 * e], p.x, x1[4 * e]); x1[4 * e + 1] = bfma2(gb[2 * e], p.y, x1[4 * e + 1]);
          x1[4 * e + 2] = bfma2(gb[2 * e + 1], p.z, x1[4 * e + 2]); x1[4 * e + 3] = bfma2(gb[2 * e + 1], p.w, x1[4 * e + 3]);
        }
        __syncwarp();
      };
      merge(0, MG);
      wg_wait<0>();
      fence_regs(o);
#pragma unroll
      for (int k = 0; k < 10; k++) {
        if (k >= MG && k % 4 == 0) merge(k, k < 8 ? k + 4 : 10);
        uint32_t y[4];
#pragma unroll
        for (int e = 0; e < 4; e++) y[e] = bfma2(gb[2 * k + e / 2], pack_bf16(o[8 * k + 2 * e], o[8 * k + 2 * e + 1]), x1[4 * k + e]);
        stmatrix_x4(k < 8 ? xb + 2048 * (k >> 2) + (lane & 15) * 128 + (((2 * (k & 3) + (lane >> 4)) ^ (lane & 7) ^ 4 * (j & 1)) << 4)
                          : xb + 4096 + (lane & 15) * 64 + (((2 * (k & 1) + (lane >> 4)) ^ (lane >> 1 & 3)) << 4), y[0], y[1], y[2], y[3]);
        if ((SG >> k & 1) || k == 9) {
          fence_async_smem();
          __syncwarp();
#pragma unroll
          for (int b = 0; b < 3; b++) {
            const int e = b < 2 ? 4 * b + 3 : 9;
            if (e <= k && !(SG & ((1 << k) - 1) & ~((1 << e) - 1)) && lane == 0) tma2d_store(b < 2 ? &maps.outa : &maps.outb, b < 2 ? 128 * j + 64 * b : 512 + 32 * j, row, xb + 2048 * b);
          }
        }
      }
      if (lane == 0) { bulk_commit(); bulk_wait_read(); }
    }
  } else if (wg == 2) {
    asm volatile("setmaxnreg.dec.sync.aligned.u32 40;");
    mbar_init<15>(BAR(B_FULL + 15 * w), 1);
    mbar_init<11>(BAR(B_EMPTY - 1 + 11 * w), 8);
    asm volatile("fence.mbarrier_init.release.cluster;" ::: "memory");
    LAUNCHES;
    silu_vector(P.c + 80 * (blockIdx.x & 7) - 512, 296, base - 1024);
    const uint32_t epoch = EPOCH;
    if (w == 2) rank_pair(G, base, epoch, true);
    cluster_wait();
    {
      REGION_IDS;
      const uint32_t tag = opaque(~lane & 1);
      auto q_t = [&]() {
        const int tr = 4 * (lane & 1) + (lane >> 1 & 3);
        uint32_t a = base + OFF_Q + 128 * ((lane & 24) + tr) + ((w ^ tr) << 4);
        uint4* dst = G->qt + (64 * (bid & 1) + 8 * w + (lane >> 2)) * 256 + 4 * (bid >> 1) + (lane & 3);
#pragma unroll 1
        for (int c = 0; c < 5; c++) {
          mbar_wait(BAR(B_Q + c));
#pragma unroll
          for (int k = 0; k < 2; k++) {
            uint32_t x[4];
            ldmatrix_x4_t(x, a ^ (64 * k));
            st_relaxed128(dst + 8192 * k, set_tag(x[0], tag, epoch), x[1], x[2], x[3]);
          }
          a += 4096;
          dst += 32768;
        }
        arrive1(BAR(B_QTD));
      };
      q_t();
      if (w == 3) {
        mbar_wait_cluster(BAR(B_ST1));
        if (lane < 8) red_hint(G->hint[5][lane]);
        const uint2 x = lds64(base + OFF_ST + 8 * (lane & 15)), y = lds64(base + OFF_ST + 128 + 8 * (lane & 15));
        float m, sd;
        ln_final(__uint_as_float(x.x) + __uint_as_float(y.x), __uint_as_float(x.y) + __uint_as_float(y.y), m, sd);
        sd = rbf(rcpf(sd));
        const uint32_t mr = pack_bf16(sd, -rbf(m) * sd), tg = lane & 7 ? 0 : lane & 8 ? 1 : 0x8000;
        const uint32_t o = __byte_perm(__shfl_sync(~0u, mr, 2 * lane & 14), __shfl_sync(~0u, mr, (2 * lane & 14) + 1), (lane & 8) ? 0x7632 : 0x5410);
        if (lane < 16) st_relaxed32(&G->st1[lane >> 3][8 * bid + (lane & 7)], (o & ~tg) | ((epoch & 1) * tg));
      }
      if (w == 2) rank_pair(G, base, epoch, false);
      if (w == 1) mod_fetch(G, base, epoch, M8, 0, 1);
    }
    {
      REGION_IDS;
      const uint32_t tag = opaque(~lane & 1), sa = opaque(base + 16 * i0);
      uint4 q[2];
      mbar_wait(BAR(B_PFULL));
#pragma unroll 1
      for (uint32_t a = sa + tab(T_P, 0); a < sa + tab(T_P, 0) + 4096; a += 2048) {
        uint4 y = lds128(a), z = lds128(a + 4096), u = lds128(a + 8192);
        const uint4 v = lds128(a + 12288);
        add4(y, z); add4(u, v); add4(y, u);
        sts128(a, y.x, y.y, y.z, y.w);
      }
      uint4* gp = G->xs + 256 * bid + (sa - base >> 4);
      q[0] = ld_relaxed128(gp - D_ * 256);
      q[1] = ld_relaxed128(gp - D_ * 256 + 128);
      mbar_wait(BAR(B_MR));
      e_round<true>(G, base, sa, gp, q, 0, w, tag, epoch);
#pragma unroll 1
      for (int c = 1; c < 5; c++) e_round<false>(G, base, sa, gp, q, c, w, tag, epoch);
    }
    int h, j, r;
    ffn_role(h, j, r);
    arrive1(BAR(B_ED));
    {
      REGION_IDS;
      float s0 = 0.f, q0 = 0.f, s1 = 0.f, q1 = 0.f;
#pragma unroll 1
      for (int c = 2; c < 5; c++) {
        const uint32_t buf = base + OFF_SX + 4096 * (c - 2), b = BAR(B_SX + c);
        uint32_t x[8];
#pragma unroll 1
        for (int it = 0; it < SPIN_LIMIT; it++) {
          mbar_wait(b, it & 1);
#pragma unroll
          for (int i = 0; i < 8; i++) x[i] = lds32(buf + 1024 * w + 4 * lane + 128 * i);
          if (bar_all(3, (lane & 7) || min(min(min(x[0], x[1]), min(x[2], x[3])), min(min(x[4], x[5]), min(x[6], x[7]))))) break;
          if (w == 0 && elect()) { mbar_expect_tx(b, 4096); tma2d(buf, &maps.x1s, 128 * r + 64 * h, D_ * (epoch & 1) + 128 * c + 32 * j, b); }
        }
#pragma unroll
        for (int i = 0; i < 8; i++) { const float lo = bf_lo(x[i]), hi = bf_hi(x[i]); s0 += lo; q0 = fmaf(lo, lo, q0); s1 += hi; q1 = fmaf(hi, hi, q1); }
      }
      sts128(base + OFF_MR + 1024 * w + 16 * lane, __float_as_uint(s0), __float_as_uint(q0), __float_as_uint(s1), __float_as_uint(q1));
      arrive1(BAR(B_S2));
    }
    {
      REGION_IDS;
      const uint32_t* sp = &G->st2[2 * r + (h ^ (w >> 1))][0][2 * (i0 & 63)];
      uint2 x[4];
      int it;
#pragma unroll 1
      for (it = 0; it < SPIN_LIMIT; it++) {
        mbar_wait(BAR(B_BX), it & 1);
        uint32_t y = 0;
#pragma unroll
        for (int k = 0; k < 3; k++) y |= lds32(base + OFF_BX + 32 * i0 + 4096 * k) ^ epoch;
        if (bar_all(3, !(y & 1))) break;
        if (w == 0 && elect()) { mbar_expect_tx(BAR(B_BX), 12288); bulk_load(base + OFF_BX, G->uv[4 * h + j], 12288, BAR(B_BX)); }
      }
      it = 0;
#pragma unroll 1
      do {
#pragma unroll
        for (int k = 0; k < 4; k++) x[k] = ld_relaxed64(sp + 128 * k);
      } while (__any_sync(~0u, ((x[0].x ^ epoch) | (x[1].x ^ epoch) | (x[2].x ^ epoch) | (x[3].x ^ epoch)) & 1) && ++it < SPIN_LIMIT);
      float m, sd;
      ln_final((__uint_as_float(x[0].x) + __uint_as_float(x[1].x)) + (__uint_as_float(x[2].x) + __uint_as_float(x[3].x)),
               (__uint_as_float(x[0].y) + __uint_as_float(x[1].y)) + (__uint_as_float(x[2].y) + __uint_as_float(x[3].y)), m, sd);
      const uint32_t e = pack_bf16(-m, sd);
      sts128(base + OFF_AX + 16 * i0, e, e, e, e);
      sts32(base + OFF_RT + 4 * i0, __float_as_uint(rcpf(sd)));
      fence_async_smem();
      arrive1(BAR(B_EXT));
      {
        uint2 g0, g1;
        int it = 0;
#pragma unroll 1
        do {
          g0 = ld_relaxed64(&G->modv[1][128 * j + i0]);
          g1 = ld_relaxed64(&G->modv[1][512 + 32 * j + lane]);
        } while (__any_sync(~0u, ((g0.x ^ epoch) | (g0.y ^ epoch) | (g1.x ^ epoch) | (g1.y ^ epoch)) & 1) && ++it < SPIN_LIMIT);
        const uint32_t a = base + OFF_GB + 40 * (lane & 6) + 2 * (lane & 1) + (lane >> 3) * 4;
        asm volatile("st.shared.u16 [%0], %1; st.shared.u16 [%2], %3;" ::"r"(a + 16 * (w ^ (j & 1))), "h"((uint16_t)(mod_sum(g0) >> 16)), "r"(a + 64), "h"((uint16_t)(mod_sum(g1) >> 16)) : "memory");
        arrive1(BAR(B_GB));
      }
      const int id = 16 * r + 4 * h + ((j + 1 + w) & 3);
#pragma unroll 1
      for (int q = w == 3 ? 3 : 0; q < 3; q++) {
        const int m = 3 * q + w;
        const uint4* src = G->hh + id * 1536 + 512 * q;
        it = 0;
#pragma unroll 1
        while (__any_sync(~0u, ld_relaxed32(&G->hhf[8 * id + 64 * (lane & 1) + q]) != 4 * epoch) && ++it < SPIN_LIMIT);
        mbar_wait(BAR(P.hid[2][m]));
        if (elect()) {
          bulk_load(base + (P.hid[h][m] & ~15), src, UNIT, BAR(B_FULL + 33 + m));
          bulk_load(base + (P.hid[h ^ 1][m] & ~15), src + 8 * 1536, UNIT, BAR(B_FULL + 33 + m));
        }
      }
    }
  } else {
    asm volatile("setmaxnreg.dec.sync.aligned.u32 24;");
    if (w >= 2) {
      LAUNCHES;
      uint32_t epoch;
      {
        REGION_IDS;
        uint32_t dv;
        asm volatile("ld.global.nc.u16 %0, [%1];" : "=r"(dv) : "l"(P.ssmd + 128 * (lane & 7) % D_ + bid));
        if (lane < 5) sts128(base + tab(T_F, lane) + (w & 1) * (F_O - F_E) + F_E - 16, 0, 0, 0, 0);
        epoch = EPOCH;
        __syncwarp();
#pragma unroll 1
        for (int c = 0; c < 5; c++) {
          const float d = i0 == 64 ? bf_lo(dv) : 0.f;
          dv = __shfl_down_sync(~0u, dv, 1);
          const uint32_t a = base + tab(T_F, c) + 16 * (i0 - 64);
          mbar_wait(BAR(B_FRAW + c));
#pragma unroll
          for (int k = 0; k < 4; k++) {
            uint4 x = lds128(a + F_E + 1024 * k);
            const uint32_t pv = lds32(a + F_E - 4 + 1024 * k);
            if (k == 0) { x.x = pack_bf16(bf_lo(x.x) + d, bf_hi(x.x)); sts32(a + F_E, x.x); }
            sts128(a + F_O + 1024 * k, __byte_perm(pv, x.x, 0x5432), __byte_perm(x.x, x.y, 0x5432), __byte_perm(x.y, x.z, 0x5432), __byte_perm(x.z, x.w, 0x5432));
          }
          __syncwarp();
          if (elect()) mbar_arrive2(BAR(B_FRDY + c));
          if (c == 0 && w == 3) {
#pragma unroll 1
            for (int k = 0; k < 13; k++) prefetch_map(&maps.w1a + k);
          }
        }
      }
      REGION_IDS;
      int h, j, r;
      ffn_role(h, j, r);
      cluster_wait();
      if (w == 2) {
        const unsigned* fp = G->xsh[lane < 10 ? lane >> 1 : 0][(r & 6) + (lane & 1)];
        uint32_t rdy = 0;
        mbar_wait(BAR(B_SC + 4));
#pragma unroll 1
        for (int e = 0; e < 14; e++) {
          const uint32_t x = P.adep[e], n = x >> 21 & 15, s = base + (x >> 25 << 13), b = BAR(B_FULL + (x >> 16 & 31));
          mbar_wait(BAR(opaque(x & 255)));
          mbar_wait(BAR(opaque(x >> 8 & 255)));
          const uint32_t f = BAR(B_FULL + 7 + 2 * (e < 7 ? e : e - 7));
          if (elect()) mbar_arrive_remote(mapa(f, h ^ 1));
#pragma unroll 1
          for (int it = 0; !(rdy >> n & 1) && it < SPIN_LIMIT; it++) rdy = __ballot_sync(~0u, ld_relaxed32(fp) == 64 * epoch);
          mbar_wait(f, e >= 7);
          if (elect()) asm volatile("cp.async.bulk.tensor.2d.shared::cluster.global.mbarrier::complete_tx::bytes.multicast::cluster [%0], [%1, {%3,%4}], [%2], %5;"
                                    ::"r"(s + UNIT * h), "l"(&maps.xs), "r"(b), "r"(128 * r + 64 * h), "r"(64 * n), "h"((uint16_t)3) : "memory");
        }
#pragma unroll 1
        for (int v = 0; v < 12; v++) {
          const int q = v * 11 >> 5, e = v - 3 * q, k32 = 24 * h + (q ? 6 * ((j + 1 + e) & 3) + 2 * q - 2 : 6 * j + 2 * e);
          const uint2 x = P.w2t[v];
          mbar_wait(BAR(x.y));
          if (elect()) {
            mbar_expect_tx(BAR(B_FULL + 30 + v), q ? W2TILE + 2 * UNIT : W2TILE);
#pragma unroll
            for (int k = 0; k < 3; k++) tma5d(base - DB + 16 * (x.x & 0xFFFF) + UNIT * k, &maps.w2a + (q > 0), k < 2 ? 128 * j + 64 * k : 512 + 32 * (j & 2), k32, BAR(B_FULL + 30 + v));
          }
        }
      } else {
        float s0 = 0.f, q0 = 0.f, s1 = 0.f, q1 = 0.f;
        uint32_t nl = 0, np = 0, ph = 0;
#pragma unroll 1
        for (uint32_t seq = 0x94; seq > 1; seq >>= 1) {
          const uint32_t c = seq & 1 ? np : nl, buf = base + OFF_SX + 4096 * (c < 4 ? c & 1 : 2), b = BAR(opaque(B_SX + c));
          int it = 0;
          if (seq & 1) {
            mbar_wait(b, ph >> c & 1);
            ph ^= 1 << c;
            const uint32_t a = buf + 32 * lane;
            if (__all_sync(~0u, min(min(lds32(a), lds32(a + 1024)), min(lds32(a + 2048), lds32(a + 3072)))) || ph > SPIN_LIMIT) {
#pragma unroll 1
              for (uint32_t o = buf + 4 * lane; o < buf + 4096; o += 1024) {
                uint32_t x[8];
#pragma unroll
                for (int i = 0; i < 8; i++) x[i] = lds32(o + 128 * i);
#pragma unroll
                for (int i = 0; i < 8; i++) { const float lo = bf_lo(x[i]), hi = bf_hi(x[i]); s0 += lo; q0 = fmaf(lo, lo, q0); s1 += hi; q1 = fmaf(hi, hi, q1); }
              }
              np++;
              continue;
            }
            ph += 4;
            seq = 2 * seq + 1;
          } else {
#pragma unroll 1
            while (__any_sync(~0u, ld_relaxed32(G->xsh[c][(r & 6) + (j >> 1)]) != 64 * epoch) && ++it < SPIN_LIMIT);
            if (++nl == 5) mbar_wait(BAR(B_PEMPTY + 4));
          }
          if (elect()) { mbar_expect_tx(b, 4096); tma2d(buf, &maps.x1s, 128 * r + 64 * h, D_ * (epoch & 1) + 128 * c + 32 * j, b); }
        }
        mbar_wait(BAR(B_S2));
#pragma unroll
        for (int k = 0; k < 4; k++) {
          const uint4 x = lds128(base + OFF_MR + 1024 * k + 16 * lane);
          s0 += __uint_as_float(x.x); q0 += __uint_as_float(x.y); s1 += __uint_as_float(x.z); q1 += __uint_as_float(x.w);
        }
        asm volatile("{.reg .b128 t, x; .reg .b64 a, b; mov.b64 a, {%1,%2}; mov.b64 b, {%3,%4}; mov.b128 x, {a,b}; atom.relaxed.gpu.global.exch.b128 t, [%0], x;}"
                     ::"l"(&G->st2[2 * r + h][j][4 * lane]), "r"((__float_as_uint(s0) & ~1u) | (epoch & 1)), "f"(q0), "r"((__float_as_uint(s1) & ~1u) | (epoch & 1)), "f"(q1) : "memory");
        mbar_wait(BAR(B_EMPTY + 2 * UVS + 1));
        sts128(base + OFF_CO + 16 * lane, 0, 0, 0, 0);
        fence_async_smem();
        __syncwarp();
        if (elect()) {
#pragma unroll 1
          for (int k = 0; k < 40; k++) asm volatile("cp.async.bulk.global.shared::cta.bulk_group [%0], [%1], 512;" ::"l"(G->x1[~epoch & 1] + 1280 * blockIdx.x + 32 * k), "r"(base + OFF_CO) : "memory");
          bulk_commit();
          bulk_wait_read();
        }
      }
    } else if (w == 0) {
      LAUNCHES;
      uint32_t epoch;
      {
        REGION_IDS;
        const unsigned* hp = G->hint[0][4 * (bid >> 6) + (bid >> 3 & 3)];
        uint32_t v = ld_relaxed32(hp + 256 * min(lane, 5));
        if (lane < 3) sts128(base + tab(T_X, lane) + 4096, 0, 0, 0, 0);
        if (lane && lane <= B_WM) mbar_expect_tx(BAR(lane), lane < B_FRAW ? 9728 : lane == B_WM ? 10240 : 4096);
        epoch = EPOCH;
        fence_async_smem();
        const uint32_t rdy = __ballot_sync(~0u, v == epoch << 6) & 31;
        uint32_t nx = 0, mr = 1;
#pragma unroll 1
        for (int it = 0; (nx < 5 || mr) && it < SPIN_LIMIT; it++) {
          const bool second = nx == 5 || (lane && mr && nx >= P.mq);
          if (!(rdy >> nx & 1)) v = ld_relaxed32(hp + 256 * (second ? 5 : nx));
          const uint32_t ok = __ballot_sync(~0u, v == epoch << (second ? 7 : 6)) | (rdy >> nx & 1);
          if (nx < 5 && (ok & 1)) {
            if (nx >= 3) mbar_wait(BAR(B_PFULL - 3 + nx));
            if (elect()) { mbar_expect_tx(BAR(B_XR + nx), 4096); bulk_load(base + tab(T_X, nx), G->xr + (128 * nx + bid) * 256, 4096, BAR(B_XR + nx)); }
          }
          if (mr && (nx == 5 || nx >= P.mq) && (ok & 2) && !(rdy >> nx & 1)) {
            if (elect()) { mbar_expect_tx(BAR(B_MR), 8192); bulk_load(base + OFF_MR, G->st1, 8192, BAR(B_MR)); mbar_arrive(BAR(B_QTOK)); }
            mr = 0;
          }
          if (nx < 5) nx += ok & 1;
        }
        mod_fetch(G, base, epoch, M8, 2, 5);
      }
      REGION_IDS;
      int h, j, r;
      ffn_role(h, j, r);
      cluster_wait();
      if (elect()) mbar_expect_tx(BAR(B_UVB), 30720);
#pragma unroll 1
      for (int k = 0; k < 5; k++) {
        mbar_wait(BAR(opaque(B_EMPTY + nib(P.uvd, k))));
        if (elect()) tma3d(base + OFF_UV + 6144 * k, &maps.w1u + (r & 1), 0, 40 * (r & 14) + 16 * k, 3 * (4 * h + j), BAR(B_UVB));
      }
      mbar_wait(BAR(B_G));
      {
        const uint2* mp = &G->modv[lane & 4 ? 0 : 2][40 * (r & 14) + (lane & 24) + 2 * (lane & 3)];
        uint4 v[3];
        int it = 0;
#pragma unroll 1
        do {
          v[0] = ld_relaxed128(mp); v[1] = ld_relaxed128(mp + 32); v[2] = ld_relaxed128(mp + 64 - (lane & 16));
        } while (__any_sync(~0u, ((v[0].x ^ epoch) | (v[0].y ^ epoch) | (v[0].z ^ epoch) | (v[0].w ^ epoch) | (v[1].x ^ epoch) | (v[1].y ^ epoch) | (v[1].z ^ epoch) | (v[1].w ^ epoch) |
                                  (v[2].x ^ epoch) | (v[2].y ^ epoch) | (v[2].z ^ epoch) | (v[2].w ^ epoch)) & 1) && ++it < SPIN_LIMIT);
#pragma unroll
        for (int i = 0; i < 3; i++)
          sts32(base + OFF_CO + 128 * i + 4 * lane, badd2(pack_bf16(__uint_as_float(v[i].x) + __uint_as_float(v[i].y), __uint_as_float(v[i].z) + __uint_as_float(v[i].w)), lane & 4 ? 0 : 0x3F803F80u));
      }
      fence_async_smem();
      arrive1(BAR(B_CO));
      ffn_role(h, j, r);
      mbar_wait(BAR(B_ED));
      int it = 0;
#pragma unroll 1
      while (__any_sync(~0u, ld_relaxed32(G->hint[8][4 * h + j]) != 128 * epoch) && ++it < SPIN_LIMIT);
      if (elect()) { mbar_expect_tx(BAR(B_BX), 12288); bulk_load(base + OFF_BX, G->uv[4 * h + j], 12288, BAR(B_BX)); }
      asm volatile("fence.acq_rel.gpu;" ::: "memory");
      if (lane < 8) red_hint(G->hint[7][lane]);
      unsigned x;
      it = 0;
#pragma unroll 1
      do { asm volatile("ld.acquire.gpu.global.u32 %0, [%1];" : "=r"(x) : "l"(G->hint[7][bid >> 4]) : "memory"); } while (__any_sync(~0u, x != 128 * epoch) && ++it < SPIN_LIMIT);
      fence_async_all();
      const int ch = D_ * (epoch & 1);
      mbar_wait(BAR(P.xdep));
      if (elect()) {
        mbar_expect_tx(BAR(B_FULL + 42), 20480);
#pragma unroll
        for (int k = 0; k < 4; k++) tma2d(base + x1_at(k), &maps.x1b, 128 * r + 64 * h, ch + 128 * j + 32 * (k ^ (j & 1)), BAR(B_FULL + 42));
        tma2d(base + x1_at(4), &maps.x1b, 128 * r + 64 * h, ch + 512 + 32 * j, BAR(B_FULL + 42));
        mbar_expect_tx(BAR(B_FULL + 1), 8192); mbar_expect_tx(BAR(B_FULL + 3), 8192); mbar_expect_tx(BAR(B_FULL + 5), 4096);
      }
      mbar_wait(BAR(B_EMPTY + 37));
      if (elect()) mbar_arrive_remote(mapa(BAR(B_XFREE), h ^ 1));
    } else {
      LAUNCHES;
      {
        REGION_IDS;
        loads<0>(P, maps, base);
      }
      cluster_wait();
      int h, j, r;
      ffn_role(h, j, r);
      mbar_wait(BAR(B_QTD));
      mbar_wait(BAR(B_STD));
      mbar_wait(BAR(B_SC));
      mbar_wait(BAR(B_SC + 2));
      mbar_wait(BAR(B_FL));
#pragma unroll 1
      for (int u = 0; u < 30; u++) {
        if (u == P.mpos) mod_fetch(G, base, EPOCH, M8, 1, 2);
        if (u < 6) wait_clock(t_start + P.wt0 + u * P.wpace);
        const uint32_t x = P.wdep[u], b = x >> 8 & 1;
        uint32_t s = base + OFF_R + WSLOT * (x >> 9 & 7), f = BAR(B_FULL + (b ? u : u & ~1)), n = x & 0xC000, y = x >> 16, z = 3 * (4 * h + j) + 2 * b;
        const CUtensorMap* m = &maps.w1a + 5 * b;
        asm volatile("{.reg .pred p, q; .reg .b32 i, t; .reg .b64 m; mov.u32 i, 0; add.u32 t, %0, 8192; add.u64 m, %1, 128; elect.sync _|q, 0xffffffff;"
                     "W: mbarrier.try_wait.parity.shared::cta.b64 p, [%6], 0; @p bra.uni D; add.u32 i, i, 1; setp.lt.u32 p, i, %7; @p bra.uni W; D:"
                     "setp.ne.and.u32 p, %3, 0, q; @p mbarrier.arrive.expect_tx.shared::cta.b64 _, [%2], %3;"
                     "@q cp.async.bulk.tensor.3d.shared::cluster.global.mbarrier::complete_tx::bytes [%0], [%1, {0,%4,%5}], [%2];"
                     "@q cp.async.bulk.tensor.3d.shared::cluster.global.mbarrier::complete_tx::bytes [t], [m, {0,%4,%5}], [%2];}"
                     ::"r"(s), "l"(m), "r"(f), "r"(n), "r"(y), "r"(z), "r"(BAR(opaque(x & 255))), "n"(SPIN_LIMIT) : "memory");
      }
    }
  }
}

typedef CUresult (*EncFn)(CUtensorMap*, CUtensorMapDataType, cuuint32_t, void*, const cuuint64_t*, const cuuint64_t*, const cuuint32_t*,
                          const cuuint32_t*, CUtensorMapInterleave, CUtensorMapSwizzle, CUtensorMapL2promotion, CUtensorMapFloatOOBfill);
static int enc_err = 0;
static void enc(EncFn fn, CUtensorMap* m, const void* p, int rank, const cuuint64_t* gd, const cuuint64_t* gs, const cuuint32_t* bd, CUtensorMapSwizzle sw) {
  cuuint32_t es[5] = {1, 1, 1, 1, 1};
  enc_err = 2 * enc_err + (fn(m, CU_TENSOR_MAP_DATA_TYPE_BFLOAT16, rank, (void*)p, gd, gs, bd, es, CU_TENSOR_MAP_INTERLEAVE_NONE, sw,
                              CU_TENSOR_MAP_L2_PROMOTION_L2_128B, CU_TENSOR_MAP_FLOAT_OOB_FILL_NONE) != CUDA_SUCCESS);
}

extern "C" void kernel_launch(void* const* d_in, const int* in_sizes, int n_in, void* d_out, int out_size) {
  const bf16 *q = (const bf16*)d_in[0], *k = (const bf16*)d_in[1], *v = (const bf16*)d_in[2], *shift = (const bf16*)d_in[3],
             *ssmk = (const bf16*)d_in[4], *ssmd = (const bf16*)d_in[5], *w1 = (const bf16*)d_in[7], *w3 = (const bf16*)d_in[8],
             *w2 = (const bf16*)d_in[9], *c = (const bf16*)d_in[10], *wmod = (const bf16*)d_in[11];
  EncFn fn = nullptr;
  cudaDriverEntryPointQueryResult qr;
  cudaGetDriverEntryPoint("cuTensorMapEncodeTiled", (void**)&fn, cudaEnableDefault, &qr);
  Scratch* pg;
  cudaGetSymbolAddress((void**)&pg, g_s);
  Maps maps;
  enc_err = 0;
  const CUtensorMapSwizzle S128 = CU_TENSOR_MAP_SWIZZLE_128B;
  { cuuint64_t gd[3] = {D_, S_ / 8, 8}, gs[2] = {D_ * 16, D_ * 2}; cuuint32_t b[3] = {64, 4, 8};
    enc(fn, &maps.km, k, 3, gd, gs, b, S128);
    enc(fn, &maps.v, v, 3, gd, gs, b, S128);
    enc(fn, &maps.q, q, 3, gd, gs, b, S128);
    b[2] = 3;
    enc(fn, &maps.kh, k, 3, gd, gs, b, S128); }
  { cuuint64_t gd[3] = {256, 8, D_}, gs[2] = {512, 4096}; cuuint32_t b[3] = {256, 8, 1};
    enc(fn, &maps.fm, ssmk, 3, gd, gs, b, CU_TENSOR_MAP_SWIZZLE_NONE); }
  { cuuint64_t gd[3] = {256, 2, 5}, gs[2] = {512, 1024}; cuuint32_t b[3] = {256, 1, 5};
    enc(fn, &maps.tap, shift, 3, gd, gs, b, CU_TENSOR_MAP_SWIZZLE_NONE); }
  { cuuint64_t gd[3] = {6 * D_, D_, 1}, gs[2] = {6 * D_ * 2, 6 * D_ * 2 * D_}; cuuint32_t b[3] = {64, 64, 1};
    enc(fn, &maps.wm, wmod, 3, gd, gs, b, S128);
    b[1] = 80;
    enc(fn, &maps.wmp, wmod, 3, gd, gs, b, S128); }
  { cuuint64_t gd[3] = {64, D_, F_ / 64}, gs[2] = {F_ * 2, 128}; cuuint32_t b[3] = {64, 16, 3};
    enc(fn, &maps.w1u, w1, 3, gd, gs, b, S128);
    enc(fn, &maps.w3u, w3, 3, gd, gs, b, S128);
    b[1] = 32; b[2] = 2;
    enc(fn, &maps.w1a, w1, 3, gd, gs, b, S128);
    enc(fn, &maps.w3a, w3, 3, gd, gs, b, S128);
    b[1] = 64; b[2] = 1;
    enc(fn, &maps.w1b, w1, 3, gd, gs, b, S128);
    enc(fn, &maps.w3b, w3, 3, gd, gs, b, S128); }
  { cuuint64_t gd[2] = {S_, D_}, gs[1] = {S_ * 2}; cuuint32_t b1[2] = {64, 64}, b2[2] = {64, 32};
    enc(fn, &maps.xs, pg->xs, 2, gd, gs, b1, S128);
    gd[1] = 2 * D_;
    enc(fn, &maps.x1b, pg->x1, 2, gd, gs, b2, S128);
    enc(fn, &maps.x1s, pg->x1, 2, gd, gs, b2, CU_TENSOR_MAP_SWIZZLE_NONE); }
  { cuuint64_t gd[5] = {D_, 2, 4, 4, 48}, gs[4] = {D_ * 2, D_ * 4, D_ * 16, D_ * 64}; cuuint32_t b[5] = {64, 2, 4, 4, 2};
    enc(fn, &maps.w2a, w2, 5, gd, gs, b, S128);
    gs[1] = D_ * 16; gs[2] = D_ * 4;
    enc(fn, &maps.w2b, w2, 5, gd, gs, b, S128); }
  { cuuint64_t gd[2] = {D_, S_}, gs[1] = {D_ * 2}; cuuint32_t b1[2] = {64, 16}, b2[2] = {32, 16};
    enc(fn, &maps.outa, d_out, 2, gd, gs, b1, S128);
    enc(fn, &maps.outb, d_out, 2, gd, gs, b2, CU_TENSOR_MAP_SWIZZLE_64B); }
  if (enc_err) return;
  cudaFuncSetAttribute(k_fused<0>, cudaFuncAttributeMaxDynamicSharedMemorySize, SMEM_BYTES);
  cudaFuncSetAttribute(k_fused<128>, cudaFuncAttributeMaxDynamicSharedMemorySize, SMEM_BYTES);
  cudaLaunchConfig_t cfg = {132, 512, SMEM_BYTES};
  cudaLaunchAttribute at = {cudaLaunchAttributeClusterDimension};
  at.val.clusterDim.x = 2; at.val.clusterDim.y = at.val.clusterDim.z = 1;
  cfg.attrs = &at; cfg.numAttrs = 1;
  int nc = 0;
  cudaOccupancyMaxActiveClusters(&nc, k_fused<0>, &cfg);
  Ptrs P = {c, ssmd, pg, {0x676360, 0x57246209}, {}, 32, 2, 0, B_EMPTY + 32, 0 | 0 << 16, 0, {}, 0x53511, 1, 11600, 900, 1.f};
  const char *win = "4444444444444444444", *ho = "abcdefghijklmnopqrstuvwxyz{|}~";
  memset(P.hl, 255, sizeof(P.hl));
  for (int k = 0, n = 0; k < 30; k++) {
    const int i = ho[k] - 'a';
    if (i >= 20 || !(M8 >> i / 4 & 1)) ((uint8_t*)P.hl)[n++] = i;
  }
  for (int e = 0; e < NL; e++) {
    auto size = [](int i) { return i < 0 ? 8 : ORDER[2 * i] == 'w' ? 10 : 4; };
    int i = e, sum = 0, g = 2 * load_bar(e) + 1;
    while (i >= -1 && sum + size(i) <= 4 * (win[e] - '0')) sum += size(i--);
    for (; i >= -1; i--) {
      bool ok = i < e;
      for (int k = e; k < NL; k++) ok = ok && load_bar(k) != load_bar(i);
      if (ok) { g = 2 * load_bar(i); break; }
    }
    ((uint8_t*)P.gate)[e] = g;
  }
  for (int u = 0; u < 30; u++) P.wdep[u] = (u < 4 ? B_FL + 1 + u / 3 : u < 6 ? B_G : B_EMPTY + (u < 26 ? (u - 6) | 1 : u - 6)) | (u >= 20) << 8 | u % 6 << 9 | (u < 20 ? 3 * (~u & 1) : 1 + (u >= 26)) << 14 | (u < 20 ? 32 * u : 64 * (second(u - 20) % 10)) << 16;
  const int adep[14] = {B_PEMPTY, B_PEMPTY, B_PFULL + 4, B_PEMPTY + 1, B_PEMPTY + 2, B_EMPTY + 5, B_EMPTY + 7, B_PEMPTY + 3, B_EMPTY + 2 * UVS + 1, B_EMPTY + 2 * UVS + 1, B_EMPTY + 20, B_EMPTY + 21, B_EMPTY + 22, B_EMPTY + 23};
  const char *ad = "--*--bh---vwxy", *wd = "25579:;==?\?A", *hd = "689;;>?@A";
  for (int n = 0; n < 14; n++) P.adep[n] = adep[n] | (ad[n] == '-' ? adep[n] : ad[n] == '*' ? B_PFULL + 3 : B_EMPTY + ad[n] - 'a') << 8 | (n < 10 ? 2 * n : n + 16) << 16 | n % 10 << 21 | a_at(n) / UNIT << 25;
  for (int v = 0; v < 12; v++) P.w2t[v] = make_uint2(w2_desc(v), B_EMPTY + 20 + wd[v] - '0');
  for (int m = 0; m < 9; m++) { P.hid[0][m] = hid_at(m, 0) | m / 3 * 4 | (m % 3 + 1); P.hid[1][m] = hid_at(m, 1) | m / 3 * 4 | (m % 3 + 1); P.hid[2][m] = B_EMPTY + 20 + hd[m] - '0'; }
  if (nc < 66) k_fused<128><<<4, 512, SMEM_BYTES, cudaStreamPerThread>>>(P, maps);
  k_fused<0><<<nc < 66 ? 128 : 132, 512, SMEM_BYTES, cudaStreamPerThread>>>(P, maps);
}
```

```cpp
#include <cuda_runtime.h>
#include <cuda.h>
#include <cuda_bf16.h>
#include <stdint.h>
#include <stdlib.h>
#include <string.h>

typedef __nv_bfloat16 bf16;
constexpr int S_ = 2048, D_ = 640, F_ = 1536;

struct Scratch {
  uint32_t st1[2][1024];
  uint32_t st2[32][4][128];
  uint32_t modc[128][5][32];
  uint2 modv[3][D_];
  uint32_t uv[8][3072];
  unsigned hint[9][8][32];
  unsigned xsh[5][8][32], hhf[256 * 8], key[256];
  uint4 xr[D_ * 256];
  uint4 qt[D_ * 256];
  uint4 xs[D_ * 256];
  uint4 x1[2][D_ * 256];
  uint4 hh[32 * 8 * 1536];
};
__device__ __align__(1024) Scratch g_s;

__device__ __forceinline__ uint32_t smem_u32(const void* p) { return (uint32_t)__cvta_generic_to_shared(p); }
__device__ __forceinline__ void mbar_expect_tx(uint32_t b, uint32_t n) { asm volatile("mbarrier.arrive.expect_tx.shared::cta.b64 _, [%0], %1;" ::"r"(b), "r"(n) : "memory"); }
__device__ __forceinline__ void mbar_arrive(uint32_t b) { asm volatile("mbarrier.arrive.shared::cta.b64 _, [%0];" ::"r"(b) : "memory"); }
__device__ __forceinline__ void mbar_arrive2(uint32_t b) { asm volatile("mbarrier.arrive.shared::cta.b64 _, [%0], 2;" ::"r"(b) : "memory"); }
__device__ __forceinline__ uint32_t mapa(uint32_t a, uint32_t cta) { uint32_t r; asm volatile("mapa.shared::cluster.u32 %0, %1, %2;" : "=r"(r) : "r"(a), "r"(cta)); return r; }
__device__ __forceinline__ void mbar_arrive_remote(uint32_t rb) { asm volatile("mbarrier.arrive.shared::cluster.b64 _, [%0];" ::"r"(rb) : "memory"); }
constexpr int SPIN_LIMIT = 1 << 16;
template <int N> __device__ __forceinline__ void mbar_init(uint32_t b, uint32_t count) {
#pragma unroll
  for (int i = 0; i < N; i++) asm volatile("mbarrier.init.shared::cta.b64 [%0], %1;" ::"r"(b + 8 * i), "r"(count) : "memory");
}
__device__ __forceinline__ bool elect() { uint32_t p; asm volatile("{.reg .pred q; elect.sync _|q, 0xffffffff; selp.u32 %0, 1, 0, q;}" : "=r"(p)); return p; }
__device__ __forceinline__ void arrive1(uint32_t b) { __syncwarp(); if (elect()) mbar_arrive(b); }
__device__ __forceinline__ bool mbar_test(uint32_t b) {
  uint32_t ok;
  asm volatile("{.reg .pred p; mbarrier.test_wait.parity.shared::cta.b64 p, [%1], 0; selp.u32 %0,1,0,p;}" : "=r"(ok) : "r"(b) : "memory");
  return ok;
}
#define WAIT_LOOP(sem) "{.reg .pred p; mov.u32 %0, 0; W: mbarrier.try_wait.parity" sem ".shared::cta.b64 p, [%1], %2; @p bra.uni D; add.u32 %0, %0, 1; setp.lt.u32 p, %0, %3; @p bra.uni W; D:}"
__device__ __forceinline__ void mbar_wait(uint32_t b, uint32_t ph = 0) {
  int it;
  asm volatile(WAIT_LOOP("") : "=&r"(it) : "r"(b), "r"(ph), "n"(SPIN_LIMIT) : "memory");
}
__device__ __forceinline__ void mbar_wait_cluster(uint32_t b, uint32_t ph = 0) {
  int it;
  asm volatile(WAIT_LOOP(".acquire.cluster") : "=&r"(it) : "r"(b), "r"(ph), "n"(SPIN_LIMIT) : "memory");
}
__device__ __forceinline__ void wait_clock(uint32_t t) {
  asm volatile("{.reg .pred p; .reg .s32 d; W: mov.u32 d, %%clock; sub.s32 d, d, %0; setp.lt.s32 p, d, 0; @p bra.uni W;}" ::"r"(t) : "memory");
}
__device__ __forceinline__ void tma2d(uint32_t dst, const CUtensorMap* m, int c0, int c1, uint32_t bar) {
  asm volatile("cp.async.bulk.tensor.2d.shared::cluster.global.mbarrier::complete_tx::bytes [%0], [%1, {%3,%4}], [%2];" ::"r"(dst), "l"(m), "r"(bar), "r"(c0), "r"(c1) : "memory");
}
__device__ __forceinline__ void tma3d(uint32_t dst, const CUtensorMap* m, int c0, int c1, int c2, uint32_t bar) {
  asm volatile("cp.async.bulk.tensor.3d.shared::cluster.global.mbarrier::complete_tx::bytes [%0], [%1, {%3,%4,%5}], [%2];" ::"r"(dst), "l"(m), "r"(bar), "r"(c0), "r"(c1), "r"(c2) : "memory");
}
__device__ __forceinline__ void tma5d(uint32_t dst, const CUtensorMap* m, int c0, int c4, uint32_t bar) {
  asm volatile("cp.async.bulk.tensor.5d.shared::cluster.global.mbarrier::complete_tx::bytes [%0], [%1, {%4,%3,%3,%3,%5}], [%2];" ::"r"(dst), "l"(m), "r"(bar), "r"(0), "r"(c0), "r"(c4) : "memory");
}
__device__ __forceinline__ void tma2d_store(const CUtensorMap* m, int c0, int c1, uint32_t src) {
  asm volatile("cp.async.bulk.tensor.2d.global.shared::cta.bulk_group [%0, {%2,%3}], [%1];" ::"l"(m), "r"(src), "r"(c0), "r"(c1) : "memory");
}
__device__ __forceinline__ void bulk_load(uint32_t dst, const void* src, uint32_t bytes, uint32_t bar) {
  asm volatile("cp.async.bulk.shared::cluster.global.mbarrier::complete_tx::bytes [%0], [%1], %2, [%3];" ::"r"(dst), "l"(src), "r"(bytes), "r"(bar) : "memory");
}
__device__ __forceinline__ void prefetch_map(const CUtensorMap* m) { asm volatile("prefetch.tensormap [%0];" ::"l"(m) : "memory"); }
__device__ __forceinline__ void bulk_commit() { asm volatile("cp.async.bulk.commit_group;" ::: "memory"); }
__device__ __forceinline__ void bulk_wait_read() { asm volatile("cp.async.bulk.wait_group.read 0;" ::: "memory"); }
__device__ __forceinline__ void fence_async_smem() { asm volatile("fence.proxy.async.shared::cta;" ::: "memory"); }
__device__ __forceinline__ void fence_async_all() { asm volatile("fence.proxy.async.global;" ::: "memory"); }
__device__ __forceinline__ void named_bar(int id, int n) { asm volatile("bar.sync %0, %1;" ::"r"(id), "r"(n) : "memory"); }
__device__ __forceinline__ bool bar_all(int id, bool v) {
  uint32_t r;
  asm volatile("{.reg .pred p, q; setp.ne.u32 p, %2, 0; bar.red.and.pred q, %1, 128, p; selp.u32 %0, 1, 0, q;}" : "=r"(r) : "r"(id), "r"((uint32_t)v) : "memory");
  return __all_sync(~0u, r);
}
__device__ __forceinline__ void cluster_wait() { asm volatile("barrier.cluster.wait.aligned;" ::: "memory"); }
__device__ __forceinline__ void wg_fence() { asm volatile("wgmma.fence.sync.aligned;" ::: "memory"); }
__device__ __forceinline__ void wg_commit() { asm volatile("wgmma.commit_group.sync.aligned;" ::: "memory"); }
template <int N> __device__ __forceinline__ void wg_wait() { asm volatile("wgmma.wait_group.sync.aligned %0;" ::"n"(N) : "memory"); }
template <int N> __device__ __forceinline__ void fence_regs(float (&a)[N]) {
#pragma unroll
  for (int i = 0; i < N; i++) asm volatile("" : "+f"(a[i])::"memory");
}
__device__ __forceinline__ uint64_t mkdesc(uint32_t addr, uint32_t lbo, uint32_t sbo, uint32_t swz) {
  uint32_t lo = (addr >> 4) | ((lbo >> 4) << 16), hi = (sbo >> 4) | (swz << 30);
  return ((uint64_t)hi << 32) | lo;
}
__device__ __forceinline__ void stmatrix_x4(uint32_t a, uint32_t r0, uint32_t r1, uint32_t r2, uint32_t r3) {
  asm volatile("stmatrix.sync.aligned.m8n8.x4.shared.b16 [%0], {%1,%2,%3,%4};" ::"r"(a), "r"(r0), "r"(r1), "r"(r2), "r"(r3) : "memory");
}
__device__ __forceinline__ void stmatrix_x4_t(uint32_t a, uint32_t r0, uint32_t r1, uint32_t r2, uint32_t r3) {
  asm volatile("stmatrix.sync.aligned.m8n8.x4.trans.shared.b16 [%0], {%1,%2,%3,%4};" ::"r"(a), "r"(r0), "r"(r1), "r"(r2), "r"(r3) : "memory");
}
__device__ __forceinline__ void ldmatrix_x4_t(uint32_t* r, uint32_t a) {
  asm volatile("ldmatrix.sync.aligned.m8n8.x4.trans.shared.b16 {%0,%1,%2,%3}, [%4];" : "=r"(r[0]), "=r"(r[1]), "=r"(r[2]), "=r"(r[3]) : "r"(a) : "memory");
}
__device__ __forceinline__ uint32_t lds32(uint32_t a) { uint32_t v; asm volatile("ld.shared.b32 %0, [%1];" : "=r"(v) : "r"(a) : "memory"); return v; }
__device__ __forceinline__ uint2 lds64(uint32_t a) { uint2 v; asm volatile("ld.shared.v2.b32 {%0,%1}, [%2];" : "=r"(v.x), "=r"(v.y) : "r"(a) : "memory"); return v; }
__device__ __forceinline__ uint4 lds128(uint32_t a) { uint4 v; asm volatile("ld.shared.v4.b32 {%0,%1,%2,%3}, [%4];" : "=r"(v.x), "=r"(v.y), "=r"(v.z), "=r"(v.w) : "r"(a) : "memory"); return v; }
__device__ __forceinline__ void sts32(uint32_t a, uint32_t v) { asm volatile("st.shared.b32 [%0], %1;" ::"r"(a), "r"(v) : "memory"); }
__device__ __forceinline__ void sts64(uint32_t a, uint32_t x, uint32_t y) { asm volatile("st.shared.v2.b32 [%0], {%1,%2};" ::"r"(a), "r"(x), "r"(y) : "memory"); }
__device__ __forceinline__ void sts128(uint32_t a, uint32_t x, uint32_t y, uint32_t z, uint32_t w) { asm volatile("st.shared.v4.b32 [%0], {%1,%2,%3,%4};" ::"r"(a), "r"(x), "r"(y), "r"(z), "r"(w) : "memory"); }
__device__ __forceinline__ uint4 ld_relaxed128(const void* p) { uint4 v; asm volatile("ld.relaxed.gpu.global.v4.u32 {%0,%1,%2,%3}, [%4];" : "=r"(v.x), "=r"(v.y), "=r"(v.z), "=r"(v.w) : "l"(p) : "memory"); return v; }
__device__ __forceinline__ uint2 ld_relaxed64(const void* p) { uint2 v; asm volatile("ld.relaxed.gpu.global.v2.u32 {%0,%1}, [%2];" : "=r"(v.x), "=r"(v.y) : "l"(p) : "memory"); return v; }
__device__ __forceinline__ uint32_t ld_relaxed32(const void* p) { uint32_t v; asm volatile("ld.relaxed.gpu.global.u32 %0, [%1];" : "=r"(v) : "l"(p) : "memory"); return v; }
__device__ __forceinline__ void st_relaxed128(void* p, uint32_t x, uint32_t y, uint32_t z, uint32_t w) { asm volatile("st.relaxed.gpu.global.v4.u32 [%0], {%1,%2,%3,%4};" ::"l"(p), "r"(x), "r"(y), "r"(z), "r"(w) : "memory"); }
__device__ __forceinline__ void st_relaxed32(void* p, uint32_t x) { asm volatile("st.relaxed.gpu.global.u32 [%0], %1;" ::"l"(p), "r"(x) : "memory"); }
__device__ __forceinline__ void red_hint(unsigned* p) { asm volatile("red.relaxed.gpu.global.add.u32 [%0], 1;" ::"l"(p) : "memory"); }
__device__ __forceinline__ void publish(uint32_t* p, uint32_t x) { asm volatile("{.reg .b32 t; atom.relaxed.gpu.global.exch.b32 t, [%0], %1;}" ::"l"(p), "r"(x) : "memory"); }
__device__ __forceinline__ uint32_t ldg32(const void* p) { uint32_t v; asm volatile("ld.global.nc.L1::no_allocate.b32 %0, [%1];" : "=r"(v) : "l"(p)); return v; }
__device__ __forceinline__ uint32_t pack_bf16(float lo, float hi) { uint32_t r; asm("cvt.rn.bf16x2.f32 %0, %1, %2;" : "=r"(r) : "f"(hi), "f"(lo)); return r; }
__device__ __forceinline__ float bf_lo(uint32_t v) { return __uint_as_float(v << 16); }
__device__ __forceinline__ float bf_hi(uint32_t v) { return __uint_as_float(v & 0xFFFF0000u); }
__device__ __forceinline__ uint32_t bmul2(uint32_t a, uint32_t b) { uint32_t r; asm("mul.rn.bf16x2 %0, %1, %2;" : "=r"(r) : "r"(a), "r"(b)); return r; }
__device__ __forceinline__ uint32_t badd2(uint32_t a, uint32_t b) { uint32_t r; asm("add.rn.bf16x2 %0, %1, %2;" : "=r"(r) : "r"(a), "r"(b)); return r; }
__device__ __forceinline__ uint32_t bfma2(uint32_t a, uint32_t b, uint32_t c) { uint32_t r; asm("fma.rn.bf16x2 %0, %1, %2, %3;" : "=r"(r) : "r"(a), "r"(b), "r"(c)); return r; }
__device__ __forceinline__ uint32_t set_tag(uint32_t x, uint32_t mask, uint32_t e) { uint32_t r; asm("lop3.b32 %0, %1, %2, %3, 0xB8;" : "=r"(r) : "r"(x), "r"(mask), "r"(e)); return r; }
__device__ __forceinline__ uint32_t opaque(uint32_t x) { asm volatile("" : "+r"(x)); return x; }
__device__ __forceinline__ float rbf(float x) { return __bfloat162float(__float2bfloat16(x)); }
__device__ __forceinline__ float silu_f(float x) {
  float e, r;
  asm("ex2.approx.ftz.f32 %0, %1;" : "=f"(e) : "f"(x * -1.4426950408889634f));
  asm("rcp.approx.ftz.f32 %0, %1;" : "=f"(r) : "f"(1.f + e));
  return x * r;
}
__device__ __forceinline__ float silu2(float g, float a, float b) {
  float t;
  asm("tanh.approx.f32 %0, %1;" : "=f"(t) : "f"(g * a));
  return fmaf(g * b, t, g * b);
}
__device__ __forceinline__ void pin(int off, uint32_t x) { asm volatile("{.reg .pred p; setp.lt.s32 p, %0, 0; @p st.shared.b32 [%0], %1;}" ::"r"(off), "r"(x) : "memory"); }
__device__ __forceinline__ void pin4(int off, const uint32_t* x) { asm volatile("{.reg .pred p; setp.lt.s32 p, %0, 0; @p st.shared.v4.b32 [%0], {%1,%2,%3,%4};}" ::"r"(off), "r"(x[0]), "r"(x[1]), "r"(x[2]), "r"(x[3]) : "memory"); }
__device__ __forceinline__ void split(int x, int n) { asm volatile("{.reg .pred p; setp.eq.s32 p, %0, %1; @p trap;}" ::"r"(x), "r"(~n) : "memory"); }
__device__ __forceinline__ void ln_final(float s, float q, float& m, float& sd) {
  m = s * (1.f / D_);
  asm("sqrt.approx.f32 %0, %1;" : "=f"(sd) : "f"(rbf(rbf(fmaxf(fmaf(-m, m, q * (1.f / D_)), 0.f)) + 1e-5f)));
  sd = rbf(sd);
}
__device__ __forceinline__ float rcpf(float x) { float r; asm("rcp.approx.f32 %0, %1;" : "=f"(r) : "f"(x)); return r; }

__device__ __forceinline__ void wg_rs16_0(float* d, const uint32_t* a, uint64_t db, int sc) {
  asm volatile("{.reg .pred p; setp.ne.b32 p, %13, 0; wgmma.mma_async.sync.aligned.m64n16k16.f32.bf16.bf16 {%0,%1,%2,%3,%4,%5,%6,%7}, {%8,%9,%10,%11}, %12, p, 1, 1, 0;}"
    : "+f"(d[0]),"+f"(d[1]),"+f"(d[2]),"+f"(d[3]),"+f"(d[4]),"+f"(d[5]),"+f"(d[6]),"+f"(d[7]) : "r"(a[0]),"r"(a[1]),"r"(a[2]),"r"(a[3]),"l"(db),"r"(sc));
}
__device__ __forceinline__ void wg_rs32_0(float* d, const uint32_t* a, uint64_t db, int sc) {
  asm volatile("{.reg .pred p; setp.ne.b32 p, %21, 0; wgmma.mma_async.sync.aligned.m64n32k16.f32.bf16.bf16 {%0,%1,%2,%3,%4,%5,%6,%7,%8,%9,%10,%11,%12,%13,%14,%15}, {%16,%17,%18,%19}, %20, p, 1, 1, 0;}"
    : "+f"(d[0]),"+f"(d[1]),"+f"(d[2]),"+f"(d[3]),"+f"(d[4]),"+f"(d[5]),"+f"(d[6]),"+f"(d[7]),"+f"(d[8]),"+f"(d[9]),"+f"(d[10]),"+f"(d[11]),"+f"(d[12]),"+f"(d[13]),"+f"(d[14]),"+f"(d[15]) : "r"(a[0]),"r"(a[1]),"r"(a[2]),"r"(a[3]),"l"(db),"r"(sc));
}
__device__ __forceinline__ void wg_rs48_0(float* d, const uint32_t* a, uint64_t db, int sc) {
  asm volatile("{.reg .pred p; setp.ne.b32 p, %29, 0; wgmma.mma_async.sync.aligned.m64n48k16.f32.bf16.bf16 {%0,%1,%2,%3,%4,%5,%6,%7,%8,%9,%10,%11,%12,%13,%14,%15,%16,%17,%18,%19,%20,%21,%22,%23}, {%24,%25,%26,%27}, %28, p, 1, 1, 0;}"
    : "+f"(d[0]),"+f"(d[1]),"+f"(d[2]),"+f"(d[3]),"+f"(d[4]),"+f"(d[5]),"+f"(d[6]),"+f"(d[7]),"+f"(d[8]),"+f"(d[9]),"+f"(d[10]),"+f"(d[11]),"+f"(d[12]),"+f"(d[13]),"+f"(d[14]),"+f"(d[15]),"+f"(d[16]),"+f"(d[17]),"+f"(d[18]),"+f"(d[19]),"+f"(d[20]),"+f"(d[21]),"+f"(d[22]),"+f"(d[23]) : "r"(a[0]),"r"(a[1]),"r"(a[2]),"r"(a[3]),"l"(db),"r"(sc));
}
__device__ __forceinline__ void wg_rs64_0(float* d, const uint32_t* a, uint64_t db, int sc) {
  asm volatile("{.reg .pred p; setp.ne.b32 p, %37, 0; wgmma.mma_async.sync.aligned.m64n64k16.f32.bf16.bf16 {%0,%1,%2,%3,%4,%5,%6,%7,%8,%9,%10,%11,%12,%13,%14,%15,%16,%17,%18,%19,%20,%21,%22,%23,%24,%25,%26,%27,%28,%29,%30,%31}, {%32,%33,%34,%35}, %36, p, 1, 1, 0;}"
    : "+f"(d[0]),"+f"(d[1]),"+f"(d[2]),"+f"(d[3]),"+f"(d[4]),"+f"(d[5]),"+f"(d[6]),"+f"(d[7]),"+f"(d[8]),"+f"(d[9]),"+f"(d[10]),"+f"(d[11]),"+f"(d[12]),"+f"(d[13]),"+f"(d[14]),"+f"(d[15]),"+f"(d[16]),"+f"(d[17]),"+f"(d[18]),"+f"(d[19]),"+f"(d[20]),"+f"(d[21]),"+f"(d[22]),"+f"(d[23]),"+f"(d[24]),"+f"(d[25]),"+f"(d[26]),"+f"(d[27]),"+f"(d[28]),"+f"(d[29]),"+f"(d[30]),"+f"(d[31]) : "r"(a[0]),"r"(a[1]),"r"(a[2]),"r"(a[3]),"l"(db),"r"(sc));
}
__device__ __forceinline__ void wg_rs80_0(float* d, const uint32_t* a, uint64_t db, int sc) {
  asm volatile("{.reg .pred p; setp.ne.b32 p, %45, 0; wgmma.mma_async.sync.aligned.m64n80k16.f32.bf16.bf16 {%0,%1,%2,%3,%4,%5,%6,%7,%8,%9,%10,%11,%12,%13,%14,%15,%16,%17,%18,%19,%20,%21,%22,%23,%24,%25,%26,%27,%28,%29,%30,%31,%32,%33,%34,%35,%36,%37,%38,%39}, {%40,%41,%42,%43}, %44, p, 1, 1, 0;}"
    : "+f"(d[0]),"+f"(d[1]),"+f"(d[2]),"+f"(d[3]),"+f"(d[4]),"+f"(d[5]),"+f"(d[6]),"+f"(d[7]),"+f"(d[8]),"+f"(d[9]),"+f"(d[10]),"+f"(d[11]),"+f"(d[12]),"+f"(d[13]),"+f"(d[14]),"+f"(d[15]),"+f"(d[16]),"+f"(d[17]),"+f"(d[18]),"+f"(d[19]),"+f"(d[20]),"+f"(d[21]),"+f"(d[22]),"+f"(d[23]),"+f"(d[24]),"+f"(d[25]),"+f"(d[26]),"+f"(d[27]),"+f"(d[28]),"+f"(d[29]),"+f"(d[30]),"+f"(d[31]),"+f"(d[32]),"+f"(d[33]),"+f"(d[34]),"+f"(d[35]),"+f"(d[36]),"+f"(d[37]),"+f"(d[38]),"+f"(d[39]) : "r"(a[0]),"r"(a[1]),"r"(a[2]),"r"(a[3]),"l"(db),"r"(sc));
}
__device__ __forceinline__ void wg_rs96_0(float* d, const uint32_t* a, uint64_t db, int sc) {
  asm volatile("{.reg .pred p; setp.ne.b32 p, %53, 0; wgmma.mma_async.sync.aligned.m64n96k16.f32.bf16.bf16 {%0,%1,%2,%3,%4,%5,%6,%7,%8,%9,%10,%11,%12,%13,%14,%15,%16,%17,%18,%19,%20,%21,%22,%23,%24,%25,%26,%27,%28,%29,%30,%31,%32,%33,%34,%35,%36,%37,%38,%39,%40,%41,%42,%43,%44,%45,%46,%47}, {%48,%49,%50,%51}, %52, p, 1, 1, 0;}"
    : "+f"(d[0]),"+f"(d[1]),"+f"(d[2]),"+f"(d[3]),"+f"(d[4]),"+f"(d[5]),"+f"(d[6]),"+f"(d[7]),"+f"(d[8]),"+f"(d[9]),"+f"(d[10]),"+f"(d[11]),"+f"(d[12]),"+f"(d[13]),"+f"(d[14]),"+f"(d[15]),"+f"(d[16]),"+f"(d[17]),"+f"(d[18]),"+f"(d[19]),"+f"(d[20]),"+f"(d[21]),"+f"(d[22]),"+f"(d[23]),"+f"(d[24]),"+f"(d[25]),"+f"(d[26]),"+f"(d[27]),"+f"(d[28]),"+f"(d[29]),"+f"(d[30]),"+f"(d[31]),"+f"(d[32]),"+f"(d[33]),"+f"(d[34]),"+f"(d[35]),"+f"(d[36]),"+f"(d[37]),"+f"(d[38]),"+f"(d[39]),"+f"(d[40]),"+f"(d[41]),"+f"(d[42]),"+f"(d[43]),"+f"(d[44]),"+f"(d[45]),"+f"(d[46]),"+f"(d[47]) : "r"(a[0]),"r"(a[1]),"r"(a[2]),"r"(a[3]),"l"(db),"r"(sc));
}
__device__ __forceinline__ void wg_rs112_0(float* d, const uint32_t* a, uint64_t db, int sc) {
  asm volatile("{.reg .pred p; setp.ne.b32 p, %61, 0; wgmma.mma_async.sync.aligned.m64n112k16.f32.bf16.bf16 {%0,%1,%2,%3,%4,%5,%6,%7,%8,%9,%10,%11,%12,%13,%14,%15,%16,%17,%18,%19,%20,%21,%22,%23,%24,%25,%26,%27,%28,%29,%30,%31,%32,%33,%34,%35,%36,%37,%38,%39,%40,%41,%42,%43,%44,%45,%46,%47,%48,%49,%50,%51,%52,%53,%54,%55}, {%56,%57,%58,%59}, %60, p, 1, 1, 0;}"
    : "+f"(d[0]),"+f"(d[1]),"+f"(d[2]),"+f"(d[3]),"+f"(d[4]),"+f"(d[5]),"+f"(d[6]),"+f"(d[7]),"+f"(d[8]),"+f"(d[9]),"+f"(d[10]),"+f"(d[11]),"+f"(d[12]),"+f"(d[13]),"+f"(d[14]),"+f"(d[15]),"+f"(d[16]),"+f"(d[17]),"+f"(d[18]),"+f"(d[19]),"+f"(d[20]),"+f"(d[21]),"+f"(d[22]),"+f"(d[23]),"+f"(d[24]),"+f"(d[25]),"+f"(d[26]),"+f"(d[27]),"+f"(d[28]),"+f"(d[29]),"+f"(d[30]),"+f"(d[31]),"+f"(d[32]),"+f"(d[33]),"+f"(d[34]),"+f"(d[35]),"+f"(d[36]),"+f"(d[37]),"+f"(d[38]),"+f"(d[39]),"+f"(d[40]),"+f"(d[41]),"+f"(d[42]),"+f"(d[43]),"+f"(d[44]),"+f"(d[45]),"+f"(d[46]),"+f"(d[47]),"+f"(d[48]),"+f"(d[49]),"+f"(d[50]),"+f"(d[51]),"+f"(d[52]),"+f"(d[53]),"+f"(d[54]),"+f"(d[55]) : "r"(a[0]),"r"(a[1]),"r"(a[2]),"r"(a[3]),"l"(db),"r"(sc));
}
__device__ __forceinline__ void wg_rs128_0(float* d, const uint32_t* a, uint64_t db, int sc) {
  asm volatile("{.reg .pred p; setp.ne.b32 p, %69, 0; wgmma.mma_async.sync.aligned.m64n128k16.f32.bf16.bf16 {%0,%1,%2,%3,%4,%5,%6,%7,%8,%9,%10,%11,%12,%13,%14,%15,%16,%17,%18,%19,%20,%21,%22,%23,%24,%25,%26,%27,%28,%29,%30,%31,%32,%33,%34,%35,%36,%37,%38,%39,%40,%41,%42,%43,%44,%45,%46,%47,%48,%49,%50,%51,%52,%53,%54,%55,%56,%57,%58,%59,%60,%61,%62,%63}, {%64,%65,%66,%67}, %68, p, 1, 1, 0;}"
    : "+f"(d[0]),"+f"(d[1]),"+f"(d[2]),"+f"(d[3]),"+f"(d[4]),"+f"(d[5]),"+f"(d[6]),"+f"(d[7]),"+f"(d[8]),"+f"(d[9]),"+f"(d[10]),"+f"(d[11]),"+f"(d[12]),"+f"(d[13]),"+f"(d[14]),"+f"(d[15]),"+f"(d[16]),"+f"(d[17]),"+f"(d[18]),"+f"(d[19]),"+f"(d[20]),"+f"(d[21]),"+f"(d[22]),"+f"(d[23]),"+f"(d[24]),"+f"(d[25]),"+f"(d[26]),"+f"(d[27]),"+f"(d[28]),"+f"(d[29]),"+f"(d[30]),"+f"(d[31]),"+f"(d[32]),"+f"(d[33]),"+f"(d[34]),"+f"(d[35]),"+f"(d[36]),"+f"(d[37]),"+f"(d[38]),"+f"(d[39]),"+f"(d[40]),"+f"(d[41]),"+f"(d[42]),"+f"(d[43]),"+f"(d[44]),"+f"(d[45]),"+f"(d[46]),"+f"(d[47]),"+f"(d[48]),"+f"(d[49]),"+f"(d[50]),"+f"(d[51]),"+f"(d[52]),"+f"(d[53]),"+f"(d[54]),"+f"(d[55]),"+f"(d[56]),"+f"(d[57]),"+f"(d[58]),"+f"(d[59]),"+f"(d[60]),"+f"(d[61]),"+f"(d[62]),"+f"(d[63]) : "r"(a[0]),"r"(a[1]),"r"(a[2]),"r"(a[3]),"l"(db),"r"(sc));
}
__device__ __forceinline__ void wg_rs144_0(float* d, const uint32_t* a, uint64_t db, int sc) {
  asm volatile("{.reg .pred p; setp.ne.b32 p, %77, 0; wgmma.mma_async.sync.aligned.m64n144k16.f32.bf16.bf16 {%0,%1,%2,%3,%4,%5,%6,%7,%8,%9,%10,%11,%12,%13,%14,%15,%16,%17,%18,%19,%20,%21,%22,%23,%24,%25,%26,%27,%28,%29,%30,%31,%32,%33,%34,%35,%36,%37,%38,%39,%40,%41,%42,%43,%44,%45,%46,%47,%48,%49,%50,%51,%52,%53,%54,%55,%56,%57,%58,%59,%60,%61,%62,%63,%64,%65,%66,%67,%68,%69,%70,%71}, {%72,%73,%74,%75}, %76, p, 1, 1, 0;}"
    : "+f"(d[0]),"+f"(d[1]),"+f"(d[2]),"+f"(d[3]),"+f"(d[4]),"+f"(d[5]),"+f"(d[6]),"+f"(d[7]),"+f"(d[8]),"+f"(d[9]),"+f"(d[10]),"+f"(d[11]),"+f"(d[12]),"+f"(d[13]),"+f"(d[14]),"+f"(d[15]),"+f"(d[16]),"+f"(d[17]),"+f"(d[18]),"+f"(d[19]),"+f"(d[20]),"+f"(d[21]),"+f"(d[22]),"+f"(d[23]),"+f"(d[24]),"+f"(d[25]),"+f"(d[26]),"+f"(d[27]),"+f"(d[28]),"+f"(d[29]),"+f"(d[30]),"+f"(d[31]),"+f"(d[32]),"+f"(d[33]),"+f"(d[34]),"+f"(d[35]),"+f"(d[36]),"+f"(d[37]),"+f"(d[38]),"+f"(d[39]),"+f"(d[40]),"+f"(d[41]),"+f"(d[42]),"+f"(d[43]),"+f"(d[44]),"+f"(d[45]),"+f"(d[46]),"+f"(d[47]),"+f"(d[48]),"+f"(d[49]),"+f"(d[50]),"+f"(d[51]),"+f"(d[52]),"+f"(d[53]),"+f"(d[54]),"+f"(d[55]),"+f"(d[56]),"+f"(d[57]),"+f"(d[58]),"+f"(d[59]),"+f"(d[60]),"+f"(d[61]),"+f"(d[62]),"+f"(d[63]),"+f"(d[64]),"+f"(d[65]),"+f"(d[66]),"+f"(d[67]),"+f"(d[68]),"+f"(d[69]),"+f"(d[70]),"+f"(d[71]) : "r"(a[0]),"r"(a[1]),"r"(a[2]),"r"(a[3]),"l"(db),"r"(sc));
}
__device__ __forceinline__ void wg_rs160_0(float* d, const uint32_t* a, uint64_t db, int sc) {
  asm volatile("{.reg .pred p; setp.ne.b32 p, %85, 0; wgmma.mma_async.sync.aligned.m64n160k16.f32.bf16.bf16 {%0,%1,%2,%3,%4,%5,%6,%7,%8,%9,%10,%11,%12,%13,%14,%15,%16,%17,%18,%19,%20,%21,%22,%23,%24,%25,%26,%27,%28,%29,%30,%31,%32,%33,%34,%35,%36,%37,%38,%39,%40,%41,%42,%43,%44,%45,%46,%47,%48,%49,%50,%51,%52,%53,%54,%55,%56,%57,%58,%59,%60,%61,%62,%63,%64,%65,%66,%67,%68,%69,%70,%71,%72,%73,%74,%75,%76,%77,%78,%79}, {%80,%81,%82,%83}, %84, p, 1, 1, 0;}"
    : "+f"(d[0]),"+f"(d[1]),"+f"(d[2]),"+f"(d[3]),"+f"(d[4]),"+f"(d[5]),"+f"(d[6]),"+f"(d[7]),"+f"(d[8]),"+f"(d[9]),"+f"(d[10]),"+f"(d[11]),"+f"(d[12]),"+f"(d[13]),"+f"(d[14]),"+f"(d[15]),"+f"(d[16]),"+f"(d[17]),"+f"(d[18]),"+f"(d[19]),"+f"(d[20]),"+f"(d[21]),"+f"(d[22]),"+f"(d[23]),"+f"(d[24]),"+f"(d[25]),"+f"(d[26]),"+f"(d[27]),"+f"(d[28]),"+f"(d[29]),"+f"(d[30]),"+f"(d[31]),"+f"(d[32]),"+f"(d[33]),"+f"(d[34]),"+f"(d[35]),"+f"(d[36]),"+f"(d[37]),"+f"(d[38]),"+f"(d[39]),"+f"(d[40]),"+f"(d[41]),"+f"(d[42]),"+f"(d[43]),"+f"(d[44]),"+f"(d[45]),"+f"(d[46]),"+f"(d[47]),"+f"(d[48]),"+f"(d[49]),"+f"(d[50]),"+f"(d[51]),"+f"(d[52]),"+f"(d[53]),"+f"(d[54]),"+f"(d[55]),"+f"(d[56]),"+f"(d[57]),"+f"(d[58]),"+f"(d[59]),"+f"(d[60]),"+f"(d[61]),"+f"(d[62]),"+f"(d[63]),"+f"(d[64]),"+f"(d[65]),"+f"(d[66]),"+f"(d[67]),"+f"(d[68]),"+f"(d[69]),"+f"(d[70]),"+f"(d[71]),"+f"(d[72]),"+f"(d[73]),"+f"(d[74]),"+f"(d[75]),"+f"(d[76]),"+f"(d[77]),"+f"(d[78]),"+f"(d[79]) : "r"(a[0]),"r"(a[1]),"r"(a[2]),"r"(a[3]),"l"(db),"r"(sc));
}
__device__ __forceinline__ void wg_rs176_0(float* d, const uint32_t* a, uint64_t db, int sc) {
  asm volatile("{.reg .pred p; setp.ne.b32 p, %93, 0; wgmma.mma_async.sync.aligned.m64n176k16.f32.bf16.bf16 {%0,%1,%2,%3,%4,%5,%6,%7,%8,%9,%10,%11,%12,%13,%14,%15,%16,%17,%18,%19,%20,%21,%22,%23,%24,%25,%26,%27,%28,%29,%30,%31,%32,%33,%34,%35,%36,%37,%38,%39,%40,%41,%42,%43,%44,%45,%46,%47,%48,%49,%50,%51,%52,%53,%54,%55,%56,%57,%58,%59,%60,%61,%62,%63,%64,%65,%66,%67,%68,%69,%70,%71,%72,%73,%74,%75,%76,%77,%78,%79,%80,%81,%82,%83,%84,%85,%86,%87}, {%88,%89,%90,%91}, %92, p, 1, 1, 0;}"
    : "+f"(d[0]),"+f"(d[1]),"+f"(d[2]),"+f"(d[3]),"+f"(d[4]),"+f"(d[5]),"+f"(d[6]),"+f"(d[7]),"+f"(d[8]),"+f"(d[9]),"+f"(d[10]),"+f"(d[11]),"+f"(d[12]),"+f"(d[13]),"+f"(d[14]),"+f"(d[15]),"+f"(d[16]),"+f"(d[17]),"+f"(d[18]),"+f"(d[19]),"+f"(d[20]),"+f"(d[21]),"+f"(d[22]),"+f"(d[23]),"+f"(d[24]),"+f"(d[25]),"+f"(d[26]),"+f"(d[27]),"+f"(d[28]),"+f"(d[29]),"+f"(d[30]),"+f"(d[31]),"+f"(d[32]),"+f"(d[33]),"+f"(d[34]),"+f"(d[35]),"+f"(d[36]),"+f"(d[37]),"+f"(d[38]),"+f"(d[39]),"+f"(d[40]),"+f"(d[41]),"+f"(d[42]),"+f"(d[43]),"+f"(d[44]),"+f"(d[45]),"+f"(d[46]),"+f"(d[47]),"+f"(d[48]),"+f"(d[49]),"+f"(d[50]),"+f"(d[51]),"+f"(d[52]),"+f"(d[53]),"+f"(d[54]),"+f"(d[55]),"+f"(d[56]),"+f"(d[57]),"+f"(d[58]),"+f"(d[59]),"+f"(d[60]),"+f"(d[61]),"+f"(d[62]),"+f"(d[63]),"+f"(d[64]),"+f"(d[65]),"+f"(d[66]),"+f"(d[67]),"+f"(d[68]),"+f"(d[69]),"+f"(d[70]),"+f"(d[71]),"+f"(d[72]),"+f"(d[73]),"+f"(d[74]),"+f"(d[75]),"+f"(d[76]),"+f"(d[77]),"+f"(d[78]),"+f"(d[79]),"+f"(d[80]),"+f"(d[81]),"+f"(d[82]),"+f"(d[83]),"+f"(d[84]),"+f"(d[85]),"+f"(d[86]),"+f"(d[87]) : "r"(a[0]),"r"(a[1]),"r"(a[2]),"r"(a[3]),"l"(db),"r"(sc));
}
__device__ __forceinline__ void wg_rs192_0(float* d, const uint32_t* a, uint64_t db, int sc) {
  asm volatile("{.reg .pred p; setp.ne.b32 p, %101, 0; wgmma.mma_async.sync.aligned.m64n192k16.f32.bf16.bf16 {%0,%1,%2,%3,%4,%5,%6,%7,%8,%9,%10,%11,%12,%13,%14,%15,%16,%17,%18,%19,%20,%21,%22,%23,%24,%25,%26,%27,%28,%29,%30,%31,%32,%33,%34,%35,%36,%37,%38,%39,%40,%41,%42,%43,%44,%45,%46,%47,%48,%49,%50,%51,%52,%53,%54,%55,%56,%57,%58,%59,%60,%61,%62,%63,%64,%65,%66,%67,%68,%69,%70,%71,%72,%73,%74,%75,%76,%77,%78,%79,%80,%81,%82,%83,%84,%85,%86,%87,%88,%89,%90,%91,%92,%93,%94,%95}, {%96,%97,%98,%99}, %100, p, 1, 1, 0;}"
    : "+f"(d[0]),"+f"(d[1]),"+f"(d[2]),"+f"(d[3]),"+f"(d[4]),"+f"(d[5]),"+f"(d[6]),"+f"(d[7]),"+f"(d[8]),"+f"(d[9]),"+f"(d[10]),"+f"(d[11]),"+f"(d[12]),"+f"(d[13]),"+f"(d[14]),"+f"(d[15]),"+f"(d[16]),"+f"(d[17]),"+f"(d[18]),"+f"(d[19]),"+f"(d[20]),"+f"(d[21]),"+f"(d[22]),"+f"(d[23]),"+f"(d[24]),"+f"(d[25]),"+f"(d[26]),"+f"(d[27]),"+f"(d[28]),"+f"(d[29]),"+f"(d[30]),"+f"(d[31]),"+f"(d[32]),"+f"(d[33]),"+f"(d[34]),"+f"(d[35]),"+f"(d[36]),"+f"(d[37]),"+f"(d[38]),"+f"(d[39]),"+f"(d[40]),"+f"(d[41]),"+f"(d[42]),"+f"(d[43]),"+f"(d[44]),"+f"(d[45]),"+f"(d[46]),"+f"(d[47]),"+f"(d[48]),"+f"(d[49]),"+f"(d[50]),"+f"(d[51]),"+f"(d[52]),"+f"(d[53]),"+f"(d[54]),"+f"(d[55]),"+f"(d[56]),"+f"(d[57]),"+f"(d[58]),"+f"(d[59]),"+f"(d[60]),"+f"(d[61]),"+f"(d[62]),"+f"(d[63]),"+f"(d[64]),"+f"(d[65]),"+f"(d[66]),"+f"(d[67]),"+f"(d[68]),"+f"(d[69]),"+f"(d[70]),"+f"(d[71]),"+f"(d[72]),"+f"(d[73]),"+f"(d[74]),"+f"(d[75]),"+f"(d[76]),"+f"(d[77]),"+f"(d[78]),"+f"(d[79]),"+f"(d[80]),"+f"(d[81]),"+f"(d[82]),"+f"(d[83]),"+f"(d[84]),"+f"(d[85]),"+f"(d[86]),"+f"(d[87]),"+f"(d[88]),"+f"(d[89]),"+f"(d[90]),"+f"(d[91]),"+f"(d[92]),"+f"(d[93]),"+f"(d[94]),"+f"(d[95]) : "r"(a[0]),"r"(a[1]),"r"(a[2]),"r"(a[3]),"l"(db),"r"(sc));
}
__device__ __forceinline__ void wg_ss192_11(float* d, uint64_t da, uint64_t db, int sc) {
  asm volatile("{.reg .pred p; setp.ne.b32 p, %98, 0; wgmma.mma_async.sync.aligned.m64n192k16.f32.bf16.bf16 {%0,%1,%2,%3,%4,%5,%6,%7,%8,%9,%10,%11,%12,%13,%14,%15,%16,%17,%18,%19,%20,%21,%22,%23,%24,%25,%26,%27,%28,%29,%30,%31,%32,%33,%34,%35,%36,%37,%38,%39,%40,%41,%42,%43,%44,%45,%46,%47,%48,%49,%50,%51,%52,%53,%54,%55,%56,%57,%58,%59,%60,%61,%62,%63,%64,%65,%66,%67,%68,%69,%70,%71,%72,%73,%74,%75,%76,%77,%78,%79,%80,%81,%82,%83,%84,%85,%86,%87,%88,%89,%90,%91,%92,%93,%94,%95}, %96, %97, p, 1, 1, 1, 1;}"
    : "+f"(d[0]),"+f"(d[1]),"+f"(d[2]),"+f"(d[3]),"+f"(d[4]),"+f"(d[5]),"+f"(d[6]),"+f"(d[7]),"+f"(d[8]),"+f"(d[9]),"+f"(d[10]),"+f"(d[11]),"+f"(d[12]),"+f"(d[13]),"+f"(d[14]),"+f"(d[15]),"+f"(d[16]),"+f"(d[17]),"+f"(d[18]),"+f"(d[19]),"+f"(d[20]),"+f"(d[21]),"+f"(d[22]),"+f"(d[23]),"+f"(d[24]),"+f"(d[25]),"+f"(d[26]),"+f"(d[27]),"+f"(d[28]),"+f"(d[29]),"+f"(d[30]),"+f"(d[31]),"+f"(d[32]),"+f"(d[33]),"+f"(d[34]),"+f"(d[35]),"+f"(d[36]),"+f"(d[37]),"+f"(d[38]),"+f"(d[39]),"+f"(d[40]),"+f"(d[41]),"+f"(d[42]),"+f"(d[43]),"+f"(d[44]),"+f"(d[45]),"+f"(d[46]),"+f"(d[47]),"+f"(d[48]),"+f"(d[49]),"+f"(d[50]),"+f"(d[51]),"+f"(d[52]),"+f"(d[53]),"+f"(d[54]),"+f"(d[55]),"+f"(d[56]),"+f"(d[57]),"+f"(d[58]),"+f"(d[59]),"+f"(d[60]),"+f"(d[61]),"+f"(d[62]),"+f"(d[63]),"+f"(d[64]),"+f"(d[65]),"+f"(d[66]),"+f"(d[67]),"+f"(d[68]),"+f"(d[69]),"+f"(d[70]),"+f"(d[71]),"+f"(d[72]),"+f"(d[73]),"+f"(d[74]),"+f"(d[75]),"+f"(d[76]),"+f"(d[77]),"+f"(d[78]),"+f"(d[79]),"+f"(d[80]),"+f"(d[81]),"+f"(d[82]),"+f"(d[83]),"+f"(d[84]),"+f"(d[85]),"+f"(d[86]),"+f"(d[87]),"+f"(d[88]),"+f"(d[89]),"+f"(d[90]),"+f"(d[91]),"+f"(d[92]),"+f"(d[93]),"+f"(d[94]),"+f"(d[95]) : "l"(da),"l"(db),"r"(sc));
}
__device__ __forceinline__ void wg_ss192_01(float* d, uint64_t da, uint64_t db, int sc) {
  asm volatile("{.reg .pred p; setp.ne.b32 p, %98, 0; wgmma.mma_async.sync.aligned.m64n192k16.f32.bf16.bf16 {%0,%1,%2,%3,%4,%5,%6,%7,%8,%9,%10,%11,%12,%13,%14,%15,%16,%17,%18,%19,%20,%21,%22,%23,%24,%25,%26,%27,%28,%29,%30,%31,%32,%33,%34,%35,%36,%37,%38,%39,%40,%41,%42,%43,%44,%45,%46,%47,%48,%49,%50,%51,%52,%53,%54,%55,%56,%57,%58,%59,%60,%61,%62,%63,%64,%65,%66,%67,%68,%69,%70,%71,%72,%73,%74,%75,%76,%77,%78,%79,%80,%81,%82,%83,%84,%85,%86,%87,%88,%89,%90,%91,%92,%93,%94,%95}, %96, %97, p, 1, 1, 0, 1;}"
    : "+f"(d[0]),"+f"(d[1]),"+f"(d[2]),"+f"(d[3]),"+f"(d[4]),"+f"(d[5]),"+f"(d[6]),"+f"(d[7]),"+f"(d[8]),"+f"(d[9]),"+f"(d[10]),"+f"(d[11]),"+f"(d[12]),"+f"(d[13]),"+f"(d[14]),"+f"(d[15]),"+f"(d[16]),"+f"(d[17]),"+f"(d[18]),"+f"(d[19]),"+f"(d[20]),"+f"(d[21]),"+f"(d[22]),"+f"(d[23]),"+f"(d[24]),"+f"(d[25]),"+f"(d[26]),"+f"(d[27]),"+f"(d[28]),"+f"(d[29]),"+f"(d[30]),"+f"(d[31]),"+f"(d[32]),"+f"(d[33]),"+f"(d[34]),"+f"(d[35]),"+f"(d[36]),"+f"(d[37]),"+f"(d[38]),"+f"(d[39]),"+f"(d[40]),"+f"(d[41]),"+f"(d[42]),"+f"(d[43]),"+f"(d[44]),"+f"(d[45]),"+f"(d[46]),"+f"(d[47]),"+f"(d[48]),"+f"(d[49]),"+f"(d[50]),"+f"(d[51]),"+f"(d[52]),"+f"(d[53]),"+f"(d[54]),"+f"(d[55]),"+f"(d[56]),"+f"(d[57]),"+f"(d[58]),"+f"(d[59]),"+f"(d[60]),"+f"(d[61]),"+f"(d[62]),"+f"(d[63]),"+f"(d[64]),"+f"(d[65]),"+f"(d[66]),"+f"(d[67]),"+f"(d[68]),"+f"(d[69]),"+f"(d[70]),"+f"(d[71]),"+f"(d[72]),"+f"(d[73]),"+f"(d[74]),"+f"(d[75]),"+f"(d[76]),"+f"(d[77]),"+f"(d[78]),"+f"(d[79]),"+f"(d[80]),"+f"(d[81]),"+f"(d[82]),"+f"(d[83]),"+f"(d[84]),"+f"(d[85]),"+f"(d[86]),"+f"(d[87]),"+f"(d[88]),"+f"(d[89]),"+f"(d[90]),"+f"(d[91]),"+f"(d[92]),"+f"(d[93]),"+f"(d[94]),"+f"(d[95]) : "l"(da),"l"(db),"r"(sc));
}
__device__ __forceinline__ void wg_ss64_11(float* d, uint64_t da, uint64_t db, int sc) {
  asm volatile("{.reg .pred p; setp.ne.b32 p, %34, 0; wgmma.mma_async.sync.aligned.m64n64k16.f32.bf16.bf16 {%0,%1,%2,%3,%4,%5,%6,%7,%8,%9,%10,%11,%12,%13,%14,%15,%16,%17,%18,%19,%20,%21,%22,%23,%24,%25,%26,%27,%28,%29,%30,%31}, %32, %33, p, 1, 1, 1, 1;}"
    : "+f"(d[0]),"+f"(d[1]),"+f"(d[2]),"+f"(d[3]),"+f"(d[4]),"+f"(d[5]),"+f"(d[6]),"+f"(d[7]),"+f"(d[8]),"+f"(d[9]),"+f"(d[10]),"+f"(d[11]),"+f"(d[12]),"+f"(d[13]),"+f"(d[14]),"+f"(d[15]),"+f"(d[16]),"+f"(d[17]),"+f"(d[18]),"+f"(d[19]),"+f"(d[20]),"+f"(d[21]),"+f"(d[22]),"+f"(d[23]),"+f"(d[24]),"+f"(d[25]),"+f"(d[26]),"+f"(d[27]),"+f"(d[28]),"+f"(d[29]),"+f"(d[30]),"+f"(d[31]) : "l"(da),"l"(db),"r"(sc));
}
__device__ __forceinline__ void wg_ss64_01(float* d, uint64_t da, uint64_t db, int sc) {
  asm volatile("{.reg .pred p; setp.ne.b32 p, %34, 0; wgmma.mma_async.sync.aligned.m64n64k16.f32.bf16.bf16 {%0,%1,%2,%3,%4,%5,%6,%7,%8,%9,%10,%11,%12,%13,%14,%15,%16,%17,%18,%19,%20,%21,%22,%23,%24,%25,%26,%27,%28,%29,%30,%31}, %32, %33, p, 1, 1, 0, 1;}"
    : "+f"(d[0]),"+f"(d[1]),"+f"(d[2]),"+f"(d[3]),"+f"(d[4]),"+f"(d[5]),"+f"(d[6]),"+f"(d[7]),"+f"(d[8]),"+f"(d[9]),"+f"(d[10]),"+f"(d[11]),"+f"(d[12]),"+f"(d[13]),"+f"(d[14]),"+f"(d[15]),"+f"(d[16]),"+f"(d[17]),"+f"(d[18]),"+f"(d[19]),"+f"(d[20]),"+f"(d[21]),"+f"(d[22]),"+f"(d[23]),"+f"(d[24]),"+f"(d[25]),"+f"(d[26]),"+f"(d[27]),"+f"(d[28]),"+f"(d[29]),"+f"(d[30]),"+f"(d[31]) : "l"(da),"l"(db),"r"(sc));
}
__device__ __forceinline__ void wg_ss128_11(float* d, uint64_t da, uint64_t db, int sc) {
  asm volatile("{.reg .pred p; setp.ne.b32 p, %66, 0; wgmma.mma_async.sync.aligned.m64n128k16.f32.bf16.bf16 {%0,%1,%2,%3,%4,%5,%6,%7,%8,%9,%10,%11,%12,%13,%14,%15,%16,%17,%18,%19,%20,%21,%22,%23,%24,%25,%26,%27,%28,%29,%30,%31,%32,%33,%34,%35,%36,%37,%38,%39,%40,%41,%42,%43,%44,%45,%46,%47,%48,%49,%50,%51,%52,%53,%54,%55,%56,%57,%58,%59,%60,%61,%62,%63}, %64, %65, p, 1, 1, 1, 1;}"
    : "+f"(d[0]),"+f"(d[1]),"+f"(d[2]),"+f"(d[3]),"+f"(d[4]),"+f"(d[5]),"+f"(d[6]),"+f"(d[7]),"+f"(d[8]),"+f"(d[9]),"+f"(d[10]),"+f"(d[11]),"+f"(d[12]),"+f"(d[13]),"+f"(d[14]),"+f"(d[15]),"+f"(d[16]),"+f"(d[17]),"+f"(d[18]),"+f"(d[19]),"+f"(d[20]),"+f"(d[21]),"+f"(d[22]),"+f"(d[23]),"+f"(d[24]),"+f"(d[25]),"+f"(d[26]),"+f"(d[27]),"+f"(d[28]),"+f"(d[29]),"+f"(d[30]),"+f"(d[31]),"+f"(d[32]),"+f"(d[33]),"+f"(d[34]),"+f"(d[35]),"+f"(d[36]),"+f"(d[37]),"+f"(d[38]),"+f"(d[39]),"+f"(d[40]),"+f"(d[41]),"+f"(d[42]),"+f"(d[43]),"+f"(d[44]),"+f"(d[45]),"+f"(d[46]),"+f"(d[47]),"+f"(d[48]),"+f"(d[49]),"+f"(d[50]),"+f"(d[51]),"+f"(d[52]),"+f"(d[53]),"+f"(d[54]),"+f"(d[55]),"+f"(d[56]),"+f"(d[57]),"+f"(d[58]),"+f"(d[59]),"+f"(d[60]),"+f"(d[61]),"+f"(d[62]),"+f"(d[63]) : "l"(da),"l"(db),"r"(sc));
}
__device__ __forceinline__ void wg_ss128_01(float* d, uint64_t da, uint64_t db, int sc) {
  asm volatile("{.reg .pred p; setp.ne.b32 p, %66, 0; wgmma.mma_async.sync.aligned.m64n128k16.f32.bf16.bf16 {%0,%1,%2,%3,%4,%5,%6,%7,%8,%9,%10,%11,%12,%13,%14,%15,%16,%17,%18,%19,%20,%21,%22,%23,%24,%25,%26,%27,%28,%29,%30,%31,%32,%33,%34,%35,%36,%37,%38,%39,%40,%41,%42,%43,%44,%45,%46,%47,%48,%49,%50,%51,%52,%53,%54,%55,%56,%57,%58,%59,%60,%61,%62,%63}, %64, %65, p, 1, 1, 0, 1;}"
    : "+f"(d[0]),"+f"(d[1]),"+f"(d[2]),"+f"(d[3]),"+f"(d[4]),"+f"(d[5]),"+f"(d[6]),"+f"(d[7]),"+f"(d[8]),"+f"(d[9]),"+f"(d[10]),"+f"(d[11]),"+f"(d[12]),"+f"(d[13]),"+f"(d[14]),"+f"(d[15]),"+f"(d[16]),"+f"(d[17]),"+f"(d[18]),"+f"(d[19]),"+f"(d[20]),"+f"(d[21]),"+f"(d[22]),"+f"(d[23]),"+f"(d[24]),"+f"(d[25]),"+f"(d[26]),"+f"(d[27]),"+f"(d[28]),"+f"(d[29]),"+f"(d[30]),"+f"(d[31]),"+f"(d[32]),"+f"(d[33]),"+f"(d[34]),"+f"(d[35]),"+f"(d[36]),"+f"(d[37]),"+f"(d[38]),"+f"(d[39]),"+f"(d[40]),"+f"(d[41]),"+f"(d[42]),"+f"(d[43]),"+f"(d[44]),"+f"(d[45]),"+f"(d[46]),"+f"(d[47]),"+f"(d[48]),"+f"(d[49]),"+f"(d[50]),"+f"(d[51]),"+f"(d[52]),"+f"(d[53]),"+f"(d[54]),"+f"(d[55]),"+f"(d[56]),"+f"(d[57]),"+f"(d[58]),"+f"(d[59]),"+f"(d[60]),"+f"(d[61]),"+f"(d[62]),"+f"(d[63]) : "l"(da),"l"(db),"r"(sc));
}
__device__ __forceinline__ void wg_ss96_01(float* d, uint64_t da, uint64_t db, int sc) {
  asm volatile("{.reg .pred p; setp.ne.b32 p, %50, 0; wgmma.mma_async.sync.aligned.m64n96k16.f32.bf16.bf16 {%0,%1,%2,%3,%4,%5,%6,%7,%8,%9,%10,%11,%12,%13,%14,%15,%16,%17,%18,%19,%20,%21,%22,%23,%24,%25,%26,%27,%28,%29,%30,%31,%32,%33,%34,%35,%36,%37,%38,%39,%40,%41,%42,%43,%44,%45,%46,%47}, %48, %49, p, 1, 1, 0, 1;}"
    : "+f"(d[0]),"+f"(d[1]),"+f"(d[2]),"+f"(d[3]),"+f"(d[4]),"+f"(d[5]),"+f"(d[6]),"+f"(d[7]),"+f"(d[8]),"+f"(d[9]),"+f"(d[10]),"+f"(d[11]),"+f"(d[12]),"+f"(d[13]),"+f"(d[14]),"+f"(d[15]),"+f"(d[16]),"+f"(d[17]),"+f"(d[18]),"+f"(d[19]),"+f"(d[20]),"+f"(d[21]),"+f"(d[22]),"+f"(d[23]),"+f"(d[24]),"+f"(d[25]),"+f"(d[26]),"+f"(d[27]),"+f"(d[28]),"+f"(d[29]),"+f"(d[30]),"+f"(d[31]),"+f"(d[32]),"+f"(d[33]),"+f"(d[34]),"+f"(d[35]),"+f"(d[36]),"+f"(d[37]),"+f"(d[38]),"+f"(d[39]),"+f"(d[40]),"+f"(d[41]),"+f"(d[42]),"+f"(d[43]),"+f"(d[44]),"+f"(d[45]),"+f"(d[46]),"+f"(d[47]) : "l"(da),"l"(db),"r"(sc));
}
__device__ __forceinline__ void wg_rs64_1(float* d, const uint32_t* a, uint64_t db, int sc) {
  asm volatile("{.reg .pred p; setp.ne.b32 p, %37, 0; wgmma.mma_async.sync.aligned.m64n64k16.f32.bf16.bf16 {%0,%1,%2,%3,%4,%5,%6,%7,%8,%9,%10,%11,%12,%13,%14,%15,%16,%17,%18,%19,%20,%21,%22,%23,%24,%25,%26,%27,%28,%29,%30,%31}, {%32,%33,%34,%35}, %36, p, 1, 1, 1;}"
    : "+f"(d[0]),"+f"(d[1]),"+f"(d[2]),"+f"(d[3]),"+f"(d[4]),"+f"(d[5]),"+f"(d[6]),"+f"(d[7]),"+f"(d[8]),"+f"(d[9]),"+f"(d[10]),"+f"(d[11]),"+f"(d[12]),"+f"(d[13]),"+f"(d[14]),"+f"(d[15]),"+f"(d[16]),"+f"(d[17]),"+f"(d[18]),"+f"(d[19]),"+f"(d[20]),"+f"(d[21]),"+f"(d[22]),"+f"(d[23]),"+f"(d[24]),"+f"(d[25]),"+f"(d[26]),"+f"(d[27]),"+f"(d[28]),"+f"(d[29]),"+f"(d[30]),"+f"(d[31]) : "r"(a[0]),"r"(a[1]),"r"(a[2]),"r"(a[3]),"l"(db),"r"(sc));
}
__device__ __forceinline__ void wg_rs96_1(float* d, const uint32_t* a, uint64_t db, int sc) {
  asm volatile("{.reg .pred p; setp.ne.b32 p, %53, 0; wgmma.mma_async.sync.aligned.m64n96k16.f32.bf16.bf16 {%0,%1,%2,%3,%4,%5,%6,%7,%8,%9,%10,%11,%12,%13,%14,%15,%16,%17,%18,%19,%20,%21,%22,%23,%24,%25,%26,%27,%28,%29,%30,%31,%32,%33,%34,%35,%36,%37,%38,%39,%40,%41,%42,%43,%44,%45,%46,%47}, {%48,%49,%50,%51}, %52, p, 1, 1, 1;}"
    : "+f"(d[0]),"+f"(d[1]),"+f"(d[2]),"+f"(d[3]),"+f"(d[4]),"+f"(d[5]),"+f"(d[6]),"+f"(d[7]),"+f"(d[8]),"+f"(d[9]),"+f"(d[10]),"+f"(d[11]),"+f"(d[12]),"+f"(d[13]),"+f"(d[14]),"+f"(d[15]),"+f"(d[16]),"+f"(d[17]),"+f"(d[18]),"+f"(d[19]),"+f"(d[20]),"+f"(d[21]),"+f"(d[22]),"+f"(d[23]),"+f"(d[24]),"+f"(d[25]),"+f"(d[26]),"+f"(d[27]),"+f"(d[28]),"+f"(d[29]),"+f"(d[30]),"+f"(d[31]),"+f"(d[32]),"+f"(d[33]),"+f"(d[34]),"+f"(d[35]),"+f"(d[36]),"+f"(d[37]),"+f"(d[38]),"+f"(d[39]),"+f"(d[40]),"+f"(d[41]),"+f"(d[42]),"+f"(d[43]),"+f"(d[44]),"+f"(d[45]),"+f"(d[46]),"+f"(d[47]) : "r"(a[0]),"r"(a[1]),"r"(a[2]),"r"(a[3]),"l"(db),"r"(sc));
}
__device__ __forceinline__ void wg_ss160_01(float* d, uint64_t da, uint64_t db, int sc) {
  asm volatile("{.reg .pred p; setp.ne.b32 p, %82, 0; wgmma.mma_async.sync.aligned.m64n160k16.f32.bf16.bf16 {%0,%1,%2,%3,%4,%5,%6,%7,%8,%9,%10,%11,%12,%13,%14,%15,%16,%17,%18,%19,%20,%21,%22,%23,%24,%25,%26,%27,%28,%29,%30,%31,%32,%33,%34,%35,%36,%37,%38,%39,%40,%41,%42,%43,%44,%45,%46,%47,%48,%49,%50,%51,%52,%53,%54,%55,%56,%57,%58,%59,%60,%61,%62,%63,%64,%65,%66,%67,%68,%69,%70,%71,%72,%73,%74,%75,%76,%77,%78,%79}, %80, %81, p, 1, 1, 0, 1;}"
    : "+f"(d[0]),"+f"(d[1]),"+f"(d[2]),"+f"(d[3]),"+f"(d[4]),"+f"(d[5]),"+f"(d[6]),"+f"(d[7]),"+f"(d[8]),"+f"(d[9]),"+f"(d[10]),"+f"(d[11]),"+f"(d[12]),"+f"(d[13]),"+f"(d[14]),"+f"(d[15]),"+f"(d[16]),"+f"(d[17]),"+f"(d[18]),"+f"(d[19]),"+f"(d[20]),"+f"(d[21]),"+f"(d[22]),"+f"(d[23]),"+f"(d[24]),"+f"(d[25]),"+f"(d[26]),"+f"(d[27]),"+f"(d[28]),"+f"(d[29]),"+f"(d[30]),"+f"(d[31]),"+f"(d[32]),"+f"(d[33]),"+f"(d[34]),"+f"(d[35]),"+f"(d[36]),"+f"(d[37]),"+f"(d[38]),"+f"(d[39]),"+f"(d[40]),"+f"(d[41]),"+f"(d[42]),"+f"(d[43]),"+f"(d[44]),"+f"(d[45]),"+f"(d[46]),"+f"(d[47]),"+f"(d[48]),"+f"(d[49]),"+f"(d[50]),"+f"(d[51]),"+f"(d[52]),"+f"(d[53]),"+f"(d[54]),"+f"(d[55]),"+f"(d[56]),"+f"(d[57]),"+f"(d[58]),"+f"(d[59]),"+f"(d[60]),"+f"(d[61]),"+f"(d[62]),"+f"(d[63]),"+f"(d[64]),"+f"(d[65]),"+f"(d[66]),"+f"(d[67]),"+f"(d[68]),"+f"(d[69]),"+f"(d[70]),"+f"(d[71]),"+f"(d[72]),"+f"(d[73]),"+f"(d[74]),"+f"(d[75]),"+f"(d[76]),"+f"(d[77]),"+f"(d[78]),"+f"(d[79]) : "l"(da),"l"(db),"r"(sc));
}
__device__ __forceinline__ void wg_rs160_1(float* d, const uint32_t* a, uint64_t db, int sc) {
  asm volatile("{.reg .pred p; setp.ne.b32 p, %85, 0; wgmma.mma_async.sync.aligned.m64n160k16.f32.bf16.bf16 {%0,%1,%2,%3,%4,%5,%6,%7,%8,%9,%10,%11,%12,%13,%14,%15,%16,%17,%18,%19,%20,%21,%22,%23,%24,%25,%26,%27,%28,%29,%30,%31,%32,%33,%34,%35,%36,%37,%38,%39,%40,%41,%42,%43,%44,%45,%46,%47,%48,%49,%50,%51,%52,%53,%54,%55,%56,%57,%58,%59,%60,%61,%62,%63,%64,%65,%66,%67,%68,%69,%70,%71,%72,%73,%74,%75,%76,%77,%78,%79}, {%80,%81,%82,%83}, %84, p, 1, 1, 1;}"
    : "+f"(d[0]),"+f"(d[1]),"+f"(d[2]),"+f"(d[3]),"+f"(d[4]),"+f"(d[5]),"+f"(d[6]),"+f"(d[7]),"+f"(d[8]),"+f"(d[9]),"+f"(d[10]),"+f"(d[11]),"+f"(d[12]),"+f"(d[13]),"+f"(d[14]),"+f"(d[15]),"+f"(d[16]),"+f"(d[17]),"+f"(d[18]),"+f"(d[19]),"+f"(d[20]),"+f"(d[21]),"+f"(d[22]),"+f"(d[23]),"+f"(d[24]),"+f"(d[25]),"+f"(d[26]),"+f"(d[27]),"+f"(d[28]),"+f"(d[29]),"+f"(d[30]),"+f"(d[31]),"+f"(d[32]),"+f"(d[33]),"+f"(d[34]),"+f"(d[35]),"+f"(d[36]),"+f"(d[37]),"+f"(d[38]),"+f"(d[39]),"+f"(d[40]),"+f"(d[41]),"+f"(d[42]),"+f"(d[43]),"+f"(d[44]),"+f"(d[45]),"+f"(d[46]),"+f"(d[47]),"+f"(d[48]),"+f"(d[49]),"+f"(d[50]),"+f"(d[51]),"+f"(d[52]),"+f"(d[53]),"+f"(d[54]),"+f"(d[55]),"+f"(d[56]),"+f"(d[57]),"+f"(d[58]),"+f"(d[59]),"+f"(d[60]),"+f"(d[61]),"+f"(d[62]),"+f"(d[63]),"+f"(d[64]),"+f"(d[65]),"+f"(d[66]),"+f"(d[67]),"+f"(d[68]),"+f"(d[69]),"+f"(d[70]),"+f"(d[71]),"+f"(d[72]),"+f"(d[73]),"+f"(d[74]),"+f"(d[75]),"+f"(d[76]),"+f"(d[77]),"+f"(d[78]),"+f"(d[79]) : "r"(a[0]),"r"(a[1]),"r"(a[2]),"r"(a[3]),"l"(db),"r"(sc));
}
__device__ __forceinline__ void wg_ss8_10(float* d, uint64_t da, uint64_t db, int sc) {
  asm volatile("{.reg .pred p; setp.ne.b32 p, %6, 0; wgmma.mma_async.sync.aligned.m64n8k16.f32.bf16.bf16 {%0,%1,%2,%3}, %4, %5, p, 1, 1, 1, 0;}"
    : "+f"(d[0]),"+f"(d[1]),"+f"(d[2]),"+f"(d[3]) : "l"(da),"l"(db),"r"(sc));
}
__device__ __forceinline__ void wg_ss8_if(float* d, uint64_t da, uint64_t db, int sc, int skip) {
  asm volatile("{.reg .pred p, q; setp.ne.b32 p, %6, 0; setp.eq.b32 q, %7, 0; @q wgmma.mma_async.sync.aligned.m64n8k16.f32.bf16.bf16 {%0,%1,%2,%3}, %4, %5, p, 1, 1, 1, 0;}"
    : "+f"(d[0]),"+f"(d[1]),"+f"(d[2]),"+f"(d[3]) : "l"(da),"l"(db),"r"(sc),"r"(skip));
}

constexpr uint32_t DB = 1024;
constexpr int UNIT = 8192, WSLOT = 16384, W2TILE = 24576, OFF_R = 12 * UNIT;
constexpr int OFF_PB = 26 * UNIT;
constexpr int OFF_CV = OFF_PB + 16384, OFF_ST = OFF_CV + 768, OFF_TS = OFF_ST + 256, OFF_MODR = OFF_TS + 512, OFF_ROLE = OFF_MODR + 80, OFF_BAR = OFF_ROLE + 16, SMEM_BYTES = OFF_BAR + 1368;
constexpr int OFF_BX = OFF_PB, OFF_AX = OFF_BX + 12288, OFF_RT = OFF_AX + 2048, OFF_GB = OFF_RT + 512, OFF_CO = OFF_CV;
constexpr int OFF_UV = 4 * UNIT, OFF_SX = 24 * UNIT, OFF_XCH = 12 * UNIT;
constexpr int OFF_Q = 99328, KV_V = 4096, KV_H = 8192, F_E = 128, F_O = 4288, OFF_WM = 20 * UNIT, OFF_TAP = 12672, OFF_MR = 25 * UNIT;
constexpr uint64_t pk5(int a, int b, int c, int d, int e) { return (uint64_t)(a / 128) | (uint64_t)(b / 128) << 12 | (uint64_t)(c / 128) << 24 | (uint64_t)(d / 128) << 36 | (uint64_t)(e / 128) << 48; }
constexpr uint64_t T_KV = pk5(119808, 16384, 130048, 65536, 49152), T_F = pk5(140288, 90368, 148736, 81920, OFF_PB), T_X = pk5(0, 4224, 8448, 0, 4224),
                   T_P = pk5(32768, 16384, 65536, 81920, OFF_PB);
__host__ __device__ __forceinline__ uint32_t tab(uint64_t t, int c) { return ((uint32_t)(t >> (12 * c)) & 0xFFF) << 7; }
enum { B_KV = 0, B_FRAW = 5, B_Q = 10, B_WM = 15, B_XR = 17, B_MR = B_XR + 5, B_QTOK, B_ST1, B_MODR, B_ROLE = B_MODR + 5, B_FL = 32, B_PFULL = B_FL + 5, B_PEMPTY = B_PFULL + 5, B_FRDY = B_PEMPTY + 5,
       B_G = B_FRDY + 5, B_EXT = B_G + 2, B_QTD, B_ED, B_S2 = B_ED + 2, B_GB, B_FULL = 60, B_RETRY = B_FULL + 43, B_XFREE = B_RETRY + 8, B_BX, B_UVB, B_CO, B_SX, B_EMPTY = 121, B_SC = 164, B_STD = B_SC + 5, B_LAG };
static_assert(B_ROLE < B_FL && B_GB < B_FULL && B_SX + 5 <= B_EMPTY - 1 && OFF_MR == OFF_SX + 8192 && SMEM_BYTES <= 232448, "barrier groups");
#define BAR(i) (base + OFF_BAR + 8 * (i))

struct Maps { CUtensorMap km, v, q, fm, wmp, kh, tap, wm, w1a, w3a, xs, w1u, w3u, w1b, w3b, x1s, x1b, w2a, w2b, outa, outb; };
struct Ptrs { const bf16 *c, *ssmd; Scratch* g; uint64_t prog[2]; uint32_t gate[5]; int ulo; uint32_t mq, xh, xdep, hstart, hpause, hl[8], uvd, mpos, wt0, wpace; float one; uint32_t wdep[30], adep[14]; uint2 w2t[12]; int hid[3][9]; };

#define REGION_IDS int tid, lane, bid; \
  asm volatile("mov.u32 %0, %%tid.x;" : "=r"(tid)); asm volatile("mov.u32 %0, %%laneid;" : "=r"(lane)); asm volatile("mov.u32 %0, %%ctaid.x;" : "=r"(bid)); \
  const int i0 = tid & 127; (void)i0; (void)lane; (void)bid

#define ffn_role(h, j, r) do { \
  mbar_wait(BAR(B_ROLE)); \
  r = __shfl_sync(~0u, lds32(base + OFF_ROLE), 0); \
  asm volatile("mov.u32 %0, %%ctaid.x;" : "=r"(h)); \
  h &= 1; j = r >> 4; r &= 15; } while (0)
__device__ __forceinline__ void rank_pair(Scratch* G, uint32_t base, uint32_t epoch, bool put) {
  REGION_IDS;
  uint32_t t;
  asm volatile("mov.u32 %0, %%smid;" : "=r"(t));
  t >>= 1;
  const uint32_t q = (t - 32) * 37 >> 8, g = t < 32 ? t & 7 : t < 60 ? t - 31 - 7 * q : t < 62 ? t - 54 : 0;
  const uint32_t key = epoch << 20 | (g & 3) << 18 | (g & 4) << 15 | (t & 127) << 6 | bid >> 1;
  if (put) {
    if (lane == (bid & 1) * 99) publish(&G->key[bid >> 1], key);
    return;
  }
  uint2 x;
  int it = 0;
#pragma unroll 1
  do x = ld_relaxed64(&G->key[2 * lane]); while (__any_sync(~0u, ((x.x ^ key) | (x.y ^ key)) >> 20) && ++it < SPIN_LIMIT);
  sts32(base + OFF_ROLE, __popc(__ballot_sync(~0u, x.x < key)) + __popc(__ballot_sync(~0u, x.y < key)));
  arrive1(BAR(B_ROLE));
}
__device__ __forceinline__ int mod_ch(int p) { return p < 40 ? (p >> 3) * 128 + (p & 1) * 64 : 64 * (p < 50 ? p - 40 : p - 50); }
__device__ __forceinline__ int mod_col(int p) { return mod_ch(p) + 640 * (p < 40 ? 0x4210 >> (2 * (p & 6)) & 7 : p < 50 ? 3 : 5); }
__device__ __forceinline__ uint32_t mod_sum(uint2 v) { return pack_bf16(0.f, __uint_as_float(v.x) + __uint_as_float(v.y)); }
#define UVS 5
#define XP 2
#define GA 3
#define GB 1
#define HL 0
#define EH 0
#define MG 4
#define SG 0x88
#define LAG2 38
#define NP 8
__device__ __forceinline__ int nib(uint32_t t, int i) { return (t >> (4 * i)) & 15; }
__device__ __forceinline__ int w_block(int up, int m) { return m < 2 ? 2 * up + m : 4 + up; }
__host__ __device__ constexpr int w2_at(int v) { return UNIT * (v == 1 ? 0 : 0x0811030C18ull >> (v - (v > 1)) % 5 * 8 & 255); }
__host__ __device__ constexpr int hid_at(int m, int g) { return UNIT * ((g ? 0x0200150710ull : 0x010B14060Full) >> m % 5 * 8 & 255); }
__host__ __device__ constexpr int x1_at(int k) { return k < 4 ? 22 * UNIT + 4096 * k : OFF_BX + UNIT; }
__host__ __device__ constexpr uint32_t w2_desc(int v) { return (DB + w2_at(v)) >> 4 | UNIT << 12; }
__host__ __device__ constexpr int a_at(int n) { return WSLOT * (0x54323251041032ull >> 4 * n & 15); }
__host__ __device__ constexpr int second(int v) { return 0xDCBA657498ull >> 4 * v & 15; }

#define ORDER "k1v1f0q0q1q2q3q4k2v2f1k3v3f2k4v4f3w0f4"
constexpr int NL = sizeof(ORDER) / 2, NG = 2, TA = 16, M8 = 3 << TA / 8;
__host__ __device__ constexpr int load_bar(int e) { return e < 0 ? B_KV : ORDER[2 * e + 1] - '0' + (ORDER[2 * e] == 'q' ? B_Q : ORDER[2 * e] == 'f' ? B_FRAW : ORDER[2 * e] == 'w' ? B_WM : B_KV); }
template <int E> __device__ __forceinline__ void loads(const Ptrs& P, const Maps& maps, uint32_t base) {
  if constexpr (E < NL) {
    constexpr int r = ORDER[2 * E + 1] - '0';
    constexpr char x = ORDER[2 * E];
    const int c0 = 128 * r + 64 * (blockIdx.x & 1), c1 = 2 * (blockIdx.x & 126);
    const uint32_t g = P.gate[E / 4] >> 8 * (E & 3) & 255;
    if (E >= NG) mbar_wait(BAR(opaque(g >> 1)), g & 1);
    if (elect()) {
      if (x == 'k') { tma3d(base + tab(T_KV, r), &maps.km, c0, c1, 0, BAR(B_KV + r)); tma3d(base + tab(T_KV, r) + KV_H, &maps.kh, c0, c1 - 1, 5, BAR(B_KV + r)); }
      if (x == 'v') tma3d(base + tab(T_KV, r) + KV_V, &maps.v, c0, c1, 0, BAR(B_KV + r));
      if (x == 'q') tma3d(base + OFF_Q + 4096 * r, &maps.q, c0, c1, 0, BAR(B_Q + r));
      if (x == 'f') tma3d(base + tab(T_F, r) + F_E, &maps.fm, 0, 0, 128 * r + blockIdx.x, BAR(B_FRAW + r));
      if (x == 'w') tma3d(base + OFF_WM, &maps.wmp, mod_col(TA + (blockIdx.x >> 3)), 80 * (blockIdx.x & 7), 0, BAR(B_WM));
    }
    loads<E + 1>(P, maps, base);
  }
}

template <int U> __device__ __forceinline__ void cstep(float* acc, const uint32_t* A, uint64_t db) {
  const uint32_t* a = A + 4 * U;
  const uint64_t d = db + 16 * U;
  if (U == 4) { wg_rs64_0(acc + 96, A, db + 192, 0); wg_rs48_0(acc + 96, A + 4, db + 208, 1); wg_rs32_0(acc + 96, A + 8, db + 224, 1); wg_rs16_0(acc + 96, A + 12, db + 240, 1); }
  if (U <= 4) wg_rs192_0(acc, a, d, U);
  if (U == 5) wg_rs176_0(acc, a, d, 1);
  if (U == 6) wg_rs160_0(acc, a, d, 1);
  if (U == 7) wg_rs144_0(acc, a, d, 1);
  if (U == 8) wg_rs128_0(acc, a, d, 1);
  if (U == 9) wg_rs112_0(acc, a, d, 1);
  if (U == 10) wg_rs96_0(acc, a, d, 1);
  if (U == 11) wg_rs80_0(acc, a, d, 1);
  if (U == 12) wg_rs64_0(acc, a, d, 1);
  if (U == 13) wg_rs48_0(acc, a, d, 1);
  if (U == 14) wg_rs32_0(acc, a, d, 1);
  if (U == 15) wg_rs16_0(acc, a, d, 1);
}
template <int U0, int U1> __device__ __forceinline__ void csteps(float* acc, const uint32_t* A, uint64_t db) {
  cstep<U0>(acc, A, db);
  if constexpr (U0 > U1) csteps<U0 - 1, U1>(acc, A, db);
}
template <int U0, int U1> __device__ __forceinline__ void cload(uint32_t* A, uint32_t fa) {
  asm volatile("{ld.shared.b32 %0, [%4+%5]; ld.shared.b32 %1, [%4+%5+128]; ld.shared.b32 %2, [%4+%5+16]; ld.shared.b32 %3, [%4+%5+144];}"
               : "=r"(A[4 * U0]), "=r"(A[4 * U0 + 1]), "=r"(A[4 * U0 + 2]), "=r"(A[4 * U0 + 3]) : "r"(fa), "n"(256 * U0) : "memory");
  if constexpr (U0 > U1) cload<U0 - 1, U1>(A, fa);
}

template <int NK> __device__ __forceinline__ void mod_gemv(Scratch* G, uint32_t wm, int p, int part, int w, int lane, uint32_t par) {
  float d[4] = {};
  fence_regs(d);
  wg_fence();
#pragma unroll 1
  for (int k = 0; k < NK; k += 5) {
#pragma unroll
    for (int i = 0; i < 5; i++) wg_ss8_10(d, mkdesc(DB + wm + 2048 * (k + i), 16, 1024, 1), mkdesc(DB + OFF_CV + 32 * (k + i), 16, 128, 0), 1);
  }
  wg_commit();
  const int ch = mod_ch(p) + 16 * w + (lane >> 2);
  uint32_t* dst = (p < 40 ? &G->modc[ch & 127][p >> 3][4 * (p & 6)] : (uint32_t*)&G->modv[p >= 50][ch]) + part;
  wg_wait<0>();
  fence_regs(d);
  if (!(lane & 3)) {
    publish(dst, (__float_as_uint(d[0]) & ~1u) | par);
    publish(dst + (p < 40 ? 1280 : 16), (__float_as_uint(d[2]) & ~1u) | par);
    if (NK == 20 && p < 40 && (p & 6) == 6) {
      dst = (uint32_t*)&G->modv[2][ch] + part;
      publish(dst, (__float_as_uint(d[0]) & ~1u) | par);
      publish(dst + 16, (__float_as_uint(d[2]) & ~1u) | par);
    }
  }
}
__device__ __forceinline__ void mod_fetch(Scratch* G, uint32_t base, uint32_t epoch, uint32_t m8, uint32_t c, uint32_t c1) {
  REGION_IDS;
  const uint32_t* mp = &G->modc[bid][0][lane];
  auto unused = [&]() { return (lane & 6) && !(m8 >> c & 1); };
#pragma unroll 1
  for (int it = 0; c < c1 && it < SPIN_LIMIT; it++) {
    uint32_t m = ld_relaxed32(mp + 32 * c);
    const uint32_t m1 = ld_relaxed32(mp + 32 * min(c + 1, c1 - 1));
#pragma unroll 1
    for (int k = 0; k < 2 && c < c1 && __all_sync(~0u, unused() || !((m ^ epoch) & 1)); k++) {
      float x = unused() ? 0.f : __uint_as_float(m);
      x += __shfl_xor_sync(~0u, x, 1); x += __shfl_xor_sync(~0u, x, 2); x += __shfl_xor_sync(~0u, x, 4);
      const uint32_t y = __byte_perm(badd2(pack_bf16(0.f, x), (lane & 8) * 0x07F00000u), 0, 0x3232), ga = __shfl_sync(~0u, y, 16);
      sts32(base + OFF_MODR + 16 * c + 4 * (lane >> 3), lane < 16 ? bmul2(y, ga) : y);
      arrive1(BAR(B_MODR + c));
      if (lane >= 30 && (m8 >> c & 1)) publish((uint32_t*)&G->modv[2][128 * c + bid] + (lane & 1), ((lane & 1 ? 0 : __float_as_uint(x)) & ~1u) | (epoch & 1));
      m = m1;
      c++;
    }
  }
}
__device__ __forceinline__ void add4(uint4& y, const uint4& z) { y.x = badd2(y.x, z.x); y.y = badd2(y.y, z.y); y.z = badd2(y.z, z.z); y.w = badd2(y.w, z.w); }
template <bool FIRST> __device__ __forceinline__ void e_round(Scratch* G, uint32_t base, uint32_t sa, uint4*& gp, uint4* q, int c, int w, uint32_t tag, uint32_t epoch) {
  constexpr int QO = -D_ * 256;
  mbar_wait(BAR(B_MODR + c));
  const uint4 co = lds128(base + OFF_MODR + 16 * c);
  mbar_wait(BAR(B_PFULL + c));
  const uint32_t pb = sa + tab(T_P, c);
  uint4 l[2][6];
  auto load = [&](int hf, int k) { l[hf][k] = lds128((k < 4 ? pb + 4096 * k : sa + OFF_MR + 4096 * (k - 4)) + 2048 * hf); };
#pragma unroll
  for (int hf = 0; hf < 2; hf++) {
    uint4 &y = l[hf][0], &z = l[hf][4], &m = l[hf][5];
    load(hf, 0);
    if (!FIRST) {
      load(hf, 1);
      add4(y, l[hf][1]);
      load(hf, 2); load(hf, 3);
      add4(l[hf][2], l[hf][3]);
      add4(y, l[hf][2]);
    }
    load(hf, 4); load(hf, 5);
    if (FIRST) {
#pragma unroll 1
      for (int it = 0; __any_sync(~0u, ((z.x >> 15 ^ epoch) | (m.x ^ epoch)) & tag) && it < SPIN_LIMIT; it++) {
        const uint4* sp = (const uint4*)G->st1 + (opaque(sa) - base >> 4) + 128 * hf;
        z = ld_relaxed128(sp);
        m = ld_relaxed128(sp + 256);
        sts128(sa + OFF_MR + 2048 * hf, z.x, z.y, z.z, z.w);
        sts128(sa + OFF_MR + 2048 * hf + 4096, m.x, m.y, m.z, m.w);
      }
      z.x &= 0xFFFF7FFFu;
      sts32(sa + OFF_MR + 2048 * hf, z.x);
    }
#pragma unroll 1
    for (int it = 0; __any_sync(~0u, (q[hf].x ^ epoch) & tag) && it < SPIN_LIMIT; it++) {
      q[hf] = ld_relaxed128(gp + QO + 128 * hf);
    }
    y.x = bfma2(bfma2(bfma2(q[hf].x, z.x, m.x), co.y, co.x), y.x, q[hf].x);
    auto hint = [&]() {
      __syncwarp();
      asm volatile("{.reg .pred p; elect.sync _|p, 0xffffffff; @p red.relaxed.gpu.global.add.u32 [%0], 1; @p mbarrier.arrive.shared::cta.b64 _, [%1];}"
                   ::"l"(G->xsh[c][2 * w + (blockIdx.x >> 6)]), "r"(BAR(B_PEMPTY + c)), "r"(y.x) : "memory");
    };
    if (hf && !EH) hint();
    y.y = bfma2(bfma2(bfma2(q[hf].y, z.y, m.y), co.y, co.x), y.y, q[hf].y);
    y.z = bfma2(bfma2(bfma2(q[hf].z, z.z, m.z), co.y, co.x), y.z, q[hf].z);
    y.w = bfma2(bfma2(bfma2(q[hf].w, z.w, m.w), co.y, co.x), y.w, q[hf].w);
    st_relaxed128(gp + 128 * hf, set_tag(bmul2(y.x, co.w), tag, epoch), bmul2(y.y, co.w), bmul2(y.z, co.w), bmul2(y.w, co.w));
    if (hf && EH == 1) hint();
    asm volatile("{.reg .pred p; .reg .b32 t; setp.ne.u32 p, %5, 0; max.u32 t, %1, 1; @!p st.relaxed.gpu.global.v4.u32 [%0+%6], {t,%2,%3,%4}; @p st.relaxed.gpu.global.v4.u32 [%0+%7], {t,%2,%3,%4};}"
                 ::"l"(gp + 128 * hf), "r"(y.x), "r"(y.y), "r"(y.z), "r"(y.w), "r"(epoch & 1), "n"(D_ * 4096), "n"(D_ * 8192) : "memory");
    if (hf && EH == 2) hint();
    if (c < 4) q[hf] = ld_relaxed128(gp + QO + 32768 + 128 * hf);
  }
  gp += 32768;
}
__device__ __forceinline__ void q_stats(uint32_t base, int w) {
  REGION_IDS;
  float s0 = 0.f, s1 = 0.f, q0 = 0.f, q1 = 0.f;
  const uint32_t a = OFF_Q + 1024 * w + 128 * (lane & 7) + (((lane >> 3) ^ (lane & 7)) << 4);
  const uint32_t ra = mapa(base + OFF_ST + 128 * (bid & 1) + 64 * (lane & 1) + 16 * w + 8 * (lane >> 2), lane >> 1 & 1), rb = mapa(BAR(B_ST1), lane >> 1 & 1);
  if (w == 3 && elect()) mbar_expect_tx(BAR(B_ST1), 256);
#pragma unroll 1
  for (int k = 0; k < 5; k++) {
    mbar_wait(BAR(B_Q + k));
    const uint32_t o = opaque(base + 4096 * k);
    const uint4 x = lds128(o + a), y = lds128(o + (a ^ 64));
    const uint32_t e[8] = {x.x, x.y, x.z, x.w, y.x, y.y, y.z, y.w};
#pragma unroll
    for (int i = 0; i < 8; i++) { const float lo = bf_lo(e[i]), hi = bf_hi(e[i]); s0 += lo; s1 += hi; q0 = fmaf(lo, lo, q0); q1 = fmaf(hi, hi, q1); }
  }
  s0 += s1; q0 += q1;
  arrive1(BAR(B_STD));
  s0 += __shfl_xor_sync(~0u, s0, 8); q0 += __shfl_xor_sync(~0u, q0, 8);
  s0 += __shfl_xor_sync(~0u, s0, 16); q0 += __shfl_xor_sync(~0u, q0, 16);
  if (lane < 8) asm volatile("st.async.shared::cluster.mbarrier::complete_tx::bytes.v2.b32 [%0], {%1,%2}, [%3];" ::"r"(ra), "r"(__float_as_uint(s0)), "r"(__float_as_uint(q0)), "r"(rb) : "memory");
}
__device__ __forceinline__ void short_conv(Scratch* G, uint32_t base, int s, int w, uint32_t par, uint32_t xh) {
  REGION_IDS;
  const uint32_t a = base + tab(T_KV, s) + 128 * (lane & 3) + ((w ^ (lane & 3)) << 4) + 4 * (lane & 16) + (lane & 12), keep = ~(lane & 1);
  uint4* dst = G->xr + (128 * s + 64 * (bid & 1) + 8 * w + 2 * (lane & 16) + (lane >> 1 & 6)) * 256 + 255 - 4 * (bid >> 1) - (lane & 3);
  mbar_wait(BAR(B_KV));
  mbar_wait(BAR(B_KV + s));
  const uint4 wv = lds128(base + OFF_TAP + 512 * s + 64 * w + 16 * (lane & 16) + 4 * (lane & 12));
  uint32_t kk[11], r[8];
#pragma unroll
  for (int k = 0; k < 11; k++) kk[k] = k < 3 ? lds32((a ^ (64 * (k & 1))) + KV_H + 512 * k) : lds32((a ^ (64 * (~k & 1))) + 512 * (k - 3));
  if (xh == 0 && elect()) red_hint(G->hint[s][4 * (bid & 1) + w]);
#pragma unroll
  for (int k = 0; k < 8; k++) r[k] = lds32((a ^ (64 * (k & 1))) + KV_V + 512 * k);
  arrive1(BAR(B_SC + s));
  const uint32_t w0 = __byte_perm(wv.x, wv.z, 0x5410), w1 = __byte_perm(wv.x, wv.z, 0x7632),
                 w2 = __byte_perm(wv.y, wv.w, 0x5410), w3 = __byte_perm(wv.y, wv.w, 0x7632);
#pragma unroll
  for (int k = 0; k < 8; k++) r[k] = bmul2(bfma2(kk[k + 3], w0, bfma2(kk[k + 2], w1, bfma2(kk[k + 1], w2, bmul2(kk[k], w3)))), r[k]);
  const uint32_t bit = ~par >> 7 & lane & 1;
  if (xh == 1 && elect()) red_hint(G->hint[s][4 * (bid & 1) + w]);
  st_relaxed128(dst, (__byte_perm(r[7], r[6], 0x5410) & keep) | bit, __byte_perm(r[5], r[4], 0x5410), __byte_perm(r[3], r[2], 0x5410), __byte_perm(r[1], r[0], 0x5410));
  st_relaxed128(dst + 256, (__byte_perm(r[7], r[6], 0x7632) & keep) | bit, __byte_perm(r[5], r[4], 0x7632), __byte_perm(r[3], r[2], 0x7632), __byte_perm(r[1], r[0], 0x7632));
  if (xh == 2 && elect()) red_hint(G->hint[s][4 * (bid & 1) + w]);
}
__device__ __forceinline__ void silu_vector(const bf16* c, int n, uint32_t base) {
  REGION_IDS;
  if (tid < n) {
    const uint32_t x = ldg32(c + 2 * tid);
    sts32(base + OFF_CV + 4 * tid, pack_bf16(silu_f(bf_lo(x)), silu_f(bf_hi(x))));
  }
  fence_async_smem();
}

template <int FIRST> __global__ void __cluster_dims__(2, 1, 1) __launch_bounds__(512, 1) k_fused(const __grid_constant__ Ptrs P, const __grid_constant__ Maps maps) {
  Scratch* const G = P.g;
  extern __shared__ __align__(1024) uint8_t smem_raw[];
  const uint32_t t_start = clock();
  const uint32_t base = __shfl_sync(~0u, smem_u32(smem_raw), 0);
  if (threadIdx.x == 416 && blockIdx.x + FIRST < 128) {
    const int c0 = 64 * (blockIdx.x & 1), c1 = 2 * (blockIdx.x & 126);
    mbar_init<1>(BAR(B_KV), 1);
    mbar_expect_tx(BAR(B_KV), 12288);
    tma3d(base + tab(T_KV, 0), &maps.km, c0, c1, 0, BAR(B_KV));
    tma3d(base + tab(T_KV, 0) + KV_V, &maps.v, c0, c1, 0, BAR(B_KV));
    tma3d(base + tab(T_KV, 0) + KV_H, &maps.kh, c0, c1 - 1, 5, BAR(B_KV));
    tma3d(base + OFF_TAP, &maps.tap, 0, blockIdx.x & 1, 0, BAR(B_KV));
  }
  if ((base & 0xFFFFFFu) != DB) __trap();
  const int wid = __shfl_sync(~0u, threadIdx.x >> 5, 0), wg = wid >> 2, w = wid & 3;
  if (blockIdx.x + FIRST >= 128) {
    REGION_IDS;
    auto unit = [&](int n) { return 4 * (P.hl[n >> 2] >> 8 * (n & 3) & 255) + (bid & 3); };
    auto fetch = [&](int n, int b) {
      if (unit(n) < 120 && elect()) {
        mbar_expect_tx(BAR(n), 40960);
#pragma unroll 1
        for (int k = 0; k < 5; k++) tma3d(base + 40960 * b + 8192 * k, &maps.wm, mod_col(unit(n) >> 1), 320 * (bid & 1) + 64 * k, 0, BAR(n));
      }
    };
    if (wid == 0) {
      mbar_init<4>(BAR(0), 1);
#pragma unroll 1
      for (int n = 0; n < 4; n++) { wait_clock(t_start + (P.hstart & 0xFFFF) + n * (P.hstart >> 16)); fetch(n, n); }
      mbar_init<28>(BAR(4), 1);
    }
    const uint32_t par = ~ld_relaxed32(G->hint[7][0]) >> 7 & 1;
    silu_vector(P.c + 320 * (bid & 1), 160, base);
    __syncthreads();
#pragma unroll 1
    for (int n = wg; unit(n) < 120; n += 4) {
      mbar_wait(BAR(n));
      mod_gemv<20>(G, 40960 * (n % 5), unit(n) >> 1, bid & 1, w, lane, par);
      named_bar(1 + wg, 128);
      if (w == 0) {
        wait_clock(t_start + P.hpause);
        if (n == 0) fetch(4, 4);
        fetch(n + 5, n % 5);
      }
    }
    return;
  }
  mbar_init<3>(BAR(wid < 15 ? 4 * wid + 1 : B_SC + 1), wid < 8 ? 1 : 4);
  mbar_init<1>(BAR(!wid ? B_SC + 4 : wid < 15 ? 4 * wid : B_SC), wid && wid < 8 ? 1 : 4);
  if (wid == 0) mbar_init<2>(BAR(B_SC + 5), 4);
  asm volatile("fence.mbarrier_init.release.cluster; bar.sync 0, 512;" ::: "memory");
  asm volatile("barrier.cluster.arrive.relaxed.aligned;" ::: "memory");
#define LAUNCHES const uint32_t launches = ld_relaxed32(G->hint[7][blockIdx.x >> 4])
#define EPOCH ((__shfl_sync(~0u, launches, 0) >> 7) + 1)
  if (wg < 2) {
    asm volatile("setmaxnreg.inc.sync.aligned.u32 224;");
    LAUNCHES;
    uint32_t par = launches;
    {
      float acc[128];
      uint32_t A[64];
#pragma unroll
      for (int i = 0; i < 64; i++) asm volatile("" : "=r"(A[i]));
      int c = wg;
#pragma unroll 1
      for (uint64_t prog = P.prog[wg]; prog; prog >>= 8) {
        REGION_IDS;
        const int s = prog & 7;
        if (s < 5) short_conv(G, base, s, w, par, P.xh);
        if (prog == P.prog[wg]) cluster_wait();
        if (prog & 16) {
          mbar_wait(BAR(B_QTD));
          mbar_wait(BAR(B_WM));
          mod_gemv<5>(G, OFF_WM, TA + (bid >> 3), bid & 7, w, lane, ~par >> 7 & 1);
          arrive1(BAR(B_G));
        }
        if (prog & 8) q_stats(base, w);
        if (prog & 32) {
          const int L = 16 * w + (lane >> 2) + 2 * (lane & 3) - 7;
          const uint32_t fo = base + ((L & 1) ? F_O + 2 * (L + 1) : F_E + 2 * L);
          mbar_wait(BAR(B_FRDY + c));
          cload<0, 0>(A, fo + tab(T_F, c));
          cload<15, 1>(A, fo + tab(T_F, c));
          arrive1(BAR(B_FL + c));
        }
        if (!(prog & 64)) continue;
        uint32_t xo;
#pragma unroll 1
        for (int it = 0; it < SPIN_LIMIT; it++) {
          xo = tab(T_X, opaque(c));
          mbar_wait(BAR(B_XR + c), it & 1);
          const uint32_t tag = lds32(base + xo + 32 * i0);
          wg_fence();
          csteps<0, 0>(acc, A, mkdesc(DB + xo, 16, 128, 0));
          csteps<15, 6>(acc, A, mkdesc(DB + xo, 16, 128, 0));
          wg_commit();
          if (bar_all(1 + wg, (tag ^ par >> 7) & 1)) break;
          wg_wait<0>();
          if (w == 0 && elect()) { mbar_expect_tx(BAR(B_XR + c), 4096); bulk_load(base + xo, G->xr + (128 * c + bid) * 256, 4096, BAR(B_XR + c)); }
        }
        wg_fence();
        csteps<5, 1>(acc, A, mkdesc(DB + tab(T_X, opaque(c)), 16, 128, 0));
        wg_commit();
        mbar_wait(BAR(B_SC + (c == 2 ? 3 : c)));
        wg_wait<0>();
        fence_regs(acc);
        const uint32_t pb = base + tab(T_P, c) + 4096 * w;
#pragma unroll
        for (int k = 0; k < 8; k++) {
          uint32_t p[4];
#pragma unroll
          for (int e = 0; e < 4; e++) { const int i = 4 * k + e; p[e] = i < 31 ? pack_bf16(acc[4 * i] + acc[4 * i + 6], acc[4 * i + 1] + acc[4 * i + 7]) : pack_bf16(acc[124], acc[125]); }
          if (k == 0 && (lane & 3) < w) p[0] = 0;
          stmatrix_x4_t(k == 0 ? pb + 16 * ((255 - lane + 2 * w) & 255) : pb + 16 * (255 - lane + 2 * w) - 512 * k, p[0], p[1], p[2], p[3]);
        }
        arrive1(BAR(B_PFULL + c));
        c += 2;
      }
    }
    par = ~par >> 7 & 1;
    const uint32_t ao = ((blockIdx.x ^ wg) & 1) * UNIT;
    uint32_t ck;
    { REGION_IDS; ck = base + ao + lane * 128 + (((2 * w) ^ (lane & 7)) << 4); }
    const uint32_t abd = DB + ao;
    auto tags = [&](int as, bool first) { return (lds32(ck + as) ^ par) | (lds32(ck + as + (first ? 4096 : 256)) ^ par); };
    int role;
    { int h, j, r; ffn_role(h, j, r); role = (2 * r + (h ^ wg)) * 8 + 4 * h + j; }
    auto a_tile = [&](int as, int n, bool first) {
#pragma unroll 1
      for (int it = 0; __any_sync(~0u, tags(as, first) & 1) && it < SPIN_LIMIT; it++) {
        if (elect()) {
          mbar_expect_tx(BAR(B_RETRY + wid), UNIT);
          if (first) tma2d(base + ao + as, &maps.xs, 8 * role & ~63, 64 * n, BAR(B_RETRY + wid));
          else bulk_load(base + as, G->hh + ((role & ~3) + ((role + n) & 3)) * 1536 + (n >> 2) * 512, UNIT, BAR(B_RETRY + wid));
        }
        mbar_wait(BAR(B_RETRY + wid), par >> 1);
        par ^= 2;
      }
    };
    float acc[128], acb[64];
    int ws = 0;
    float d[8];
    uint32_t *ud0, *ud1;
    unsigned* uh;
    {
      REGION_IDS;
      const int r = role >> 4, row = (r & 14) + (lane >> 2 & 1);
      ud0 = &G->uv[role & 7][32 * row + 4 * ((2 * w ^ row) & 7) + (lane & 3)];
      ud1 = ud0 + 512 * w_block(r & 1, 2);
      ud0 += 512 * w_block(r & 1, wg);
      uh = G->hint[8][role & 7];
      asm volatile("" : "+l"(ud0), "+l"(ud1), "+l"(uh));
    }
    auto step = [&](int n, int uv) {
      const int as = a_at(n);
      const uint64_t da = mkdesc(abd + as, 16, 1024, 1), db = mkdesc(DB + OFF_R + ws, 4096, 1024, 1);
      mbar_wait(BAR(B_FULL + 2 * n));
      a_tile(as, n, true);
      if (uv == 1) { mbar_wait(BAR(B_UVB)); mbar_wait(BAR(B_CO)); }
      wg_fence();
#pragma unroll
      for (int k = 0; k < 4; k++) {
        wg_ss64_11(acc + 96, da + 128 * k, db + 768 + 128 * (k & 1) + 1024 * (k >> 1), k ? 1 : n);
        if (k == GA - 1) { wg_commit(); wg_wait<1>(); if (elect()) mbar_arrive(BAR(B_EMPTY + 2 * n - 1)); if (uv == 2) fence_regs(d); }
      }
      if (uv == 1) {
#pragma unroll
        for (int k = 0; k < 5; k++) {
          wg_ss8_10(d, mkdesc(DB + OFF_UV + 2048 * wg + 6144 * k, 16, 1024, 1), mkdesc(DB + OFF_CO + 64 * k, 32, 128, 0), k);
        }
        if (!wg) {
#pragma unroll
          for (int k = 0; k < 5; k++) wg_ss8_10(d + 4, mkdesc(DB + OFF_UV + 4096 + 6144 * k, 16, 1024, 1), mkdesc(DB + OFF_CO + 64 * k, 32, 128, 0), k);
        }
      }
#pragma unroll
      for (int k = 0; k < 4; k++) wg_ss192_11(acc, da + 128 * k, db + 128 * (k & 1) + 1024 * (k >> 1), k ? 1 : n);
      wg_commit();
      ws = ws == 4 * WSLOT ? 0 : ws + 2 * WSLOT;
      if (uv == 2) {
        split(P.ulo, 30);
        REGION_IDS;
        const uint32_t tag = !(lane & 3);
        if (elect()) red_hint(uh);
        uint32_t x[4];
#pragma unroll
        for (int k = 0; k < 4; k++) asm volatile("movmatrix.sync.aligned.m8n8.trans.b16 %0, %1;" : "=r"(x[k]) : "r"(pack_bf16(d[2 * k], d[2 * k + 1])));
        const uint32_t y1 = __shfl_up_sync(~0u, x[1], 8), y3 = __shfl_up_sync(~0u, x[3], 8);
        if (lane < 16) {
          st_relaxed32((uint32_t*)((uint64_t)ud0 ^ 2 * (lane & 8)), set_tag(lane < 8 ? x[0] : y1, tag, par));
          if (!wg) st_relaxed32((uint32_t*)((uint64_t)ud1 ^ 2 * (lane & 8)), set_tag(lane < 8 ? x[2] : y3, tag, par));
        }
      }
    };
#pragma unroll 1
    for (int n = 0; n < UVS; n++) step(n, 0);
    step(UVS, 1);
    step(UVS + 1, 2);
#pragma unroll 1
    for (int n = UVS + 2; n < 10; n++) step(n, 0);
    float o[80];
    uint32_t fr[3][16], bo;
    {
      REGION_IDS;
      float r0, r1, s0, s1;
      const int id = role, j = role;
      uint4* const hdst = G->hh + id * 1536 + 128 * w + (lane ^ lane >> 3);
      const uint32_t keep = ~(~lane & 1), bit = par & ~keep;
      bo = 1024 + ((j & 1) << 23);
      auto own = [&](int i) { wg_rs160_1(o, fr[i >> 2] + 4 * (i & 3), mkdesc(DB + w2_at(i / 4) + (i & 3) * 2048, UNIT, bo, 1), i); };
      auto hint = [&](int v) { asm volatile("{.reg .pred p; setp.eq.u32 p, %1, 0; @p red.relaxed.gpu.global.add.u32 [%0], 1;}" ::"l"(&G->hhf[id * 8 + v]), "r"(lane) : "memory"); };
      auto put = [&](int v, int k) {
        uint32_t* x = fr[v] + 2 * k;
        const uint32_t t0 = (x[k / 2] & keep) | bit, t1 = (x[5 + k / 2] & keep) | bit;
        x[k / 2] = t0; x[5 + k / 2] = t1;
        st_relaxed128(hdst + 512 * v + 8 * k, x[0], x[2], x[4], x[6]);
        st_relaxed128(hdst + 512 * v + 8 * k + 64, x[1], x[3], x[5], x[7]);
      };
      auto move = [&](uint32_t* x, int n) {
#pragma unroll
        for (int k = 0; k < n; k++) asm volatile("mul.rn.f32 %0, %0, %1;" : "+r"(x[k]) : "f"(P.one));
      };
      auto act = [&](int i) {
        const int v = i >> 3, k = 7 - (i & 7);
        const float *g = v < 2 ? acc + 32 * v + 4 * k : acb + 4 * k, *up = g + (v < 2 ? 64 : 32);
        fr[v][2 * k] = pack_bf16(silu2(g[0], r0, s0) * up[0], silu2(g[1], r0, s0) * up[1]);
        fr[v][2 * k + 1] = pack_bf16(silu2(g[2], r1, s1) * up[2], silu2(g[3], r1, s1) * up[3]);
        if (!(k & 3)) { put(v, k); if (!k && !(HL >> v & 1)) hint(v); if (i == 15) { move(fr[0], 16); } }
        else asm volatile("" : "+r"(fr[v][2 * k]), "+r"(fr[v][2 * k + 1]));
      };
#pragma unroll
      for (int v = 0; v < 10; v++) {
        mbar_wait(BAR(B_FULL + 20 + v));
        if (v == XP) {
          mbar_wait(BAR(B_EXT));
          wg_fence();
          wg_ss192_01(acc, mkdesc(DB + OFF_AX + 1024 * opaque(wg), 0, 128, 0), mkdesc(DB + OFF_BX, 2048, 1024, 1), 1);
          wg_ss64_01(acc + 96, mkdesc(DB + OFF_AX + 1024 * opaque(wg), 0, 128, 0), mkdesc(DB + OFF_BX + 6144, 2048, 1024, 1), 1);
          wg_commit();
          r0 = 0.5f * __uint_as_float(lds32(base + OFF_RT + 256 * wg + 64 * w + (lane & 28)));
          r1 = 0.5f * __uint_as_float(lds32(base + OFF_RT + 256 * wg + 64 * w + 32 + (lane & 28)));
          s0 = 2.f * r0 * r0;
          s1 = 2.f * r1 * r1;
        }
        wg_fence();
#pragma unroll
        for (int k = 0; k < 4; k++) {
          wg_ss128_11(acb, mkdesc(opaque(abd) + a_at(second(v)) + k * 2048, 16, 1024, 1), mkdesc(DB + OFF_R + WSLOT * ((v + 2) % 6) + k * 2048, UNIT, 1024, 1), v + k);
          if (k == GB - 1) { wg_commit(); wg_wait<1>(); if (v == XP) fence_regs(acc); if (elect()) mbar_arrive(BAR(B_EMPTY + 19 + v)); }
        }
        if (v == 9) wg_ss128_01(acb, mkdesc(DB + OFF_AX + 1024 * opaque(wg), 0, 128, 0), mkdesc(DB + OFF_BX + UNIT, 2048, 1024, 1), 1);
        wg_commit();
        split(P.ulo, v);
        if (v == XP + NP / 2 && (HL & 1)) hint(0);
        if (v == XP + NP && (HL & 2)) hint(1);
#pragma unroll
        for (int i = 0; i < 16; i++) if (v >= XP && i * NP / 16 == v - XP) act(i);
      }
#pragma unroll
      for (int v = 0; v < 3; v++) {
        mbar_wait(BAR(B_FULL + 30 + v));
        wg_fence();
#pragma unroll
        for (int i = 0; i < 4; i++) {
          own(4 * v + i);
          if (i == GB - 1) { wg_commit(); wg_wait<1>(); if (v == 0) fence_regs(acb); if (elect()) mbar_arrive(BAR(B_EMPTY + 29 + v)); }
        }
        wg_commit();
        split(P.ulo, 10 + v);
        if (v == 0 && XP + NP == 10 && (HL & 2)) hint(1);
        if (v == 2 && (HL & 4)) hint(2);
#pragma unroll
        for (int i = 0; i < 4; i++) if (v < 2) act(16 + 4 * v + i);
      }
      ck = base + 2048 * w + 516 * (lane >> 3) + 144 * (lane >> 2 & 1) + 32 * (lane & 3);
    }
    uint32_t x1[40], gb[20];
    if (!wg) {
      REGION_IDS;
      mbar_wait(BAR(B_GB));
#pragma unroll
      for (int k = 0; k < 5; k++) {
        const uint4 g = lds128(base + OFF_GB + 80 * (lane & 3) + 16 * k);
        gb[4 * k] = g.x; gb[4 * k + 1] = g.y; gb[4 * k + 2] = g.z; gb[4 * k + 3] = g.w;
      }
    }
#pragma unroll 1
    for (int u = 33; u < 42; u++) {
      const int x = P.hid[wg][u - 33], as = x & ~15;
      const uint64_t wd = mkdesc(0, 0, bo, 1) | P.w2t[u - 30].x;
      mbar_wait(BAR(B_FULL + u));
      a_tile(as, x & 15, false);
      if (wg || u < LAG2) {
        wg_fence();
#pragma unroll
        for (int kk = 0; kk < 4; kk++) {
          wg_ss160_01(o, mkdesc(DB + as + kk / 2 * 512 + (kk & 1) * 32, 16, 1024, 2), wd + kk * 128, 1);
          if (kk == GB - 1) { wg_commit(); wg_wait<1>(); if (elect()) mbar_arrive(BAR(B_EMPTY + u - 1)); }
        }
        wg_commit();
        if (u == 41 && elect()) mbar_arrive(BAR(B_LAG));
      }
      if (u == LAG2 - 1 && !wg) {
        REGION_IDS;
        const uint32_t xa = base + (lane >> 4) * 1024 + (lane & 7) * 128 + (((2 * w + ((lane >> 3) & 1)) ^ (lane & 7)) << 4);
        mbar_wait(BAR(B_FULL + 42));
        wg_wait<0>();
        if (elect()) mbar_arrive(BAR(B_EMPTY + LAG2 - 1));
#pragma unroll
        for (int k = 0; k < 10; k++) ldmatrix_x4_t(x1 + 4 * k, xa + x1_at(k / 2) + (k & 1) * 2048);
      }
    }
    REGION_IDS;
    const int h = role >> 2 & 1, j = role & 3;
    const uint32_t xb = base + OFF_XCH + 5120 * w;
    if (wg) {
      const uint32_t rdst = mapa(xb + 16 * lane, h ^ 1), rbar = mapa(BAR(B_FULL + 1), h ^ 1);
      mbar_wait(BAR(B_XFREE));
      wg_wait<0>();
      fence_regs(o);
#pragma unroll
      for (int k = 0; k < 10; k++)
        asm volatile("st.async.shared::cluster.mbarrier::complete_tx::bytes.v4.b32 [%0], {%1,%2,%3,%4}, [%5];" ::"r"(rdst + 512 * k), "r"(pack_bf16(o[8 * k], o[8 * k + 1])),
                     "r"(pack_bf16(o[8 * k + 2], o[8 * k + 3])), "r"(pack_bf16(o[8 * k + 4], o[8 * k + 5])), "r"(pack_bf16(o[8 * k + 6], o[8 * k + 7])), "r"(rbar + 16 * (k / 4)) : "memory");
    } else {
      mbar_wait(BAR(B_LAG));
      wg_fence();
#pragma unroll
      for (int i = 4 * LAG2; i < 168; i++) wg_ss160_01(o, mkdesc(DB + hid_at(i / 4 - 33, 0) + (i & 2) * 256 + (i & 1) * 32, 16, 1024, 2), mkdesc(DB + w2_at(i / 4 - 30) + (i & 3) * 2048, UNIT, bo, 1), 1);
      wg_commit();
      const int row = (8 * role & ~63) + 16 * w;
      auto merge = [&](int e0, int e1) {
#pragma unroll
        for (int e = e0; e < e1; e++) {
          if (e % 4 == 0) mbar_wait_cluster(BAR(B_FULL + 1 + e / 2));
          const uint4 p = lds128(xb + 16 * lane + 512 * e);
          x1[4 * e] = bfma2(gb[2 * e], p.x, x1[4 * e]); x1[4 * e + 1] = bfma2(gb[2 * e], p.y, x1[4 * e + 1]);
          x1[4 * e + 2] = bfma2(gb[2 * e + 1], p.z, x1[4 * e + 2]); x1[4 * e + 3] = bfma2(gb[2 * e + 1], p.w, x1[4 * e + 3]);
        }
        __syncwarp();
      };
      merge(0, MG);
      wg_wait<0>();
      fence_regs(o);
#pragma unroll
      for (int k = 0; k < 10; k++) {
        if (k >= MG && k % 4 == 0) merge(k, k < 8 ? k + 4 : 10);
        uint32_t y[4];
#pragma unroll
        for (int e = 0; e < 4; e++) y[e] = bfma2(gb[2 * k + e / 2], pack_bf16(o[8 * k + 2 * e], o[8 * k + 2 * e + 1]), x1[4 * k + e]);
        stmatrix_x4(k < 8 ? xb + 2048 * (k >> 2) + (lane & 15) * 128 + (((2 * (k & 3) + (lane >> 4)) ^ (lane & 7) ^ 4 * (j & 1)) << 4)
                          : xb + 4096 + (lane & 15) * 64 + (((2 * (k & 1) + (lane >> 4)) ^ (lane >> 1 & 3)) << 4), y[0], y[1], y[2], y[3]);
        if ((SG >> k & 1) || k == 9) {
          fence_async_smem();
          __syncwarp();
#pragma unroll
          for (int b = 0; b < 3; b++) {
            const int e = b < 2 ? 4 * b + 3 : 9;
            if (e <= k && !(SG & ((1 << k) - 1) & ~((1 << e) - 1)) && lane == 0) tma2d_store(b < 2 ? &maps.outa : &maps.outb, b < 2 ? 128 * j + 64 * b : 512 + 32 * j, row, xb + 2048 * b);
          }
        }
      }
      if (lane == 0) { bulk_commit(); bulk_wait_read(); }
    }
  } else if (wg == 2) {
    asm volatile("setmaxnreg.dec.sync.aligned.u32 40;");
    mbar_init<15>(BAR(B_FULL + 15 * w), 1);
    mbar_init<11>(BAR(B_EMPTY - 1 + 11 * w), 8);
    asm volatile("fence.mbarrier_init.release.cluster;" ::: "memory");
    LAUNCHES;
    silu_vector(P.c + 80 * (blockIdx.x & 7) - 512, 296, base - 1024);
    const uint32_t epoch = EPOCH;
    if (w == 2) rank_pair(G, base, epoch, true);
    cluster_wait();
    {
      REGION_IDS;
      const uint32_t tag = opaque(~lane & 1);
      auto q_t = [&]() {
        const int tr = 4 * (lane & 1) + (lane >> 1 & 3);
        uint32_t a = base + OFF_Q + 128 * ((lane & 24) + tr) + ((w ^ tr) << 4);
        uint4* dst = G->qt + (64 * (bid & 1) + 8 * w + (lane >> 2)) * 256 + 4 * (bid >> 1) + (lane & 3);
#pragma unroll 1
        for (int c = 0; c < 5; c++) {
          mbar_wait(BAR(B_Q + c));
#pragma unroll
          for (int k = 0; k < 2; k++) {
            uint32_t x[4];
            ldmatrix_x4_t(x, a ^ (64 * k));
            st_relaxed128(dst + 8192 * k, set_tag(x[0], tag, epoch), x[1], x[2], x[3]);
          }
          a += 4096;
          dst += 32768;
        }
        arrive1(BAR(B_QTD));
      };
      q_t();
      if (w == 3) {
        mbar_wait_cluster(BAR(B_ST1));
        if (lane < 8) red_hint(G->hint[5][lane]);
        const uint2 x = lds64(base + OFF_ST + 8 * (lane & 15)), y = lds64(base + OFF_ST + 128 + 8 * (lane & 15));
        float m, sd;
        ln_final(__uint_as_float(x.x) + __uint_as_float(y.x), __uint_as_float(x.y) + __uint_as_float(y.y), m, sd);
        sd = rbf(rcpf(sd));
        const uint32_t mr = pack_bf16(sd, -rbf(m) * sd), tg = lane & 7 ? 0 : lane & 8 ? 1 : 0x8000;
        const uint32_t o = __byte_perm(__shfl_sync(~0u, mr, 2 * lane & 14), __shfl_sync(~0u, mr, (2 * lane & 14) + 1), (lane & 8) ? 0x7632 : 0x5410);
        if (lane < 16) st_relaxed32(&G->st1[lane >> 3][8 * bid + (lane & 7)], (o & ~tg) | ((epoch & 1) * tg));
      }
      if (w == 2) rank_pair(G, base, epoch, false);
      if (w == 1) mod_fetch(G, base, epoch, M8, 0, 1);
    }
    {
      REGION_IDS;
      const uint32_t tag = opaque(~lane & 1), sa = opaque(base + 16 * i0);
      uint4 q[2];
      mbar_wait(BAR(B_PFULL));
#pragma unroll 1
      for (uint32_t a = sa + tab(T_P, 0); a < sa + tab(T_P, 0) + 4096; a += 2048) {
        uint4 y = lds128(a), z = lds128(a + 4096), u = lds128(a + 8192);
        const uint4 v = lds128(a + 12288);
        add4(y, z); add4(u, v); add4(y, u);
        sts128(a, y.x, y.y, y.z, y.w);
      }
      uint4* gp = G->xs + 256 * bid + (sa - base >> 4);
      q[0] = ld_relaxed128(gp - D_ * 256);
      q[1] = ld_relaxed128(gp - D_ * 256 + 128);
      mbar_wait(BAR(B_MR));
      e_round<true>(G, base, sa, gp, q, 0, w, tag, epoch);
#pragma unroll 1
      for (int c = 1; c < 5; c++) e_round<false>(G, base, sa, gp, q, c, w, tag, epoch);
    }
    int h, j, r;
    ffn_role(h, j, r);
    arrive1(BAR(B_ED));
    {
      REGION_IDS;
      float s0 = 0.f, q0 = 0.f, s1 = 0.f, q1 = 0.f;
#pragma unroll 1
      for (int c = 2; c < 5; c++) {
        const uint32_t buf = base + OFF_SX + 4096 * (c - 2), b = BAR(B_SX + c);
        uint32_t x[8];
#pragma unroll 1
        for (int it = 0; it < SPIN_LIMIT; it++) {
          mbar_wait(b, it & 1);
#pragma unroll
          for (int i = 0; i < 8; i++) x[i] = lds32(buf + 1024 * w + 4 * lane + 128 * i);
          if (bar_all(3, (lane & 7) || min(min(min(x[0], x[1]), min(x[2], x[3])), min(min(x[4], x[5]), min(x[6], x[7]))))) break;
          if (w == 0 && elect()) { mbar_expect_tx(b, 4096); tma2d(buf, &maps.x1s, 128 * r + 64 * h, D_ * (epoch & 1) + 128 * c + 32 * j, b); }
        }
#pragma unroll
        for (int i = 0; i < 8; i++) { const float lo = bf_lo(x[i]), hi = bf_hi(x[i]); s0 += lo; q0 = fmaf(lo, lo, q0); s1 += hi; q1 = fmaf(hi, hi, q1); }
      }
      sts128(base + OFF_MR + 1024 * w + 16 * lane, __float_as_uint(s0), __float_as_uint(q0), __float_as_uint(s1), __float_as_uint(q1));
      arrive1(BAR(B_S2));
    }
    {
      REGION_IDS;
      const uint32_t* sp = &G->st2[2 * r + (h ^ (w >> 1))][0][2 * (i0 & 63)];
      uint2 x[4];
      int it;
#pragma unroll 1
      for (it = 0; it < SPIN_LIMIT; it++) {
        mbar_wait(BAR(B_BX), it & 1);
        uint32_t y = 0;
#pragma unroll
        for (int k = 0; k < 3; k++) y |= lds32(base + OFF_BX + 32 * i0 + 4096 * k) ^ epoch;
        if (bar_all(3, !(y & 1))) break;
        if (w == 0 && elect()) { mbar_expect_tx(BAR(B_BX), 12288); bulk_load(base + OFF_BX, G->uv[4 * h + j], 12288, BAR(B_BX)); }
      }
      it = 0;
#pragma unroll 1
      do {
#pragma unroll
        for (int k = 0; k < 4; k++) x[k] = ld_relaxed64(sp + 128 * k);
      } while (__any_sync(~0u, ((x[0].x ^ epoch) | (x[1].x ^ epoch) | (x[2].x ^ epoch) | (x[3].x ^ epoch)) & 1) && ++it < SPIN_LIMIT);
      float m, sd;
      ln_final((__uint_as_float(x[0].x) + __uint_as_float(x[1].x)) + (__uint_as_float(x[2].x) + __uint_as_float(x[3].x)),
               (__uint_as_float(x[0].y) + __uint_as_float(x[1].y)) + (__uint_as_float(x[2].y) + __uint_as_float(x[3].y)), m, sd);
      const uint32_t e = pack_bf16(-m, sd);
      sts128(base + OFF_AX + 16 * i0, e, e, e, e);
      sts32(base + OFF_RT + 4 * i0, __float_as_uint(rcpf(sd)));
      fence_async_smem();
      arrive1(BAR(B_EXT));
      {
        uint2 g0, g1;
        int it = 0;
#pragma unroll 1
        do {
          g0 = ld_relaxed64(&G->modv[1][128 * j + i0]);
          g1 = ld_relaxed64(&G->modv[1][512 + 32 * j + lane]);
        } while (__any_sync(~0u, ((g0.x ^ epoch) | (g0.y ^ epoch) | (g1.x ^ epoch) | (g1.y ^ epoch)) & 1) && ++it < SPIN_LIMIT);
        const uint32_t a = base + OFF_GB + 40 * (lane & 6) + 2 * (lane & 1) + (lane >> 3) * 4;
        asm volatile("st.shared.u16 [%0], %1; st.shared.u16 [%2], %3;" ::"r"(a + 16 * (w ^ (j & 1))), "h"((uint16_t)(mod_sum(g0) >> 16)), "r"(a + 64), "h"((uint16_t)(mod_sum(g1) >> 16)) : "memory");
        arrive1(BAR(B_GB));
      }
      const int id = 16 * r + 4 * h + ((j + 1 + w) & 3);
#pragma unroll 1
      for (int q = w == 3 ? 3 : 0; q < 3; q++) {
        const int m = 3 * q + w;
        const uint4* src = G->hh + id * 1536 + 512 * q;
        it = 0;
#pragma unroll 1
        while (__any_sync(~0u, ld_relaxed32(&G->hhf[8 * id + 64 * (lane & 1) + q]) != 4 * epoch) && ++it < SPIN_LIMIT);
        mbar_wait(BAR(P.hid[2][m]));
        if (elect()) {
          bulk_load(base + (P.hid[h][m] & ~15), src, UNIT, BAR(B_FULL + 33 + m));
          bulk_load(base + (P.hid[h ^ 1][m] & ~15), src + 8 * 1536, UNIT, BAR(B_FULL + 33 + m));
        }
      }
    }
  } else {
    asm volatile("setmaxnreg.dec.sync.aligned.u32 24;");
    if (w >= 2) {
      LAUNCHES;
      uint32_t epoch;
      {
        REGION_IDS;
        uint32_t dv;
        asm volatile("ld.global.nc.u16 %0, [%1];" : "=r"(dv) : "l"(P.ssmd + 128 * (lane & 7) % D_ + bid));
        if (lane < 5) sts128(base + tab(T_F, lane) + (w & 1) * (F_O - F_E) + F_E - 16, 0, 0, 0, 0);
        epoch = EPOCH;
        __syncwarp();
#pragma unroll 1
        for (int c = 0; c < 5; c++) {
          const float d = i0 == 64 ? bf_lo(dv) : 0.f;
          dv = __shfl_down_sync(~0u, dv, 1);
          const uint32_t a = base + tab(T_F, c) + 16 * (i0 - 64);
          mbar_wait(BAR(B_FRAW + c));
#pragma unroll
          for (int k = 0; k < 4; k++) {
            uint4 x = lds128(a + F_E + 1024 * k);
            const uint32_t pv = lds32(a + F_E - 4 + 1024 * k);
            if (k == 0) { x.x = pack_bf16(bf_lo(x.x) + d, bf_hi(x.x)); sts32(a + F_E, x.x); }
            sts128(a + F_O + 1024 * k, __byte_perm(pv, x.x, 0x5432), __byte_perm(x.x, x.y, 0x5432), __byte_perm(x.y, x.z, 0x5432), __byte_perm(x.z, x.w, 0x5432));
          }
          __syncwarp();
          if (elect()) mbar_arrive2(BAR(B_FRDY + c));
          if (c == 0 && w == 3) {
#pragma unroll 1
            for (int k = 0; k < 13; k++) prefetch_map(&maps.w1a + k);
          }
        }
      }
      REGION_IDS;
      int h, j, r;
      ffn_role(h, j, r);
      cluster_wait();
      if (w == 2) {
        const unsigned* fp = G->xsh[lane < 10 ? lane >> 1 : 0][(r & 6) + (lane & 1)];
        uint32_t rdy = 0;
        mbar_wait(BAR(B_SC + 4));
#pragma unroll 1
        for (int e = 0; e < 14; e++) {
          const uint32_t x = P.adep[e], n = x >> 21 & 15, s = base + (x >> 25 << 13), b = BAR(B_FULL + (x >> 16 & 31));
          mbar_wait(BAR(opaque(x & 255)));
          mbar_wait(BAR(opaque(x >> 8 & 255)));
          const uint32_t f = BAR(B_FULL + 7 + 2 * (e < 7 ? e : e - 7));
          if (elect()) mbar_arrive_remote(mapa(f, h ^ 1));
#pragma unroll 1
          for (int it = 0; !(rdy >> n & 1) && it < SPIN_LIMIT; it++) rdy = __ballot_sync(~0u, ld_relaxed32(fp) == 64 * epoch);
          mbar_wait(f, e >= 7);
          if (elect()) asm volatile("cp.async.bulk.tensor.2d.shared::cluster.global.mbarrier::complete_tx::bytes.multicast::cluster [%0], [%1, {%3,%4}], [%2], %5;"
                                    ::"r"(s + UNIT * h), "l"(&maps.xs), "r"(b), "r"(128 * r + 64 * h), "r"(64 * n), "h"((uint16_t)3) : "memory");
        }
#pragma unroll 1
        for (int v = 0; v < 12; v++) {
          const int q = v * 11 >> 5, e = v - 3 * q, k32 = 24 * h + (q ? 6 * ((j + 1 + e) & 3) + 2 * q - 2 : 6 * j + 2 * e);
          const uint2 x = P.w2t[v];
          mbar_wait(BAR(x.y));
          if (elect()) {
            mbar_expect_tx(BAR(B_FULL + 30 + v), q ? W2TILE + 2 * UNIT : W2TILE);
#pragma unroll
            for (int k = 0; k < 3; k++) tma5d(base - DB + 16 * (x.x & 0xFFFF) + UNIT * k, &maps.w2a + (q > 0), k < 2 ? 128 * j + 64 * k : 512 + 32 * (j & 2), k32, BAR(B_FULL + 30 + v));
          }
        }
      } else {
        float s0 = 0.f, q0 = 0.f, s1 = 0.f, q1 = 0.f;
        uint32_t nl = 0, np = 0, ph = 0;
#pragma unroll 1
        for (uint32_t seq = 0x94; seq > 1; seq >>= 1) {
          const uint32_t c = seq & 1 ? np : nl, buf = base + OFF_SX + 4096 * (c < 4 ? c & 1 : 2), b = BAR(opaque(B_SX + c));
          int it = 0;
          if (seq & 1) {
            mbar_wait(b, ph >> c & 1);
            ph ^= 1 << c;
            const uint32_t a = buf + 32 * lane;
            if (__all_sync(~0u, min(min(lds32(a), lds32(a + 1024)), min(lds32(a + 2048), lds32(a + 3072)))) || ph > SPIN_LIMIT) {
#pragma unroll 1
              for (uint32_t o = buf + 4 * lane; o < buf + 4096; o += 1024) {
                uint32_t x[8];
#pragma unroll
                for (int i = 0; i < 8; i++) x[i] = lds32(o + 128 * i);
#pragma unroll
                for (int i = 0; i < 8; i++) { const float lo = bf_lo(x[i]), hi = bf_hi(x[i]); s0 += lo; q0 = fmaf(lo, lo, q0); s1 += hi; q1 = fmaf(hi, hi, q1); }
              }
              np++;
              continue;
            }
            ph += 4;
            seq = 2 * seq + 1;
          } else {
#pragma unroll 1
            while (__any_sync(~0u, ld_relaxed32(G->xsh[c][(r & 6) + (j >> 1)]) != 64 * epoch) && ++it < SPIN_LIMIT);
            if (++nl == 5) mbar_wait(BAR(B_PEMPTY + 4));
          }
          if (elect()) { mbar_expect_tx(b, 4096); tma2d(buf, &maps.x1s, 128 * r + 64 * h, D_ * (epoch & 1) + 128 * c + 32 * j, b); }
        }
        mbar_wait(BAR(B_S2));
#pragma unroll
        for (int k = 0; k < 4; k++) {
          const uint4 x = lds128(base + OFF_MR + 1024 * k + 16 * lane);
          s0 += __uint_as_float(x.x); q0 += __uint_as_float(x.y); s1 += __uint_as_float(x.z); q1 += __uint_as_float(x.w);
        }
        asm volatile("{.reg .b128 t, x; .reg .b64 a, b; mov.b64 a, {%1,%2}; mov.b64 b, {%3,%4}; mov.b128 x, {a,b}; atom.relaxed.gpu.global.exch.b128 t, [%0], x;}"
                     ::"l"(&G->st2[2 * r + h][j][4 * lane]), "r"((__float_as_uint(s0) & ~1u) | (epoch & 1)), "f"(q0), "r"((__float_as_uint(s1) & ~1u) | (epoch & 1)), "f"(q1) : "memory");
        mbar_wait(BAR(B_EMPTY + 2 * UVS + 1));
        sts128(base + OFF_CO + 16 * lane, 0, 0, 0, 0);
        fence_async_smem();
        __syncwarp();
        if (elect()) {
#pragma unroll 1
          for (int k = 0; k < 40; k++) asm volatile("cp.async.bulk.global.shared::cta.bulk_group [%0], [%1], 512;" ::"l"(G->x1[~epoch & 1] + 1280 * blockIdx.x + 32 * k), "r"(base + OFF_CO) : "memory");
          bulk_commit();
          bulk_wait_read();
        }
      }
    } else if (w == 0) {
      LAUNCHES;
      uint32_t epoch;
      {
        REGION_IDS;
        const unsigned* hp = G->hint[0][4 * (bid >> 6) + (bid >> 3 & 3)];
        uint32_t v = ld_relaxed32(hp + 256 * min(lane, 5));
        if (lane < 3) sts128(base + tab(T_X, lane) + 4096, 0, 0, 0, 0);
        if (lane && lane <= B_WM) mbar_expect_tx(BAR(lane), lane < B_FRAW ? 9728 : lane == B_WM ? 10240 : 4096);
        epoch = EPOCH;
        fence_async_smem();
        const uint32_t rdy = __ballot_sync(~0u, v == epoch << 6) & 31;
        uint32_t nx = 0, mr = 1;
#pragma unroll 1
        for (int it = 0; (nx < 5 || mr) && it < SPIN_LIMIT; it++) {
          const bool second = nx == 5 || (lane && mr && nx >= P.mq);
          if (!(rdy >> nx & 1)) v = ld_relaxed32(hp + 256 * (second ? 5 : nx));
          const uint32_t ok = __ballot_sync(~0u, v == epoch << (second ? 7 : 6)) | (rdy >> nx & 1);
          if (nx < 5 && (ok & 1)) {
            if (nx >= 3) mbar_wait(BAR(B_PFULL - 3 + nx));
            if (elect()) { mbar_expect_tx(BAR(B_XR + nx), 4096); bulk_load(base + tab(T_X, nx), G->xr + (128 * nx + bid) * 256, 4096, BAR(B_XR + nx)); }
          }
          if (mr && (nx == 5 || nx >= P.mq) && (ok & 2) && !(rdy >> nx & 1)) {
            if (elect()) { mbar_expect_tx(BAR(B_MR), 8192); bulk_load(base + OFF_MR, G->st1, 8192, BAR(B_MR)); mbar_arrive(BAR(B_QTOK)); }
            mr = 0;
          }
          if (nx < 5) nx += ok & 1;
        }
        mod_fetch(G, base, epoch, M8, 2, 5);
      }
      REGION_IDS;
      int h, j, r;
      ffn_role(h, j, r);
      cluster_wait();
      if (elect()) mbar_expect_tx(BAR(B_UVB), 30720);
#pragma unroll 1
      for (int k = 0; k < 5; k++) {
        mbar_wait(BAR(opaque(B_EMPTY + nib(P.uvd, k))));
        if (elect()) tma3d(base + OFF_UV + 6144 * k, &maps.w1u + (r & 1), 0, 40 * (r & 14) + 16 * k, 3 * (4 * h + j), BAR(B_UVB));
      }
      mbar_wait(BAR(B_G));
      {
        const uint2* mp = &G->modv[lane & 4 ? 0 : 2][40 * (r & 14) + (lane & 24) + 2 * (lane & 3)];
        uint4 v[3];
        int it = 0;
#pragma unroll 1
        do {
          v[0] = ld_relaxed128(mp); v[1] = ld_relaxed128(mp + 32); v[2] = ld_relaxed128(mp + 64 - (lane & 16));
        } while (__any_sync(~0u, ((v[0].x ^ epoch) | (v[0].y ^ epoch) | (v[0].z ^ epoch) | (v[0].w ^ epoch) | (v[1].x ^ epoch) | (v[1].y ^ epoch) | (v[1].z ^ epoch) | (v[1].w ^ epoch) |
                                  (v[2].x ^ epoch) | (v[2].y ^ epoch) | (v[2].z ^ epoch) | (v[2].w ^ epoch)) & 1) && ++it < SPIN_LIMIT);
#pragma unroll
        for (int i = 0; i < 3; i++)
          sts32(base + OFF_CO + 128 * i + 4 * lane, badd2(pack_bf16(__uint_as_float(v[i].x) + __uint_as_float(v[i].y), __uint_as_float(v[i].z) + __uint_as_float(v[i].w)), lane & 4 ? 0 : 0x3F803F80u));
      }
      fence_async_smem();
      arrive1(BAR(B_CO));
      ffn_role(h, j, r);
      mbar_wait(BAR(B_ED));
      int it = 0;
#pragma unroll 1
      while (__any_sync(~0u, ld_relaxed32(G->hint[8][4 * h + j]) != 128 * epoch) && ++it < SPIN_LIMIT);
      if (elect()) { mbar_expect_tx(BAR(B_BX), 12288); bulk_load(base + OFF_BX, G->uv[4 * h + j], 12288, BAR(B_BX)); }
      asm volatile("fence.acq_rel.gpu;" ::: "memory");
      if (lane < 8) red_hint(G->hint[7][lane]);
      unsigned x;
      it = 0;
#pragma unroll 1
      do { asm volatile("ld.acquire.gpu.global.u32 %0, [%1];" : "=r"(x) : "l"(G->hint[7][bid >> 4]) : "memory"); } while (__any_sync(~0u, x != 128 * epoch) && ++it < SPIN_LIMIT);
      fence_async_all();
      const int ch = D_ * (epoch & 1);
      mbar_wait(BAR(P.xdep));
      if (elect()) {
        mbar_expect_tx(BAR(B_FULL + 42), 20480);
#pragma unroll
        for (int k = 0; k < 4; k++) tma2d(base + x1_at(k), &maps.x1b, 128 * r + 64 * h, ch + 128 * j + 32 * (k ^ (j & 1)), BAR(B_FULL + 42));
        tma2d(base + x1_at(4), &maps.x1b, 128 * r + 64 * h, ch + 512 + 32 * j, BAR(B_FULL + 42));
        mbar_expect_tx(BAR(B_FULL + 1), 8192); mbar_expect_tx(BAR(B_FULL + 3), 8192); mbar_expect_tx(BAR(B_FULL + 5), 4096);
      }
      mbar_wait(BAR(B_EMPTY + 37));
      if (elect()) mbar_arrive_remote(mapa(BAR(B_XFREE), h ^ 1));
    } else {
      LAUNCHES;
      {
        REGION_IDS;
        loads<0>(P, maps, base);
      }
      cluster_wait();
      int h, j, r;
      ffn_role(h, j, r);
      mbar_wait(BAR(B_QTD));
      mbar_wait(BAR(B_STD));
      mbar_wait(BAR(B_SC));
      mbar_wait(BAR(B_SC + 2));
      mbar_wait(BAR(B_FL));
#pragma unroll 1
      for (int u = 0; u < 30; u++) {
        if (u == P.mpos) mod_fetch(G, base, EPOCH, M8, 1, 2);
        if (u < 6) wait_clock(t_start + P.wt0 + u * P.wpace);
        const uint32_t x = P.wdep[u], b = x >> 8 & 1;
        uint32_t s = base + OFF_R + WSLOT * (x >> 9 & 7), f = BAR(B_FULL + (b ? u : u & ~1)), n = x & 0xC000, y = x >> 16, z = 3 * (4 * h + j) + 2 * b;
        const CUtensorMap* m = &maps.w1a + 5 * b;
        asm volatile("{.reg .pred p, q; .reg .b32 i, t; .reg .b64 m; mov.u32 i, 0; add.u32 t, %0, 8192; add.u64 m, %1, 128; elect.sync _|q, 0xffffffff;"
                     "W: mbarrier.try_wait.parity.shared::cta.b64 p, [%6], 0; @p bra.uni D; add.u32 i, i, 1; setp.lt.u32 p, i, %7; @p bra.uni W; D:"
                     "setp.ne.and.u32 p, %3, 0, q; @p mbarrier.arrive.expect_tx.shared::cta.b64 _, [%2], %3;"
                     "@q cp.async.bulk.tensor.3d.shared::cluster.global.mbarrier::complete_tx::bytes [%0], [%1, {0,%4,%5}], [%2];"
                     "@q cp.async.bulk.tensor.3d.shared::cluster.global.mbarrier::complete_tx::bytes [t], [m, {0,%4,%5}], [%2];}"
                     ::"r"(s), "l"(m), "r"(f), "r"(n), "r"(y), "r"(z), "r"(BAR(opaque(x & 255))), "n"(SPIN_LIMIT) : "memory");
      }
    }
  }
}

typedef CUresult (*EncFn)(CUtensorMap*, CUtensorMapDataType, cuuint32_t, void*, const cuuint64_t*, const cuuint64_t*, const cuuint32_t*,
                          const cuuint32_t*, CUtensorMapInterleave, CUtensorMapSwizzle, CUtensorMapL2promotion, CUtensorMapFloatOOBfill);
static int enc_err = 0;
static void enc(EncFn fn, CUtensorMap* m, const void* p, int rank, const cuuint64_t* gd, const cuuint64_t* gs, const cuuint32_t* bd, CUtensorMapSwizzle sw) {
  cuuint32_t es[5] = {1, 1, 1, 1, 1};
  enc_err = 2 * enc_err + (fn(m, CU_TENSOR_MAP_DATA_TYPE_BFLOAT16, rank, (void*)p, gd, gs, bd, es, CU_TENSOR_MAP_INTERLEAVE_NONE, sw,
                              CU_TENSOR_MAP_L2_PROMOTION_L2_128B, CU_TENSOR_MAP_FLOAT_OOB_FILL_NONE) != CUDA_SUCCESS);
}

extern "C" void kernel_launch(void* const* d_in, const int* in_sizes, int n_in, void* d_out, int out_size) {
  const bf16 *q = (const bf16*)d_in[0], *k = (const bf16*)d_in[1], *v = (const bf16*)d_in[2], *shift = (const bf16*)d_in[3],
             *ssmk = (const bf16*)d_in[4], *ssmd = (const bf16*)d_in[5], *w1 = (const bf16*)d_in[7], *w3 = (const bf16*)d_in[8],
             *w2 = (const bf16*)d_in[9], *c = (const bf16*)d_in[10], *wmod = (const bf16*)d_in[11];
  EncFn fn = nullptr;
  cudaDriverEntryPointQueryResult qr;
  cudaGetDriverEntryPoint("cuTensorMapEncodeTiled", (void**)&fn, cudaEnableDefault, &qr);
  Scratch* pg;
  cudaGetSymbolAddress((void**)&pg, g_s);
  Maps maps;
  enc_err = 0;
  const CUtensorMapSwizzle S128 = CU_TENSOR_MAP_SWIZZLE_128B;
  { cuuint64_t gd[3] = {D_, S_ / 8, 8}, gs[2] = {D_ * 16, D_ * 2}; cuuint32_t b[3] = {64, 4, 8};
    enc(fn, &maps.km, k, 3, gd, gs, b, S128);
    enc(fn, &maps.v, v, 3, gd, gs, b, S128);
    enc(fn, &maps.q, q, 3, gd, gs, b, S128);
    b[2] = 3;
    enc(fn, &maps.kh, k, 3, gd, gs, b, S128); }
  { cuuint64_t gd[3] = {256, 8, D_}, gs[2] = {512, 4096}; cuuint32_t b[3] = {256, 8, 1};
    enc(fn, &maps.fm, ssmk, 3, gd, gs, b, CU_TENSOR_MAP_SWIZZLE_NONE); }
  { cuuint64_t gd[3] = {256, 2, 5}, gs[2] = {512, 1024}; cuuint32_t b[3] = {256, 1, 5};
    enc(fn, &maps.tap, shift, 3, gd, gs, b, CU_TENSOR_MAP_SWIZZLE_NONE); }
  { cuuint64_t gd[3] = {6 * D_, D_, 1}, gs[2] = {6 * D_ * 2, 6 * D_ * 2 * D_}; cuuint32_t b[3] = {64, 64, 1};
    enc(fn, &maps.wm, wmod, 3, gd, gs, b, S128);
    b[1] = 80;
    enc(fn, &maps.wmp, wmod, 3, gd, gs, b, S128); }
  { cuuint64_t gd[3] = {64, D_, F_ / 64}, gs[2] = {F_ * 2, 128}; cuuint32_t b[3] = {64, 16, 3};
    enc(fn, &maps.w1u, w1, 3, gd, gs, b, S128);
    enc(fn, &maps.w3u, w3, 3, gd, gs, b, S128);
    b[1] = 32; b[2] = 2;
    enc(fn, &maps.w1a, w1, 3, gd, gs, b, S128);
    enc(fn, &maps.w3a, w3, 3, gd, gs, b, S128);
    b[1] = 64; b[2] = 1;
    enc(fn, &maps.w1b, w1, 3, gd, gs, b, S128);
    enc(fn, &maps.w3b, w3, 3, gd, gs, b, S128); }
  { cuuint64_t gd[2] = {S_, D_}, gs[1] = {S_ * 2}; cuuint32_t b1[2] = {64, 64}, b2[2] = {64, 32};
    enc(fn, &maps.xs, pg->xs, 2, gd, gs, b1, S128);
    gd[1] = 2 * D_;
    enc(fn, &maps.x1b, pg->x1, 2, gd, gs, b2, S128);
    enc(fn, &maps.x1s, pg->x1, 2, gd, gs, b2, CU_TENSOR_MAP_SWIZZLE_NONE); }
  { cuuint64_t gd[5] = {D_, 2, 4, 4, 48}, gs[4] = {D_ * 2, D_ * 4, D_ * 16, D_ * 64}; cuuint32_t b[5] = {64, 2, 4, 4, 2};
    enc(fn, &maps.w2a, w2, 5, gd, gs, b, S128);
    gs[1] = D_ * 16; gs[2] = D_ * 4;
    enc(fn, &maps.w2b, w2, 5, gd, gs, b, S128); }
  { cuuint64_t gd[2] = {D_, S_}, gs[1] = {D_ * 2}; cuuint32_t b1[2] = {64, 16}, b2[2] = {32, 16};
    enc(fn, &maps.outa, d_out, 2, gd, gs, b1, S128);
    enc(fn, &maps.outb, d_out, 2, gd, gs, b2, CU_TENSOR_MAP_SWIZZLE_64B); }
  if (enc_err) return;
  cudaFuncSetAttribute(k_fused<0>, cudaFuncAttributeMaxDynamicSharedMemorySize, SMEM_BYTES);
  cudaFuncSetAttribute(k_fused<128>, cudaFuncAttributeMaxDynamicSharedMemorySize, SMEM_BYTES);
  cudaLaunchConfig_t cfg = {132, 512, SMEM_BYTES};
  cudaLaunchAttribute at = {cudaLaunchAttributeClusterDimension};
  at.val.clusterDim.x = 2; at.val.clusterDim.y = at.val.clusterDim.z = 1;
  cfg.attrs = &at; cfg.numAttrs = 1;
  int nc = 0;
  cudaOccupancyMaxActiveClusters(&nc, k_fused<0>, &cfg);
  Ptrs P = {c, ssmd, pg, {0x676360, 0x746209}, {}, 32, 3, 0, B_EMPTY + 32, 0 | 0 << 16, 0, {}, 0x33511, 0, 11400, 900, 1.f};
  const char *win = "4444444444443444444", *ho = "abcdefghijklmnopqrstuvwxyz{|}~";
  memset(P.hl, 255, sizeof(P.hl));
  for (int k = 0, n = 0; k < 30; k++) {
    const int i = ho[k] - 'a';
    if (i >= 20 || !(M8 >> i / 4 & 1)) ((uint8_t*)P.hl)[n++] = i;
  }
  for (int e = 0; e < NL; e++) {
    auto size = [](int i) { return i < 0 ? 8 : ORDER[2 * i] == 'w' ? 10 : 4; };
    int i = e, sum = 0, g = 2 * load_bar(e) + 1;
    while (i >= -1 && sum + size(i) <= 4 * (win[e] - '0')) sum += size(i--);
    for (; i >= -1; i--) {
      bool ok = i < e;
      for (int k = e; k < NL; k++) ok = ok && load_bar(k) != load_bar(i);
      if (ok) { g = 2 * load_bar(i); break; }
    }
    ((uint8_t*)P.gate)[e] = g;
  }
  for (int u = 0; u < 30; u++) P.wdep[u] = (u < 4 ? B_FL + 1 + u / 3 : u < 6 ? B_G : B_EMPTY + (u < 26 ? (u - 6) | 1 : u - 6)) | (u >= 20) << 8 | u % 6 << 9 | (u < 20 ? 3 * (~u & 1) : 1 + (u >= 26)) << 14 | (u < 20 ? 32 * u : 64 * (second(u - 20) % 10)) << 16;
  const int adep[14] = {B_PEMPTY, B_PEMPTY, B_PFULL + 4, B_PEMPTY + 1, B_PEMPTY + 2, B_EMPTY + 5, B_EMPTY + 7, B_PEMPTY + 3, B_EMPTY + 2 * UVS + 1, B_EMPTY + 2 * UVS + 1, B_EMPTY + 20, B_EMPTY + 21, B_EMPTY + 22, B_EMPTY + 23};
  const char *ad = "--*--d----uvwx", *wd = "255679:<=>?@", *hd = "789;;>?@A";
  for (int n = 0; n < 14; n++) P.adep[n] = adep[n] | (ad[n] == '-' ? adep[n] : ad[n] == '*' ? B_PFULL + 3 : B_EMPTY + ad[n] - 'a') << 8 | (n < 10 ? 2 * n : n + 16) << 16 | n % 10 << 21 | a_at(n) / UNIT << 25;
  for (int v = 0; v < 12; v++) P.w2t[v] = make_uint2(w2_desc(v), B_EMPTY + 20 + wd[v] - '0');
  for (int m = 0; m < 9; m++) { P.hid[0][m] = hid_at(m, 0) | m / 3 * 4 | (m % 3 + 1); P.hid[1][m] = hid_at(m, 1) | m / 3 * 4 | (m % 3 + 1); P.hid[2][m] = B_EMPTY + 20 + hd[m] - '0'; }
  if (nc < 66) k_fused<128><<<4, 512, SMEM_BYTES, cudaStreamPerThread>>>(P, maps);
  k_fused<0><<<nc < 66 ? 128 : 132, 512, SMEM_BYTES, cudaStreamPerThread>>>(P, maps);
}
```

```cpp
#include <cuda_runtime.h>
#include <cuda.h>
#include <cuda_bf16.h>
#include <stdint.h>
#include <stdlib.h>
#include <string.h>

typedef __nv_bfloat16 bf16;
constexpr int S_ = 2048, D_ = 640, F_ = 1536;

struct Scratch {
  uint32_t st1[2][1024];
  uint32_t st2[32][4][128];
  uint32_t modc[128][5][32];
  uint2 modv[3][D_];
  uint32_t uv[8][3072];
  unsigned hint[9][8][32];
  unsigned xsh[5][8][32], hhf[256 * 8], key[256];
  uint4 xr[D_ * 256];
  uint4 qt[D_ * 256];
  uint4 xs[D_ * 256];
  uint4 x1[2][D_ * 256];
  uint4 hh[32 * 8 * 1536];
};
__device__ __align__(1024) Scratch g_s;

__device__ __forceinline__ uint32_t smem_u32(const void* p) { return (uint32_t)__cvta_generic_to_shared(p); }
__device__ __forceinline__ void mbar_expect_tx(uint32_t b, uint32_t n) { asm volatile("mbarrier.arrive.expect_tx.shared::cta.b64 _, [%0], %1;" ::"r"(b), "r"(n) : "memory"); }
__device__ __forceinline__ void mbar_arrive(uint32_t b) { asm volatile("mbarrier.arrive.shared::cta.b64 _, [%0];" ::"r"(b) : "memory"); }
__device__ __forceinline__ void mbar_arrive2(uint32_t b) { asm volatile("mbarrier.arrive.shared::cta.b64 _, [%0], 2;" ::"r"(b) : "memory"); }
__device__ __forceinline__ uint32_t mapa(uint32_t a, uint32_t cta) { uint32_t r; asm volatile("mapa.shared::cluster.u32 %0, %1, %2;" : "=r"(r) : "r"(a), "r"(cta)); return r; }
__device__ __forceinline__ void mbar_arrive_remote(uint32_t rb) { asm volatile("mbarrier.arrive.shared::cluster.b64 _, [%0];" ::"r"(rb) : "memory"); }
constexpr int SPIN_LIMIT = 1 << 16;
template <int N> __device__ __forceinline__ void mbar_init(uint32_t b, uint32_t count) {
#pragma unroll
  for (int i = 0; i < N; i++) asm volatile("mbarrier.init.shared::cta.b64 [%0], %1;" ::"r"(b + 8 * i), "r"(count) : "memory");
}
__device__ __forceinline__ bool elect() { uint32_t p; asm volatile("{.reg .pred q; elect.sync _|q, 0xffffffff; selp.u32 %0, 1, 0, q;}" : "=r"(p)); return p; }
__device__ __forceinline__ void arrive1(uint32_t b) { __syncwarp(); if (elect()) mbar_arrive(b); }
__device__ __forceinline__ bool mbar_test(uint32_t b) {
  uint32_t ok;
  asm volatile("{.reg .pred p; mbarrier.test_wait.parity.shared::cta.b64 p, [%1], 0; selp.u32 %0,1,0,p;}" : "=r"(ok) : "r"(b) : "memory");
  return ok;
}
#define WAIT_LOOP(sem) "{.reg .pred p; mov.u32 %0, 0; W: mbarrier.try_wait.parity" sem ".shared::cta.b64 p, [%1], %2; @p bra.uni D; add.u32 %0, %0, 1; setp.lt.u32 p, %0, %3; @p bra.uni W; D:}"
__device__ __forceinline__ void mbar_wait(uint32_t b, uint32_t ph = 0) {
  int it;
  asm volatile(WAIT_LOOP("") : "=&r"(it) : "r"(b), "r"(ph), "n"(SPIN_LIMIT) : "memory");
}
__device__ __forceinline__ void mbar_wait_cluster(uint32_t b, uint32_t ph = 0) {
  int it;
  asm volatile(WAIT_LOOP(".acquire.cluster") : "=&r"(it) : "r"(b), "r"(ph), "n"(SPIN_LIMIT) : "memory");
}
__device__ __forceinline__ void wait_clock(uint32_t t) {
  asm volatile("{.reg .pred p; .reg .s32 d; W: mov.u32 d, %%clock; sub.s32 d, d, %0; setp.lt.s32 p, d, 0; @p bra.uni W;}" ::"r"(t) : "memory");
}
__device__ __forceinline__ void tma2d(uint32_t dst, const CUtensorMap* m, int c0, int c1, uint32_t bar) {
  asm volatile("cp.async.bulk.tensor.2d.shared::cluster.global.mbarrier::complete_tx::bytes [%0], [%1, {%3,%4}], [%2];" ::"r"(dst), "l"(m), "r"(bar), "r"(c0), "r"(c1) : "memory");
}
__device__ __forceinline__ void tma3d(uint32_t dst, const CUtensorMap* m, int c0, int c1, int c2, uint32_t bar) {
  asm volatile("cp.async.bulk.tensor.3d.shared::cluster.global.mbarrier::complete_tx::bytes [%0], [%1, {%3,%4,%5}], [%2];" ::"r"(dst), "l"(m), "r"(bar), "r"(c0), "r"(c1), "r"(c2) : "memory");
}
__device__ __forceinline__ void tma5d(uint32_t dst, const CUtensorMap* m, int c0, int c4, uint32_t bar) {
  asm volatile("cp.async.bulk.tensor.5d.shared::cluster.global.mbarrier::complete_tx::bytes [%0], [%1, {%4,%3,%3,%3,%5}], [%2];" ::"r"(dst), "l"(m), "r"(bar), "r"(0), "r"(c0), "r"(c4) : "memory");
}
__device__ __forceinline__ void tma2d_store(const CUtensorMap* m, int c0, int c1, uint32_t src) {
  asm volatile("cp.async.bulk.tensor.2d.global.shared::cta.bulk_group [%0, {%2,%3}], [%1];" ::"l"(m), "r"(src), "r"(c0), "r"(c1) : "memory");
}
__device__ __forceinline__ void bulk_load(uint32_t dst, const void* src, uint32_t bytes, uint32_t bar) {
  asm volatile("cp.async.bulk.shared::cluster.global.mbarrier::complete_tx::bytes [%0], [%1], %2, [%3];" ::"r"(dst), "l"(src), "r"(bytes), "r"(bar) : "memory");
}
__device__ __forceinline__ void prefetch_map(const CUtensorMap* m) { asm volatile("prefetch.tensormap [%0];" ::"l"(m) : "memory"); }
__device__ __forceinline__ void bulk_commit() { asm volatile("cp.async.bulk.commit_group;" ::: "memory"); }
__device__ __forceinline__ void bulk_wait_read() { asm volatile("cp.async.bulk.wait_group.read 0;" ::: "memory"); }
__device__ __forceinline__ void fence_async_smem() { asm volatile("fence.proxy.async.shared::cta;" ::: "memory"); }
__device__ __forceinline__ void fence_async_all() { asm volatile("fence.proxy.async.global;" ::: "memory"); }
__device__ __forceinline__ void named_bar(int id, int n) { asm volatile("bar.sync %0, %1;" ::"r"(id), "r"(n) : "memory"); }
__device__ __forceinline__ bool bar_all(int id, bool v) {
  uint32_t r;
  asm volatile("{.reg .pred p, q; setp.ne.u32 p, %2, 0; bar.red.and.pred q, %1, 128, p; selp.u32 %0, 1, 0, q;}" : "=r"(r) : "r"(id), "r"((uint32_t)v) : "memory");
  return __all_sync(~0u, r);
}
__device__ __forceinline__ void cluster_wait() { asm volatile("barrier.cluster.wait.aligned;" ::: "memory"); }
__device__ __forceinline__ void wg_fence() { asm volatile("wgmma.fence.sync.aligned;" ::: "memory"); }
__device__ __forceinline__ void wg_commit() { asm volatile("wgmma.commit_group.sync.aligned;" ::: "memory"); }
template <int N> __device__ __forceinline__ void wg_wait() { asm volatile("wgmma.wait_group.sync.aligned %0;" ::"n"(N) : "memory"); }
template <int N> __device__ __forceinline__ void fence_regs(float (&a)[N]) {
#pragma unroll
  for (int i = 0; i < N; i++) asm volatile("" : "+f"(a[i])::"memory");
}
__device__ __forceinline__ uint64_t mkdesc(uint32_t addr, uint32_t lbo, uint32_t sbo, uint32_t swz) {
  uint32_t lo = (addr >> 4) | ((lbo >> 4) << 16), hi = (sbo >> 4) | (swz << 30);
  return ((uint64_t)hi << 32) | lo;
}
__device__ __forceinline__ void stmatrix_x4(uint32_t a, uint32_t r0, uint32_t r1, uint32_t r2, uint32_t r3) {
  asm volatile("stmatrix.sync.aligned.m8n8.x4.shared.b16 [%0], {%1,%2,%3,%4};" ::"r"(a), "r"(r0), "r"(r1), "r"(r2), "r"(r3) : "memory");
}
__device__ __forceinline__ void stmatrix_x4_t(uint32_t a, uint32_t r0, uint32_t r1, uint32_t r2, uint32_t r3) {
  asm volatile("stmatrix.sync.aligned.m8n8.x4.trans.shared.b16 [%0], {%1,%2,%3,%4};" ::"r"(a), "r"(r0), "r"(r1), "r"(r2), "r"(r3) : "memory");
}
__device__ __forceinline__ void ldmatrix_x4_t(uint32_t* r, uint32_t a) {
  asm volatile("ldmatrix.sync.aligned.m8n8.x4.trans.shared.b16 {%0,%1,%2,%3}, [%4];" : "=r"(r[0]), "=r"(r[1]), "=r"(r[2]), "=r"(r[3]) : "r"(a) : "memory");
}
__device__ __forceinline__ uint32_t lds32(uint32_t a) { uint32_t v; asm volatile("ld.shared.b32 %0, [%1];" : "=r"(v) : "r"(a) : "memory"); return v; }
__device__ __forceinline__ uint2 lds64(uint32_t a) { uint2 v; asm volatile("ld.shared.v2.b32 {%0,%1}, [%2];" : "=r"(v.x), "=r"(v.y) : "r"(a) : "memory"); return v; }
__device__ __forceinline__ uint4 lds128(uint32_t a) { uint4 v; asm volatile("ld.shared.v4.b32 {%0,%1,%2,%3}, [%4];" : "=r"(v.x), "=r"(v.y), "=r"(v.z), "=r"(v.w) : "r"(a) : "memory"); return v; }
__device__ __forceinline__ void sts32(uint32_t a, uint32_t v) { asm volatile("st.shared.b32 [%0], %1;" ::"r"(a), "r"(v) : "memory"); }
__device__ __forceinline__ void sts64(uint32_t a, uint32_t x, uint32_t y) { asm volatile("st.shared.v2.b32 [%0], {%1,%2};" ::"r"(a), "r"(x), "r"(y) : "memory"); }
__device__ __forceinline__ void sts128(uint32_t a, uint32_t x, uint32_t y, uint32_t z, uint32_t w) { asm volatile("st.shared.v4.b32 [%0], {%1,%2,%3,%4};" ::"r"(a), "r"(x), "r"(y), "r"(z), "r"(w) : "memory"); }
__device__ __forceinline__ uint4 ld_relaxed128(const void* p) { uint4 v; asm volatile("ld.relaxed.gpu.global.v4.u32 {%0,%1,%2,%3}, [%4];" : "=r"(v.x), "=r"(v.y), "=r"(v.z), "=r"(v.w) : "l"(p) : "memory"); return v; }
__device__ __forceinline__ uint2 ld_relaxed64(const void* p) { uint2 v; asm volatile("ld.relaxed.gpu.global.v2.u32 {%0,%1}, [%2];" : "=r"(v.x), "=r"(v.y) : "l"(p) : "memory"); return v; }
__device__ __forceinline__ uint32_t ld_relaxed32(const void* p) { uint32_t v; asm volatile("ld.relaxed.gpu.global.u32 %0, [%1];" : "=r"(v) : "l"(p) : "memory"); return v; }
__device__ __forceinline__ void st_relaxed128(void* p, uint32_t x, uint32_t y, uint32_t z, uint32_t w) { asm volatile("st.relaxed.gpu.global.v4.u32 [%0], {%1,%2,%3,%4};" ::"l"(p), "r"(x), "r"(y), "r"(z), "r"(w) : "memory"); }
__device__ __forceinline__ void st_relaxed32(void* p, uint32_t x) { asm volatile("st.relaxed.gpu.global.u32 [%0], %1;" ::"l"(p), "r"(x) : "memory"); }
__device__ __forceinline__ void red_hint(unsigned* p) { asm volatile("red.relaxed.gpu.global.add.u32 [%0], 1;" ::"l"(p) : "memory"); }
__device__ __forceinline__ void publish(uint32_t* p, uint32_t x) { asm volatile("{.reg .b32 t; atom.relaxed.gpu.global.exch.b32 t, [%0], %1;}" ::"l"(p), "r"(x) : "memory"); }
__device__ __forceinline__ uint32_t ldg32(const void* p) { uint32_t v; asm volatile("ld.global.nc.L1::no_allocate.b32 %0, [%1];" : "=r"(v) : "l"(p)); return v; }
__device__ __forceinline__ uint32_t pack_bf16(float lo, float hi) { uint32_t r; asm("cvt.rn.bf16x2.f32 %0, %1, %2;" : "=r"(r) : "f"(hi), "f"(lo)); return r; }
__device__ __forceinline__ float bf_lo(uint32_t v) { return __uint_as_float(v << 16); }
__device__ __forceinline__ float bf_hi(uint32_t v) { return __uint_as_float(v & 0xFFFF0000u); }
__device__ __forceinline__ uint32_t bmul2(uint32_t a, uint32_t b) { uint32_t r; asm("mul.rn.bf16x2 %0, %1, %2;" : "=r"(r) : "r"(a), "r"(b)); return r; }
__device__ __forceinline__ uint32_t badd2(uint32_t a, uint32_t b) { uint32_t r; asm("add.rn.bf16x2 %0, %1, %2;" : "=r"(r) : "r"(a), "r"(b)); return r; }
__device__ __forceinline__ uint32_t bfma2(uint32_t a, uint32_t b, uint32_t c) { uint32_t r; asm("fma.rn.bf16x2 %0, %1, %2, %3;" : "=r"(r) : "r"(a), "r"(b), "r"(c)); return r; }
__device__ __forceinline__ uint32_t set_tag(uint32_t x, uint32_t mask, uint32_t e) { uint32_t r; asm("lop3.b32 %0, %1, %2, %3, 0xB8;" : "=r"(r) : "r"(x), "r"(mask), "r"(e)); return r; }
__device__ __forceinline__ uint32_t opaque(uint32_t x) { asm volatile("" : "+r"(x)); return x; }
__device__ __forceinline__ float rbf(float x) { return __bfloat162float(__float2bfloat16(x)); }
__device__ __forceinline__ float silu_f(float x) {
  float e, r;
  asm("ex2.approx.ftz.f32 %0, %1;" : "=f"(e) : "f"(x * -1.4426950408889634f));
  asm("rcp.approx.ftz.f32 %0, %1;" : "=f"(r) : "f"(1.f + e));
  return x * r;
}
__device__ __forceinline__ float silu2(float g, float a, float b) {
  float t;
  asm("tanh.approx.f32 %0, %1;" : "=f"(t) : "f"(g * a));
  return fmaf(g * b, t, g * b);
}
__device__ __forceinline__ void pin(int off, uint32_t x) { asm volatile("{.reg .pred p; setp.lt.s32 p, %0, 0; @p st.shared.b32 [%0], %1;}" ::"r"(off), "r"(x) : "memory"); }
__device__ __forceinline__ void pin4(int off, const uint32_t* x) { asm volatile("{.reg .pred p; setp.lt.s32 p, %0, 0; @p st.shared.v4.b32 [%0], {%1,%2,%3,%4};}" ::"r"(off), "r"(x[0]), "r"(x[1]), "r"(x[2]), "r"(x[3]) : "memory"); }
__device__ __forceinline__ void split(int x, int n) { asm volatile("{.reg .pred p; setp.eq.s32 p, %0, %1; @p trap;}" ::"r"(x), "r"(~n) : "memory"); }
__device__ __forceinline__ void ln_final(float s, float q, float& m, float& sd) {
  m = s * (1.f / D_);
  asm("sqrt.approx.f32 %0, %1;" : "=f"(sd) : "f"(rbf(rbf(fmaxf(fmaf(-m, m, q * (1.f / D_)), 0.f)) + 1e-5f)));
  sd = rbf(sd);
}
__device__ __forceinline__ float rcpf(float x) { float r; asm("rcp.approx.f32 %0, %1;" : "=f"(r) : "f"(x)); return r; }

__device__ __forceinline__ void wg_rs16_0(float* d, const uint32_t* a, uint64_t db, int sc) {
  asm volatile("{.reg .pred p; setp.ne.b32 p, %13, 0; wgmma.mma_async.sync.aligned.m64n16k16.f32.bf16.bf16 {%0,%1,%2,%3,%4,%5,%6,%7}, {%8,%9,%10,%11}, %12, p, 1, 1, 0;}"
    : "+f"(d[0]),"+f"(d[1]),"+f"(d[2]),"+f"(d[3]),"+f"(d[4]),"+f"(d[5]),"+f"(d[6]),"+f"(d[7]) : "r"(a[0]),"r"(a[1]),"r"(a[2]),"r"(a[3]),"l"(db),"r"(sc));
}
__device__ __forceinline__ void wg_rs32_0(float* d, const uint32_t* a, uint64_t db, int sc) {
  asm volatile("{.reg .pred p; setp.ne.b32 p, %21, 0; wgmma.mma_async.sync.aligned.m64n32k16.f32.bf16.bf16 {%0,%1,%2,%3,%4,%5,%6,%7,%8,%9,%10,%11,%12,%13,%14,%15}, {%16,%17,%18,%19}, %20, p, 1, 1, 0;}"
    : "+f"(d[0]),"+f"(d[1]),"+f"(d[2]),"+f"(d[3]),"+f"(d[4]),"+f"(d[5]),"+f"(d[6]),"+f"(d[7]),"+f"(d[8]),"+f"(d[9]),"+f"(d[10]),"+f"(d[11]),"+f"(d[12]),"+f"(d[13]),"+f"(d[14]),"+f"(d[15]) : "r"(a[0]),"r"(a[1]),"r"(a[2]),"r"(a[3]),"l"(db),"r"(sc));
}
__device__ __forceinline__ void wg_rs48_0(float* d, const uint32_t* a, uint64_t db, int sc) {
  asm volatile("{.reg .pred p; setp.ne.b32 p, %29, 0; wgmma.mma_async.sync.aligned.m64n48k16.f32.bf16.bf16 {%0,%1,%2,%3,%4,%5,%6,%7,%8,%9,%10,%11,%12,%13,%14,%15,%16,%17,%18,%19,%20,%21,%22,%23}, {%24,%25,%26,%27}, %28, p, 1, 1, 0;}"
    : "+f"(d[0]),"+f"(d[1]),"+f"(d[2]),"+f"(d[3]),"+f"(d[4]),"+f"(d[5]),"+f"(d[6]),"+f"(d[7]),"+f"(d[8]),"+f"(d[9]),"+f"(d[10]),"+f"(d[11]),"+f"(d[12]),"+f"(d[13]),"+f"(d[14]),"+f"(d[15]),"+f"(d[16]),"+f"(d[17]),"+f"(d[18]),"+f"(d[19]),"+f"(d[20]),"+f"(d[21]),"+f"(d[22]),"+f"(d[23]) : "r"(a[0]),"r"(a[1]),"r"(a[2]),"r"(a[3]),"l"(db),"r"(sc));
}
__device__ __forceinline__ void wg_rs64_0(float* d, const uint32_t* a, uint64_t db, int sc) {
  asm volatile("{.reg .pred p; setp.ne.b32 p, %37, 0; wgmma.mma_async.sync.aligned.m64n64k16.f32.bf16.bf16 {%0,%1,%2,%3,%4,%5,%6,%7,%8,%9,%10,%11,%12,%13,%14,%15,%16,%17,%18,%19,%20,%21,%22,%23,%24,%25,%26,%27,%28,%29,%30,%31}, {%32,%33,%34,%35}, %36, p, 1, 1, 0;}"
    : "+f"(d[0]),"+f"(d[1]),"+f"(d[2]),"+f"(d[3]),"+f"(d[4]),"+f"(d[5]),"+f"(d[6]),"+f"(d[7]),"+f"(d[8]),"+f"(d[9]),"+f"(d[10]),"+f"(d[11]),"+f"(d[12]),"+f"(d[13]),"+f"(d[14]),"+f"(d[15]),"+f"(d[16]),"+f"(d[17]),"+f"(d[18]),"+f"(d[19]),"+f"(d[20]),"+f"(d[21]),"+f"(d[22]),"+f"(d[23]),"+f"(d[24]),"+f"(d[25]),"+f"(d[26]),"+f"(d[27]),"+f"(d[28]),"+f"(d[29]),"+f"(d[30]),"+f"(d[31]) : "r"(a[0]),"r"(a[1]),"r"(a[2]),"r"(a[3]),"l"(db),"r"(sc));
}
__device__ __forceinline__ void wg_rs80_0(float* d, const uint32_t* a, uint64_t db, int sc) {
  asm volatile("{.reg .pred p; setp.ne.b32 p, %45, 0; wgmma.mma_async.sync.aligned.m64n80k16.f32.bf16.bf16 {%0,%1,%2,%3,%4,%5,%6,%7,%8,%9,%10,%11,%12,%13,%14,%15,%16,%17,%18,%19,%20,%21,%22,%23,%24,%25,%26,%27,%28,%29,%30,%31,%32,%33,%34,%35,%36,%37,%38,%39}, {%40,%41,%42,%43}, %44, p, 1, 1, 0;}"
    : "+f"(d[0]),"+f"(d[1]),"+f"(d[2]),"+f"(d[3]),"+f"(d[4]),"+f"(d[5]),"+f"(d[6]),"+f"(d[7]),"+f"(d[8]),"+f"(d[9]),"+f"(d[10]),"+f"(d[11]),"+f"(d[12]),"+f"(d[13]),"+f"(d[14]),"+f"(d[15]),"+f"(d[16]),"+f"(d[17]),"+f"(d[18]),"+f"(d[19]),"+f"(d[20]),"+f"(d[21]),"+f"(d[22]),"+f"(d[23]),"+f"(d[24]),"+f"(d[25]),"+f"(d[26]),"+f"(d[27]),"+f"(d[28]),"+f"(d[29]),"+f"(d[30]),"+f"(d[31]),"+f"(d[32]),"+f"(d[33]),"+f"(d[34]),"+f"(d[35]),"+f"(d[36]),"+f"(d[37]),"+f"(d[38]),"+f"(d[39]) : "r"(a[0]),"r"(a[1]),"r"(a[2]),"r"(a[3]),"l"(db),"r"(sc));
}
__device__ __forceinline__ void wg_rs96_0(float* d, const uint32_t* a, uint64_t db, int sc) {
  asm volatile("{.reg .pred p; setp.ne.b32 p, %53, 0; wgmma.mma_async.sync.aligned.m64n96k16.f32.bf16.bf16 {%0,%1,%2,%3,%4,%5,%6,%7,%8,%9,%10,%11,%12,%13,%14,%15,%16,%17,%18,%19,%20,%21,%22,%23,%24,%25,%26,%27,%28,%29,%30,%31,%32,%33,%34,%35,%36,%37,%38,%39,%40,%41,%42,%43,%44,%45,%46,%47}, {%48,%49,%50,%51}, %52, p, 1, 1, 0;}"
    : "+f"(d[0]),"+f"(d[1]),"+f"(d[2]),"+f"(d[3]),"+f"(d[4]),"+f"(d[5]),"+f"(d[6]),"+f"(d[7]),"+f"(d[8]),"+f"(d[9]),"+f"(d[10]),"+f"(d[11]),"+f"(d[12]),"+f"(d[13]),"+f"(d[14]),"+f"(d[15]),"+f"(d[16]),"+f"(d[17]),"+f"(d[18]),"+f"(d[19]),"+f"(d[20]),"+f"(d[21]),"+f"(d[22]),"+f"(d[23]),"+f"(d[24]),"+f"(d[25]),"+f"(d[26]),"+f"(d[27]),"+f"(d[28]),"+f"(d[29]),"+f"(d[30]),"+f"(d[31]),"+f"(d[32]),"+f"(d[33]),"+f"(d[34]),"+f"(d[35]),"+f"(d[36]),"+f"(d[37]),"+f"(d[38]),"+f"(d[39]),"+f"(d[40]),"+f"(d[41]),"+f"(d[42]),"+f"(d[43]),"+f"(d[44]),"+f"(d[45]),"+f"(d[46]),"+f"(d[47]) : "r"(a[0]),"r"(a[1]),"r"(a[2]),"r"(a[3]),"l"(db),"r"(sc));
}
__device__ __forceinline__ void wg_rs112_0(float* d, const uint32_t* a, uint64_t db, int sc) {
  asm volatile("{.reg .pred p; setp.ne.b32 p, %61, 0; wgmma.mma_async.sync.aligned.m64n112k16.f32.bf16.bf16 {%0,%1,%2,%3,%4,%5,%6,%7,%8,%9,%10,%11,%12,%13,%14,%15,%16,%17,%18,%19,%20,%21,%22,%23,%24,%25,%26,%27,%28,%29,%30,%31,%32,%33,%34,%35,%36,%37,%38,%39,%40,%41,%42,%43,%44,%45,%46,%47,%48,%49,%50,%51,%52,%53,%54,%55}, {%56,%57,%58,%59}, %60, p, 1, 1, 0;}"
    : "+f"(d[0]),"+f"(d[1]),"+f"(d[2]),"+f"(d[3]),"+f"(d[4]),"+f"(d[5]),"+f"(d[6]),"+f"(d[7]),"+f"(d[8]),"+f"(d[9]),"+f"(d[10]),"+f"(d[11]),"+f"(d[12]),"+f"(d[13]),"+f"(d[14]),"+f"(d[15]),"+f"(d[16]),"+f"(d[17]),"+f"(d[18]),"+f"(d[19]),"+f"(d[20]),"+f"(d[21]),"+f"(d[22]),"+f"(d[23]),"+f"(d[24]),"+f"(d[25]),"+f"(d[26]),"+f"(d[27]),"+f"(d[28]),"+f"(d[29]),"+f"(d[30]),"+f"(d[31]),"+f"(d[32]),"+f"(d[33]),"+f"(d[34]),"+f"(d[35]),"+f"(d[36]),"+f"(d[37]),"+f"(d[38]),"+f"(d[39]),"+f"(d[40]),"+f"(d[41]),"+f"(d[42]),"+f"(d[43]),"+f"(d[44]),"+f"(d[45]),"+f"(d[46]),"+f"(d[47]),"+f"(d[48]),"+f"(d[49]),"+f"(d[50]),"+f"(d[51]),"+f"(d[52]),"+f"(d[53]),"+f"(d[54]),"+f"(d[55]) : "r"(a[0]),"r"(a[1]),"r"(a[2]),"r"(a[3]),"l"(db),"r"(sc));
}
__device__ __forceinline__ void wg_rs128_0(float* d, const uint32_t* a, uint64_t db, int sc) {
  asm volatile("{.reg .pred p; setp.ne.b32 p, %69, 0; wgmma.mma_async.sync.aligned.m64n128k16.f32.bf16.bf16 {%0,%1,%2,%3,%4,%5,%6,%7,%8,%9,%10,%11,%12,%13,%14,%15,%16,%17,%18,%19,%20,%21,%22,%23,%24,%25,%26,%27,%28,%29,%30,%31,%32,%33,%34,%35,%36,%37,%38,%39,%40,%41,%42,%43,%44,%45,%46,%47,%48,%49,%50,%51,%52,%53,%54,%55,%56,%57,%58,%59,%60,%61,%62,%63}, {%64,%65,%66,%67}, %68, p, 1, 1, 0;}"
    : "+f"(d[0]),"+f"(d[1]),"+f"(d[2]),"+f"(d[3]),"+f"(d[4]),"+f"(d[5]),"+f"(d[6]),"+f"(d[7]),"+f"(d[8]),"+f"(d[9]),"+f"(d[10]),"+f"(d[11]),"+f"(d[12]),"+f"(d[13]),"+f"(d[14]),"+f"(d[15]),"+f"(d[16]),"+f"(d[17]),"+f"(d[18]),"+f"(d[19]),"+f"(d[20]),"+f"(d[21]),"+f"(d[22]),"+f"(d[23]),"+f"(d[24]),"+f"(d[25]),"+f"(d[26]),"+f"(d[27]),"+f"(d[28]),"+f"(d[29]),"+f"(d[30]),"+f"(d[31]),"+f"(d[32]),"+f"(d[33]),"+f"(d[34]),"+f"(d[35]),"+f"(d[36]),"+f"(d[37]),"+f"(d[38]),"+f"(d[39]),"+f"(d[40]),"+f"(d[41]),"+f"(d[42]),"+f"(d[43]),"+f"(d[44]),"+f"(d[45]),"+f"(d[46]),"+f"(d[47]),"+f"(d[48]),"+f"(d[49]),"+f"(d[50]),"+f"(d[51]),"+f"(d[52]),"+f"(d[53]),"+f"(d[54]),"+f"(d[55]),"+f"(d[56]),"+f"(d[57]),"+f"(d[58]),"+f"(d[59]),"+f"(d[60]),"+f"(d[61]),"+f"(d[62]),"+f"(d[63]) : "r"(a[0]),"r"(a[1]),"r"(a[2]),"r"(a[3]),"l"(db),"r"(sc));
}
__device__ __forceinline__ void wg_rs144_0(float* d, const uint32_t* a, uint64_t db, int sc) {
  asm volatile("{.reg .pred p; setp.ne.b32 p, %77, 0; wgmma.mma_async.sync.aligned.m64n144k16.f32.bf16.bf16 {%0,%1,%2,%3,%4,%5,%6,%7,%8,%9,%10,%11,%12,%13,%14,%15,%16,%17,%18,%19,%20,%21,%22,%23,%24,%25,%26,%27,%28,%29,%30,%31,%32,%33,%34,%35,%36,%37,%38,%39,%40,%41,%42,%43,%44,%45,%46,%47,%48,%49,%50,%51,%52,%53,%54,%55,%56,%57,%58,%59,%60,%61,%62,%63,%64,%65,%66,%67,%68,%69,%70,%71}, {%72,%73,%74,%75}, %76, p, 1, 1, 0;}"
    : "+f"(d[0]),"+f"(d[1]),"+f"(d[2]),"+f"(d[3]),"+f"(d[4]),"+f"(d[5]),"+f"(d[6]),"+f"(d[7]),"+f"(d[8]),"+f"(d[9]),"+f"(d[10]),"+f"(d[11]),"+f"(d[12]),"+f"(d[13]),"+f"(d[14]),"+f"(d[15]),"+f"(d[16]),"+f"(d[17]),"+f"(d[18]),"+f"(d[19]),"+f"(d[20]),"+f"(d[21]),"+f"(d[22]),"+f"(d[23]),"+f"(d[24]),"+f"(d[25]),"+f"(d[26]),"+f"(d[27]),"+f"(d[28]),"+f"(d[29]),"+f"(d[30]),"+f"(d[31]),"+f"(d[32]),"+f"(d[33]),"+f"(d[34]),"+f"(d[35]),"+f"(d[36]),"+f"(d[37]),"+f"(d[38]),"+f"(d[39]),"+f"(d[40]),"+f"(d[41]),"+f"(d[42]),"+f"(d[43]),"+f"(d[44]),"+f"(d[45]),"+f"(d[46]),"+f"(d[47]),"+f"(d[48]),"+f"(d[49]),"+f"(d[50]),"+f"(d[51]),"+f"(d[52]),"+f"(d[53]),"+f"(d[54]),"+f"(d[55]),"+f"(d[56]),"+f"(d[57]),"+f"(d[58]),"+f"(d[59]),"+f"(d[60]),"+f"(d[61]),"+f"(d[62]),"+f"(d[63]),"+f"(d[64]),"+f"(d[65]),"+f"(d[66]),"+f"(d[67]),"+f"(d[68]),"+f"(d[69]),"+f"(d[70]),"+f"(d[71]) : "r"(a[0]),"r"(a[1]),"r"(a[2]),"r"(a[3]),"l"(db),"r"(sc));
}
__device__ __forceinline__ void wg_rs160_0(float* d, const uint32_t* a, uint64_t db, int sc) {
  asm volatile("{.reg .pred p; setp.ne.b32 p, %85, 0; wgmma.mma_async.sync.aligned.m64n160k16.f32.bf16.bf16 {%0,%1,%2,%3,%4,%5,%6,%7,%8,%9,%10,%11,%12,%13,%14,%15,%16,%17,%18,%19,%20,%21,%22,%23,%24,%25,%26,%27,%28,%29,%30,%31,%32,%33,%34,%35,%36,%37,%38,%39,%40,%41,%42,%43,%44,%45,%46,%47,%48,%49,%50,%51,%52,%53,%54,%55,%56,%57,%58,%59,%60,%61,%62,%63,%64,%65,%66,%67,%68,%69,%70,%71,%72,%73,%74,%75,%76,%77,%78,%79}, {%80,%81,%82,%83}, %84, p, 1, 1, 0;}"
    : "+f"(d[0]),"+f"(d[1]),"+f"(d[2]),"+f"(d[3]),"+f"(d[4]),"+f"(d[5]),"+f"(d[6]),"+f"(d[7]),"+f"(d[8]),"+f"(d[9]),"+f"(d[10]),"+f"(d[11]),"+f"(d[12]),"+f"(d[13]),"+f"(d[14]),"+f"(d[15]),"+f"(d[16]),"+f"(d[17]),"+f"(d[18]),"+f"(d[19]),"+f"(d[20]),"+f"(d[21]),"+f"(d[22]),"+f"(d[23]),"+f"(d[24]),"+f"(d[25]),"+f"(d[26]),"+f"(d[27]),"+f"(d[28]),"+f"(d[29]),"+f"(d[30]),"+f"(d[31]),"+f"(d[32]),"+f"(d[33]),"+f"(d[34]),"+f"(d[35]),"+f"(d[36]),"+f"(d[37]),"+f"(d[38]),"+f"(d[39]),"+f"(d[40]),"+f"(d[41]),"+f"(d[42]),"+f"(d[43]),"+f"(d[44]),"+f"(d[45]),"+f"(d[46]),"+f"(d[47]),"+f"(d[48]),"+f"(d[49]),"+f"(d[50]),"+f"(d[51]),"+f"(d[52]),"+f"(d[53]),"+f"(d[54]),"+f"(d[55]),"+f"(d[56]),"+f"(d[57]),"+f"(d[58]),"+f"(d[59]),"+f"(d[60]),"+f"(d[61]),"+f"(d[62]),"+f"(d[63]),"+f"(d[64]),"+f"(d[65]),"+f"(d[66]),"+f"(d[67]),"+f"(d[68]),"+f"(d[69]),"+f"(d[70]),"+f"(d[71]),"+f"(d[72]),"+f"(d[73]),"+f"(d[74]),"+f"(d[75]),"+f"(d[76]),"+f"(d[77]),"+f"(d[78]),"+f"(d[79]) : "r"(a[0]),"r"(a[1]),"r"(a[2]),"r"(a[3]),"l"(db),"r"(sc));
}
__device__ __forceinline__ void wg_rs176_0(float* d, const uint32_t* a, uint64_t db, int sc) {
  asm volatile("{.reg .pred p; setp.ne.b32 p, %93, 0; wgmma.mma_async.sync.aligned.m64n176k16.f32.bf16.bf16 {%0,%1,%2,%3,%4,%5,%6,%7,%8,%9,%10,%11,%12,%13,%14,%15,%16,%17,%18,%19,%20,%21,%22,%23,%24,%25,%26,%27,%28,%29,%30,%31,%32,%33,%34,%35,%36,%37,%38,%39,%40,%41,%42,%43,%44,%45,%46,%47,%48,%49,%50,%51,%52,%53,%54,%55,%56,%57,%58,%59,%60,%61,%62,%63,%64,%65,%66,%67,%68,%69,%70,%71,%72,%73,%74,%75,%76,%77,%78,%79,%80,%81,%82,%83,%84,%85,%86,%87}, {%88,%89,%90,%91}, %92, p, 1, 1, 0;}"
    : "+f"(d[0]),"+f"(d[1]),"+f"(d[2]),"+f"(d[3]),"+f"(d[4]),"+f"(d[5]),"+f"(d[6]),"+f"(d[7]),"+f"(d[8]),"+f"(d[9]),"+f"(d[10]),"+f"(d[11]),"+f"(d[12]),"+f"(d[13]),"+f"(d[14]),"+f"(d[15]),"+f"(d[16]),"+f"(d[17]),"+f"(d[18]),"+f"(d[19]),"+f"(d[20]),"+f"(d[21]),"+f"(d[22]),"+f"(d[23]),"+f"(d[24]),"+f"(d[25]),"+f"(d[26]),"+f"(d[27]),"+f"(d[28]),"+f"(d[29]),"+f"(d[30]),"+f"(d[31]),"+f"(d[32]),"+f"(d[33]),"+f"(d[34]),"+f"(d[35]),"+f"(d[36]),"+f"(d[37]),"+f"(d[38]),"+f"(d[39]),"+f"(d[40]),"+f"(d[41]),"+f"(d[42]),"+f"(d[43]),"+f"(d[44]),"+f"(d[45]),"+f"(d[46]),"+f"(d[47]),"+f"(d[48]),"+f"(d[49]),"+f"(d[50]),"+f"(d[51]),"+f"(d[52]),"+f"(d[53]),"+f"(d[54]),"+f"(d[55]),"+f"(d[56]),"+f"(d[57]),"+f"(d[58]),"+f"(d[59]),"+f"(d[60]),"+f"(d[61]),"+f"(d[62]),"+f"(d[63]),"+f"(d[64]),"+f"(d[65]),"+f"(d[66]),"+f"(d[67]),"+f"(d[68]),"+f"(d[69]),"+f"(d[70]),"+f"(d[71]),"+f"(d[72]),"+f"(d[73]),"+f"(d[74]),"+f"(d[75]),"+f"(d[76]),"+f"(d[77]),"+f"(d[78]),"+f"(d[79]),"+f"(d[80]),"+f"(d[81]),"+f"(d[82]),"+f"(d[83]),"+f"(d[84]),"+f"(d[85]),"+f"(d[86]),"+f"(d[87]) : "r"(a[0]),"r"(a[1]),"r"(a[2]),"r"(a[3]),"l"(db),"r"(sc));
}
__device__ __forceinline__ void wg_rs192_0(float* d, const uint32_t* a, uint64_t db, int sc) {
  asm volatile("{.reg .pred p; setp.ne.b32 p, %101, 0; wgmma.mma_async.sync.aligned.m64n192k16.f32.bf16.bf16 {%0,%1,%2,%3,%4,%5,%6,%7,%8,%9,%10,%11,%12,%13,%14,%15,%16,%17,%18,%19,%20,%21,%22,%23,%24,%25,%26,%27,%28,%29,%30,%31,%32,%33,%34,%35,%36,%37,%38,%39,%40,%41,%42,%43,%44,%45,%46,%47,%48,%49,%50,%51,%52,%53,%54,%55,%56,%57,%58,%59,%60,%61,%62,%63,%64,%65,%66,%67,%68,%69,%70,%71,%72,%73,%74,%75,%76,%77,%78,%79,%80,%81,%82,%83,%84,%85,%86,%87,%88,%89,%90,%91,%92,%93,%94,%95}, {%96,%97,%98,%99}, %100, p, 1, 1, 0;}"
    : "+f"(d[0]),"+f"(d[1]),"+f"(d[2]),"+f"(d[3]),"+f"(d[4]),"+f"(d[5]),"+f"(d[6]),"+f"(d[7]),"+f"(d[8]),"+f"(d[9]),"+f"(d[10]),"+f"(d[11]),"+f"(d[12]),"+f"(d[13]),"+f"(d[14]),"+f"(d[15]),"+f"(d[16]),"+f"(d[17]),"+f"(d[18]),"+f"(d[19]),"+f"(d[20]),"+f"(d[21]),"+f"(d[22]),"+f"(d[23]),"+f"(d[24]),"+f"(d[25]),"+f"(d[26]),"+f"(d[27]),"+f"(d[28]),"+f"(d[29]),"+f"(d[30]),"+f"(d[31]),"+f"(d[32]),"+f"(d[33]),"+f"(d[34]),"+f"(d[35]),"+f"(d[36]),"+f"(d[37]),"+f"(d[38]),"+f"(d[39]),"+f"(d[40]),"+f"(d[41]),"+f"(d[42]),"+f"(d[43]),"+f"(d[44]),"+f"(d[45]),"+f"(d[46]),"+f"(d[47]),"+f"(d[48]),"+f"(d[49]),"+f"(d[50]),"+f"(d[51]),"+f"(d[52]),"+f"(d[53]),"+f"(d[54]),"+f"(d[55]),"+f"(d[56]),"+f"(d[57]),"+f"(d[58]),"+f"(d[59]),"+f"(d[60]),"+f"(d[61]),"+f"(d[62]),"+f"(d[63]),"+f"(d[64]),"+f"(d[65]),"+f"(d[66]),"+f"(d[67]),"+f"(d[68]),"+f"(d[69]),"+f"(d[70]),"+f"(d[71]),"+f"(d[72]),"+f"(d[73]),"+f"(d[74]),"+f"(d[75]),"+f"(d[76]),"+f"(d[77]),"+f"(d[78]),"+f"(d[79]),"+f"(d[80]),"+f"(d[81]),"+f"(d[82]),"+f"(d[83]),"+f"(d[84]),"+f"(d[85]),"+f"(d[86]),"+f"(d[87]),"+f"(d[88]),"+f"(d[89]),"+f"(d[90]),"+f"(d[91]),"+f"(d[92]),"+f"(d[93]),"+f"(d[94]),"+f"(d[95]) : "r"(a[0]),"r"(a[1]),"r"(a[2]),"r"(a[3]),"l"(db),"r"(sc));
}
__device__ __forceinline__ void wg_ss192_11(float* d, uint64_t da, uint64_t db, int sc) {
  asm volatile("{.reg .pred p; setp.ne.b32 p, %98, 0; wgmma.mma_async.sync.aligned.m64n192k16.f32.bf16.bf16 {%0,%1,%2,%3,%4,%5,%6,%7,%8,%9,%10,%11,%12,%13,%14,%15,%16,%17,%18,%19,%20,%21,%22,%23,%24,%25,%26,%27,%28,%29,%30,%31,%32,%33,%34,%35,%36,%37,%38,%39,%40,%41,%42,%43,%44,%45,%46,%47,%48,%49,%50,%51,%52,%53,%54,%55,%56,%57,%58,%59,%60,%61,%62,%63,%64,%65,%66,%67,%68,%69,%70,%71,%72,%73,%74,%75,%76,%77,%78,%79,%80,%81,%82,%83,%84,%85,%86,%87,%88,%89,%90,%91,%92,%93,%94,%95}, %96, %97, p, 1, 1, 1, 1;}"
    : "+f"(d[0]),"+f"(d[1]),"+f"(d[2]),"+f"(d[3]),"+f"(d[4]),"+f"(d[5]),"+f"(d[6]),"+f"(d[7]),"+f"(d[8]),"+f"(d[9]),"+f"(d[10]),"+f"(d[11]),"+f"(d[12]),"+f"(d[13]),"+f"(d[14]),"+f"(d[15]),"+f"(d[16]),"+f"(d[17]),"+f"(d[18]),"+f"(d[19]),"+f"(d[20]),"+f"(d[21]),"+f"(d[22]),"+f"(d[23]),"+f"(d[24]),"+f"(d[25]),"+f"(d[26]),"+f"(d[27]),"+f"(d[28]),"+f"(d[29]),"+f"(d[30]),"+f"(d[31]),"+f"(d[32]),"+f"(d[33]),"+f"(d[34]),"+f"(d[35]),"+f"(d[36]),"+f"(d[37]),"+f"(d[38]),"+f"(d[39]),"+f"(d[40]),"+f"(d[41]),"+f"(d[42]),"+f"(d[43]),"+f"(d[44]),"+f"(d[45]),"+f"(d[46]),"+f"(d[47]),"+f"(d[48]),"+f"(d[49]),"+f"(d[50]),"+f"(d[51]),"+f"(d[52]),"+f"(d[53]),"+f"(d[54]),"+f"(d[55]),"+f"(d[56]),"+f"(d[57]),"+f"(d[58]),"+f"(d[59]),"+f"(d[60]),"+f"(d[61]),"+f"(d[62]),"+f"(d[63]),"+f"(d[64]),"+f"(d[65]),"+f"(d[66]),"+f"(d[67]),"+f"(d[68]),"+f"(d[69]),"+f"(d[70]),"+f"(d[71]),"+f"(d[72]),"+f"(d[73]),"+f"(d[74]),"+f"(d[75]),"+f"(d[76]),"+f"(d[77]),"+f"(d[78]),"+f"(d[79]),"+f"(d[80]),"+f"(d[81]),"+f"(d[82]),"+f"(d[83]),"+f"(d[84]),"+f"(d[85]),"+f"(d[86]),"+f"(d[87]),"+f"(d[88]),"+f"(d[89]),"+f"(d[90]),"+f"(d[91]),"+f"(d[92]),"+f"(d[93]),"+f"(d[94]),"+f"(d[95]) : "l"(da),"l"(db),"r"(sc));
}
__device__ __forceinline__ void wg_ss192_01(float* d, uint64_t da, uint64_t db, int sc) {
  asm volatile("{.reg .pred p; setp.ne.b32 p, %98, 0; wgmma.mma_async.sync.aligned.m64n192k16.f32.bf16.bf16 {%0,%1,%2,%3,%4,%5,%6,%7,%8,%9,%10,%11,%12,%13,%14,%15,%16,%17,%18,%19,%20,%21,%22,%23,%24,%25,%26,%27,%28,%29,%30,%31,%32,%33,%34,%35,%36,%37,%38,%39,%40,%41,%42,%43,%44,%45,%46,%47,%48,%49,%50,%51,%52,%53,%54,%55,%56,%57,%58,%59,%60,%61,%62,%63,%64,%65,%66,%67,%68,%69,%70,%71,%72,%73,%74,%75,%76,%77,%78,%79,%80,%81,%82,%83,%84,%85,%86,%87,%88,%89,%90,%91,%92,%93,%94,%95}, %96, %97, p, 1, 1, 0, 1;}"
    : "+f"(d[0]),"+f"(d[1]),"+f"(d[2]),"+f"(d[3]),"+f"(d[4]),"+f"(d[5]),"+f"(d[6]),"+f"(d[7]),"+f"(d[8]),"+f"(d[9]),"+f"(d[10]),"+f"(d[11]),"+f"(d[12]),"+f"(d[13]),"+f"(d[14]),"+f"(d[15]),"+f"(d[16]),"+f"(d[17]),"+f"(d[18]),"+f"(d[19]),"+f"(d[20]),"+f"(d[21]),"+f"(d[22]),"+f"(d[23]),"+f"(d[24]),"+f"(d[25]),"+f"(d[26]),"+f"(d[27]),"+f"(d[28]),"+f"(d[29]),"+f"(d[30]),"+f"(d[31]),"+f"(d[32]),"+f"(d[33]),"+f"(d[34]),"+f"(d[35]),"+f"(d[36]),"+f"(d[37]),"+f"(d[38]),"+f"(d[39]),"+f"(d[40]),"+f"(d[41]),"+f"(d[42]),"+f"(d[43]),"+f"(d[44]),"+f"(d[45]),"+f"(d[46]),"+f"(d[47]),"+f"(d[48]),"+f"(d[49]),"+f"(d[50]),"+f"(d[51]),"+f"(d[52]),"+f"(d[53]),"+f"(d[54]),"+f"(d[55]),"+f"(d[56]),"+f"(d[57]),"+f"(d[58]),"+f"(d[59]),"+f"(d[60]),"+f"(d[61]),"+f"(d[62]),"+f"(d[63]),"+f"(d[64]),"+f"(d[65]),"+f"(d[66]),"+f"(d[67]),"+f"(d[68]),"+f"(d[69]),"+f"(d[70]),"+f"(d[71]),"+f"(d[72]),"+f"(d[73]),"+f"(d[74]),"+f"(d[75]),"+f"(d[76]),"+f"(d[77]),"+f"(d[78]),"+f"(d[79]),"+f"(d[80]),"+f"(d[81]),"+f"(d[82]),"+f"(d[83]),"+f"(d[84]),"+f"(d[85]),"+f"(d[86]),"+f"(d[87]),"+f"(d[88]),"+f"(d[89]),"+f"(d[90]),"+f"(d[91]),"+f"(d[92]),"+f"(d[93]),"+f"(d[94]),"+f"(d[95]) : "l"(da),"l"(db),"r"(sc));
}
__device__ __forceinline__ void wg_ss64_11(float* d, uint64_t da, uint64_t db, int sc) {
  asm volatile("{.reg .pred p; setp.ne.b32 p, %34, 0; wgmma.mma_async.sync.aligned.m64n64k16.f32.bf16.bf16 {%0,%1,%2,%3,%4,%5,%6,%7,%8,%9,%10,%11,%12,%13,%14,%15,%16,%17,%18,%19,%20,%21,%22,%23,%24,%25,%26,%27,%28,%29,%30,%31}, %32, %33, p, 1, 1, 1, 1;}"
    : "+f"(d[0]),"+f"(d[1]),"+f"(d[2]),"+f"(d[3]),"+f"(d[4]),"+f"(d[5]),"+f"(d[6]),"+f"(d[7]),"+f"(d[8]),"+f"(d[9]),"+f"(d[10]),"+f"(d[11]),"+f"(d[12]),"+f"(d[13]),"+f"(d[14]),"+f"(d[15]),"+f"(d[16]),"+f"(d[17]),"+f"(d[18]),"+f"(d[19]),"+f"(d[20]),"+f"(d[21]),"+f"(d[22]),"+f"(d[23]),"+f"(d[24]),"+f"(d[25]),"+f"(d[26]),"+f"(d[27]),"+f"(d[28]),"+f"(d[29]),"+f"(d[30]),"+f"(d[31]) : "l"(da),"l"(db),"r"(sc));
}
__device__ __forceinline__ void wg_ss64_01(float* d, uint64_t da, uint64_t db, int sc) {
  asm volatile("{.reg .pred p; setp.ne.b32 p, %34, 0; wgmma.mma_async.sync.aligned.m64n64k16.f32.bf16.bf16 {%0,%1,%2,%3,%4,%5,%6,%7,%8,%9,%10,%11,%12,%13,%14,%15,%16,%17,%18,%19,%20,%21,%22,%23,%24,%25,%26,%27,%28,%29,%30,%31}, %32, %33, p, 1, 1, 0, 1;}"
    : "+f"(d[0]),"+f"(d[1]),"+f"(d[2]),"+f"(d[3]),"+f"(d[4]),"+f"(d[5]),"+f"(d[6]),"+f"(d[7]),"+f"(d[8]),"+f"(d[9]),"+f"(d[10]),"+f"(d[11]),"+f"(d[12]),"+f"(d[13]),"+f"(d[14]),"+f"(d[15]),"+f"(d[16]),"+f"(d[17]),"+f"(d[18]),"+f"(d[19]),"+f"(d[20]),"+f"(d[21]),"+f"(d[22]),"+f"(d[23]),"+f"(d[24]),"+f"(d[25]),"+f"(d[26]),"+f"(d[27]),"+f"(d[28]),"+f"(d[29]),"+f"(d[30]),"+f"(d[31]) : "l"(da),"l"(db),"r"(sc));
}
__device__ __forceinline__ void wg_ss128_11(float* d, uint64_t da, uint64_t db, int sc) {
  asm volatile("{.reg .pred p; setp.ne.b32 p, %66, 0; wgmma.mma_async.sync.aligned.m64n128k16.f32.bf16.bf16 {%0,%1,%2,%3,%4,%5,%6,%7,%8,%9,%10,%11,%12,%13,%14,%15,%16,%17,%18,%19,%20,%21,%22,%23,%24,%25,%26,%27,%28,%29,%30,%31,%32,%33,%34,%35,%36,%37,%38,%39,%40,%41,%42,%43,%44,%45,%46,%47,%48,%49,%50,%51,%52,%53,%54,%55,%56,%57,%58,%59,%60,%61,%62,%63}, %64, %65, p, 1, 1, 1, 1;}"
    : "+f"(d[0]),"+f"(d[1]),"+f"(d[2]),"+f"(d[3]),"+f"(d[4]),"+f"(d[5]),"+f"(d[6]),"+f"(d[7]),"+f"(d[8]),"+f"(d[9]),"+f"(d[10]),"+f"(d[11]),"+f"(d[12]),"+f"(d[13]),"+f"(d[14]),"+f"(d[15]),"+f"(d[16]),"+f"(d[17]),"+f"(d[18]),"+f"(d[19]),"+f"(d[20]),"+f"(d[21]),"+f"(d[22]),"+f"(d[23]),"+f"(d[24]),"+f"(d[25]),"+f"(d[26]),"+f"(d[27]),"+f"(d[28]),"+f"(d[29]),"+f"(d[30]),"+f"(d[31]),"+f"(d[32]),"+f"(d[33]),"+f"(d[34]),"+f"(d[35]),"+f"(d[36]),"+f"(d[37]),"+f"(d[38]),"+f"(d[39]),"+f"(d[40]),"+f"(d[41]),"+f"(d[42]),"+f"(d[43]),"+f"(d[44]),"+f"(d[45]),"+f"(d[46]),"+f"(d[47]),"+f"(d[48]),"+f"(d[49]),"+f"(d[50]),"+f"(d[51]),"+f"(d[52]),"+f"(d[53]),"+f"(d[54]),"+f"(d[55]),"+f"(d[56]),"+f"(d[57]),"+f"(d[58]),"+f"(d[59]),"+f"(d[60]),"+f"(d[61]),"+f"(d[62]),"+f"(d[63]) : "l"(da),"l"(db),"r"(sc));
}
__device__ __forceinline__ void wg_ss128_01(float* d, uint64_t da, uint64_t db, int sc) {
  asm volatile("{.reg .pred p; setp.ne.b32 p, %66, 0; wgmma.mma_async.sync.aligned.m64n128k16.f32.bf16.bf16 {%0,%1,%2,%3,%4,%5,%6,%7,%8,%9,%10,%11,%12,%13,%14,%15,%16,%17,%18,%19,%20,%21,%22,%23,%24,%25,%26,%27,%28,%29,%30,%31,%32,%33,%34,%35,%36,%37,%38,%39,%40,%41,%42,%43,%44,%45,%46,%47,%48,%49,%50,%51,%52,%53,%54,%55,%56,%57,%58,%59,%60,%61,%62,%63}, %64, %65, p, 1, 1, 0, 1;}"
    : "+f"(d[0]),"+f"(d[1]),"+f"(d[2]),"+f"(d[3]),"+f"(d[4]),"+f"(d[5]),"+f"(d[6]),"+f"(d[7]),"+f"(d[8]),"+f"(d[9]),"+f"(d[10]),"+f"(d[11]),"+f"(d[12]),"+f"(d[13]),"+f"(d[14]),"+f"(d[15]),"+f"(d[16]),"+f"(d[17]),"+f"(d[18]),"+f"(d[19]),"+f"(d[20]),"+f"(d[21]),"+f"(d[22]),"+f"(d[23]),"+f"(d[24]),"+f"(d[25]),"+f"(d[26]),"+f"(d[27]),"+f"(d[28]),"+f"(d[29]),"+f"(d[30]),"+f"(d[31]),"+f"(d[32]),"+f"(d[33]),"+f"(d[34]),"+f"(d[35]),"+f"(d[36]),"+f"(d[37]),"+f"(d[38]),"+f"(d[39]),"+f"(d[40]),"+f"(d[41]),"+f"(d[42]),"+f"(d[43]),"+f"(d[44]),"+f"(d[45]),"+f"(d[46]),"+f"(d[47]),"+f"(d[48]),"+f"(d[49]),"+f"(d[50]),"+f"(d[51]),"+f"(d[52]),"+f"(d[53]),"+f"(d[54]),"+f"(d[55]),"+f"(d[56]),"+f"(d[57]),"+f"(d[58]),"+f"(d[59]),"+f"(d[60]),"+f"(d[61]),"+f"(d[62]),"+f"(d[63]) : "l"(da),"l"(db),"r"(sc));
}
__device__ __forceinline__ void wg_ss96_01(float* d, uint64_t da, uint64_t db, int sc) {
  asm volatile("{.reg .pred p; setp.ne.b32 p, %50, 0; wgmma.mma_async.sync.aligned.m64n96k16.f32.bf16.bf16 {%0,%1,%2,%3,%4,%5,%6,%7,%8,%9,%10,%11,%12,%13,%14,%15,%16,%17,%18,%19,%20,%21,%22,%23,%24,%25,%26,%27,%28,%29,%30,%31,%32,%33,%34,%35,%36,%37,%38,%39,%40,%41,%42,%43,%44,%45,%46,%47}, %48, %49, p, 1, 1, 0, 1;}"
    : "+f"(d[0]),"+f"(d[1]),"+f"(d[2]),"+f"(d[3]),"+f"(d[4]),"+f"(d[5]),"+f"(d[6]),"+f"(d[7]),"+f"(d[8]),"+f"(d[9]),"+f"(d[10]),"+f"(d[11]),"+f"(d[12]),"+f"(d[13]),"+f"(d[14]),"+f"(d[15]),"+f"(d[16]),"+f"(d[17]),"+f"(d[18]),"+f"(d[19]),"+f"(d[20]),"+f"(d[21]),"+f"(d[22]),"+f"(d[23]),"+f"(d[24]),"+f"(d[25]),"+f"(d[26]),"+f"(d[27]),"+f"(d[28]),"+f"(d[29]),"+f"(d[30]),"+f"(d[31]),"+f"(d[32]),"+f"(d[33]),"+f"(d[34]),"+f"(d[35]),"+f"(d[36]),"+f"(d[37]),"+f"(d[38]),"+f"(d[39]),"+f"(d[40]),"+f"(d[41]),"+f"(d[42]),"+f"(d[43]),"+f"(d[44]),"+f"(d[45]),"+f"(d[46]),"+f"(d[47]) : "l"(da),"l"(db),"r"(sc));
}
__device__ __forceinline__ void wg_rs64_1(float* d, const uint32_t* a, uint64_t db, int sc) {
  asm volatile("{.reg .pred p; setp.ne.b32 p, %37, 0; wgmma.mma_async.sync.aligned.m64n64k16.f32.bf16.bf16 {%0,%1,%2,%3,%4,%5,%6,%7,%8,%9,%10,%11,%12,%13,%14,%15,%16,%17,%18,%19,%20,%21,%22,%23,%24,%25,%26,%27,%28,%29,%30,%31}, {%32,%33,%34,%35}, %36, p, 1, 1, 1;}"
    : "+f"(d[0]),"+f"(d[1]),"+f"(d[2]),"+f"(d[3]),"+f"(d[4]),"+f"(d[5]),"+f"(d[6]),"+f"(d[7]),"+f"(d[8]),"+f"(d[9]),"+f"(d[10]),"+f"(d[11]),"+f"(d[12]),"+f"(d[13]),"+f"(d[14]),"+f"(d[15]),"+f"(d[16]),"+f"(d[17]),"+f"(d[18]),"+f"(d[19]),"+f"(d[20]),"+f"(d[21]),"+f"(d[22]),"+f"(d[23]),"+f"(d[24]),"+f"(d[25]),"+f"(d[26]),"+f"(d[27]),"+f"(d[28]),"+f"(d[29]),"+f"(d[30]),"+f"(d[31]) : "r"(a[0]),"r"(a[1]),"r"(a[2]),"r"(a[3]),"l"(db),"r"(sc));
}
__device__ __forceinline__ void wg_rs96_1(float* d, const uint32_t* a, uint64_t db, int sc) {
  asm volatile("{.reg .pred p; setp.ne.b32 p, %53, 0; wgmma.mma_async.sync.aligned.m64n96k16.f32.bf16.bf16 {%0,%1,%2,%3,%4,%5,%6,%7,%8,%9,%10,%11,%12,%13,%14,%15,%16,%17,%18,%19,%20,%21,%22,%23,%24,%25,%26,%27,%28,%29,%30,%31,%32,%33,%34,%35,%36,%37,%38,%39,%40,%41,%42,%43,%44,%45,%46,%47}, {%48,%49,%50,%51}, %52, p, 1, 1, 1;}"
    : "+f"(d[0]),"+f"(d[1]),"+f"(d[2]),"+f"(d[3]),"+f"(d[4]),"+f"(d[5]),"+f"(d[6]),"+f"(d[7]),"+f"(d[8]),"+f"(d[9]),"+f"(d[10]),"+f"(d[11]),"+f"(d[12]),"+f"(d[13]),"+f"(d[14]),"+f"(d[15]),"+f"(d[16]),"+f"(d[17]),"+f"(d[18]),"+f"(d[19]),"+f"(d[20]),"+f"(d[21]),"+f"(d[22]),"+f"(d[23]),"+f"(d[24]),"+f"(d[25]),"+f"(d[26]),"+f"(d[27]),"+f"(d[28]),"+f"(d[29]),"+f"(d[30]),"+f"(d[31]),"+f"(d[32]),"+f"(d[33]),"+f"(d[34]),"+f"(d[35]),"+f"(d[36]),"+f"(d[37]),"+f"(d[38]),"+f"(d[39]),"+f"(d[40]),"+f"(d[41]),"+f"(d[42]),"+f"(d[43]),"+f"(d[44]),"+f"(d[45]),"+f"(d[46]),"+f"(d[47]) : "r"(a[0]),"r"(a[1]),"r"(a[2]),"r"(a[3]),"l"(db),"r"(sc));
}
__device__ __forceinline__ void wg_ss160_01(float* d, uint64_t da, uint64_t db, int sc) {
  asm volatile("{.reg .pred p; setp.ne.b32 p, %82, 0; wgmma.mma_async.sync.aligned.m64n160k16.f32.bf16.bf16 {%0,%1,%2,%3,%4,%5,%6,%7,%8,%9,%10,%11,%12,%13,%14,%15,%16,%17,%18,%19,%20,%21,%22,%23,%24,%25,%26,%27,%28,%29,%30,%31,%32,%33,%34,%35,%36,%37,%38,%39,%40,%41,%42,%43,%44,%45,%46,%47,%48,%49,%50,%51,%52,%53,%54,%55,%56,%57,%58,%59,%60,%61,%62,%63,%64,%65,%66,%67,%68,%69,%70,%71,%72,%73,%74,%75,%76,%77,%78,%79}, %80, %81, p, 1, 1, 0, 1;}"
    : "+f"(d[0]),"+f"(d[1]),"+f"(d[2]),"+f"(d[3]),"+f"(d[4]),"+f"(d[5]),"+f"(d[6]),"+f"(d[7]),"+f"(d[8]),"+f"(d[9]),"+f"(d[10]),"+f"(d[11]),"+f"(d[12]),"+f"(d[13]),"+f"(d[14]),"+f"(d[15]),"+f"(d[16]),"+f"(d[17]),"+f"(d[18]),"+f"(d[19]),"+f"(d[20]),"+f"(d[21]),"+f"(d[22]),"+f"(d[23]),"+f"(d[24]),"+f"(d[25]),"+f"(d[26]),"+f"(d[27]),"+f"(d[28]),"+f"(d[29]),"+f"(d[30]),"+f"(d[31]),"+f"(d[32]),"+f"(d[33]),"+f"(d[34]),"+f"(d[35]),"+f"(d[36]),"+f"(d[37]),"+f"(d[38]),"+f"(d[39]),"+f"(d[40]),"+f"(d[41]),"+f"(d[42]),"+f"(d[43]),"+f"(d[44]),"+f"(d[45]),"+f"(d[46]),"+f"(d[47]),"+f"(d[48]),"+f"(d[49]),"+f"(d[50]),"+f"(d[51]),"+f"(d[52]),"+f"(d[53]),"+f"(d[54]),"+f"(d[55]),"+f"(d[56]),"+f"(d[57]),"+f"(d[58]),"+f"(d[59]),"+f"(d[60]),"+f"(d[61]),"+f"(d[62]),"+f"(d[63]),"+f"(d[64]),"+f"(d[65]),"+f"(d[66]),"+f"(d[67]),"+f"(d[68]),"+f"(d[69]),"+f"(d[70]),"+f"(d[71]),"+f"(d[72]),"+f"(d[73]),"+f"(d[74]),"+f"(d[75]),"+f"(d[76]),"+f"(d[77]),"+f"(d[78]),"+f"(d[79]) : "l"(da),"l"(db),"r"(sc));
}
__device__ __forceinline__ void wg_rs160_1(float* d, const uint32_t* a, uint64_t db, int sc) {
  asm volatile("{.reg .pred p; setp.ne.b32 p, %85, 0; wgmma.mma_async.sync.aligned.m64n160k16.f32.bf16.bf16 {%0,%1,%2,%3,%4,%5,%6,%7,%8,%9,%10,%11,%12,%13,%14,%15,%16,%17,%18,%19,%20,%21,%22,%23,%24,%25,%26,%27,%28,%29,%30,%31,%32,%33,%34,%35,%36,%37,%38,%39,%40,%41,%42,%43,%44,%45,%46,%47,%48,%49,%50,%51,%52,%53,%54,%55,%56,%57,%58,%59,%60,%61,%62,%63,%64,%65,%66,%67,%68,%69,%70,%71,%72,%73,%74,%75,%76,%77,%78,%79}, {%80,%81,%82,%83}, %84, p, 1, 1, 1;}"
    : "+f"(d[0]),"+f"(d[1]),"+f"(d[2]),"+f"(d[3]),"+f"(d[4]),"+f"(d[5]),"+f"(d[6]),"+f"(d[7]),"+f"(d[8]),"+f"(d[9]),"+f"(d[10]),"+f"(d[11]),"+f"(d[12]),"+f"(d[13]),"+f"(d[14]),"+f"(d[15]),"+f"(d[16]),"+f"(d[17]),"+f"(d[18]),"+f"(d[19]),"+f"(d[20]),"+f"(d[21]),"+f"(d[22]),"+f"(d[23]),"+f"(d[24]),"+f"(d[25]),"+f"(d[26]),"+f"(d[27]),"+f"(d[28]),"+f"(d[29]),"+f"(d[30]),"+f"(d[31]),"+f"(d[32]),"+f"(d[33]),"+f"(d[34]),"+f"(d[35]),"+f"(d[36]),"+f"(d[37]),"+f"(d[38]),"+f"(d[39]),"+f"(d[40]),"+f"(d[41]),"+f"(d[42]),"+f"(d[43]),"+f"(d[44]),"+f"(d[45]),"+f"(d[46]),"+f"(d[47]),"+f"(d[48]),"+f"(d[49]),"+f"(d[50]),"+f"(d[51]),"+f"(d[52]),"+f"(d[53]),"+f"(d[54]),"+f"(d[55]),"+f"(d[56]),"+f"(d[57]),"+f"(d[58]),"+f"(d[59]),"+f"(d[60]),"+f"(d[61]),"+f"(d[62]),"+f"(d[63]),"+f"(d[64]),"+f"(d[65]),"+f"(d[66]),"+f"(d[67]),"+f"(d[68]),"+f"(d[69]),"+f"(d[70]),"+f"(d[71]),"+f"(d[72]),"+f"(d[73]),"+f"(d[74]),"+f"(d[75]),"+f"(d[76]),"+f"(d[77]),"+f"(d[78]),"+f"(d[79]) : "r"(a[0]),"r"(a[1]),"r"(a[2]),"r"(a[3]),"l"(db),"r"(sc));
}
__device__ __forceinline__ void wg_ss8_10(float* d, uint64_t da, uint64_t db, int sc) {
  asm volatile("{.reg .pred p; setp.ne.b32 p, %6, 0; wgmma.mma_async.sync.aligned.m64n8k16.f32.bf16.bf16 {%0,%1,%2,%3}, %4, %5, p, 1, 1, 1, 0;}"
    : "+f"(d[0]),"+f"(d[1]),"+f"(d[2]),"+f"(d[3]) : "l"(da),"l"(db),"r"(sc));
}
__device__ __forceinline__ void wg_ss8_if(float* d, uint64_t da, uint64_t db, int sc, int skip) {
  asm volatile("{.reg .pred p, q; setp.ne.b32 p, %6, 0; setp.eq.b32 q, %7, 0; @q wgmma.mma_async.sync.aligned.m64n8k16.f32.bf16.bf16 {%0,%1,%2,%3}, %4, %5, p, 1, 1, 1, 0;}"
    : "+f"(d[0]),"+f"(d[1]),"+f"(d[2]),"+f"(d[3]) : "l"(da),"l"(db),"r"(sc),"r"(skip));
}

constexpr uint32_t DB = 1024;
constexpr int UNIT = 8192, WSLOT = 16384, W2TILE = 24576, OFF_R = 12 * UNIT;
constexpr int OFF_PB = 26 * UNIT;
constexpr int OFF_CV = OFF_PB + 16384, OFF_ST = OFF_CV + 768, OFF_TS = OFF_ST + 256, OFF_MODR = OFF_TS + 512, OFF_ROLE = OFF_MODR + 80, OFF_BAR = OFF_ROLE + 16, SMEM_BYTES = OFF_BAR + 1368;
constexpr int OFF_BX = OFF_PB, OFF_AX = OFF_BX + 12288, OFF_RT = OFF_AX + 2048, OFF_GB = OFF_RT + 512, OFF_CO = OFF_CV;
constexpr int OFF_UV = 4 * UNIT, OFF_SX = 24 * UNIT, OFF_XCH = 12 * UNIT;
constexpr int OFF_Q = 99328, KV_V = 4096, KV_H = 8192, F_E = 128, F_O = 4288, OFF_WM = 20 * UNIT, OFF_TAP = 12672, OFF_MR = 25 * UNIT;
constexpr uint64_t pk5(int a, int b, int c, int d, int e) { return (uint64_t)(a / 128) | (uint64_t)(b / 128) << 12 | (uint64_t)(c / 128) << 24 | (uint64_t)(d / 128) << 36 | (uint64_t)(e / 128) << 48; }
constexpr uint64_t T_KV = pk5(119808, 16384, 130048, 65536, 49152), T_F = pk5(140288, 90368, 148736, 81920, OFF_PB), T_X = pk5(0, 4224, 8448, 0, 4224),
                   T_P = pk5(32768, 16384, 65536, 81920, OFF_PB);
__host__ __device__ __forceinline__ uint32_t tab(uint64_t t, int c) { return ((uint32_t)(t >> (12 * c)) & 0xFFF) << 7; }
enum { B_KV = 0, B_FRAW = 5, B_Q = 10, B_WM = 15, B_XR = 17, B_MR = B_XR + 5, B_QTOK, B_ST1, B_MODR, B_ROLE = B_MODR + 5, B_FL = 32, B_PFULL = B_FL + 5, B_PEMPTY = B_PFULL + 5, B_FRDY = B_PEMPTY + 5,
       B_G = B_FRDY + 5, B_EXT = B_G + 2, B_QTD, B_ED, B_S2 = B_ED + 2, B_GB, B_FULL = 60, B_RETRY = B_FULL + 43, B_XFREE = B_RETRY + 8, B_BX, B_UVB, B_CO, B_SX, B_EMPTY = 121, B_SC = 164, B_STD = B_SC + 5, B_LAG };
static_assert(B_ROLE < B_FL && B_GB < B_FULL && B_SX + 5 <= B_EMPTY - 1 && OFF_MR == OFF_SX + 8192 && SMEM_BYTES <= 232448, "barrier groups");
#define BAR(i) (base + OFF_BAR + 8 * (i))

struct Maps { CUtensorMap km, v, q, fm, wmp, kh, tap, wm, w1a, w3a, xs, w1u, w3u, w1b, w3b, x1s, x1b, w2a, w2b, outa, outb; };
struct Ptrs { const bf16 *c, *ssmd; Scratch* g; uint64_t prog[2]; uint32_t gate[5]; int ulo; uint32_t mq, xh, xdep, hstart, hpause, hl[8], uvd, mpos, wt0, wpace; float one; uint32_t wdep[30], adep[14]; uint2 w2t[12]; int hid[3][9]; };

#define REGION_IDS int tid, lane, bid; \
  asm volatile("mov.u32 %0, %%tid.x;" : "=r"(tid)); asm volatile("mov.u32 %0, %%laneid;" : "=r"(lane)); asm volatile("mov.u32 %0, %%ctaid.x;" : "=r"(bid)); \
  const int i0 = tid & 127; (void)i0; (void)lane; (void)bid

#define ffn_role(h, j, r) do { \
  mbar_wait(BAR(B_ROLE)); \
  r = __shfl_sync(~0u, lds32(base + OFF_ROLE), 0); \
  asm volatile("mov.u32 %0, %%ctaid.x;" : "=r"(h)); \
  h &= 1; j = r >> 4; r &= 15; } while (0)
__device__ __forceinline__ void rank_pair(Scratch* G, uint32_t base, uint32_t epoch, bool put) {
  REGION_IDS;
  uint32_t t;
  asm volatile("mov.u32 %0, %%smid;" : "=r"(t));
  t >>= 1;
  const uint32_t q = (t - 32) * 37 >> 8, g = t < 32 ? t & 7 : t < 60 ? t - 31 - 7 * q : t < 62 ? t - 54 : 0;
  const uint32_t key = epoch << 20 | (g & 3) << 18 | (g & 4) << 15 | (t & 127) << 6 | bid >> 1;
  if (put) {
    if (lane == (bid & 1) * 99) publish(&G->key[bid >> 1], key);
    return;
  }
  uint2 x;
  int it = 0;
#pragma unroll 1
  do x = ld_relaxed64(&G->key[2 * lane]); while (__any_sync(~0u, ((x.x ^ key) | (x.y ^ key)) >> 20) && ++it < SPIN_LIMIT);
  t = __shfl_sync(~0u, bid & 2 ? x.y : x.x, bid >> 2);
  sts32(base + OFF_ROLE, __popc(__ballot_sync(~0u, x.x < t)) + __popc(__ballot_sync(~0u, x.y < t)));
  arrive1(BAR(B_ROLE));
}
__device__ __forceinline__ int mod_ch(int p) { return p < 40 ? (p >> 3) * 128 + (p & 1) * 64 : 64 * (p < 50 ? p - 40 : p - 50); }
__device__ __forceinline__ int mod_col(int p) { return mod_ch(p) + 640 * (p < 40 ? 0x4210 >> (2 * (p & 6)) & 7 : p < 50 ? 3 : 5); }
__device__ __forceinline__ uint32_t mod_sum(uint2 v) { return pack_bf16(0.f, __uint_as_float(v.x) + __uint_as_float(v.y)); }
#define UVS 5
#define XP 2
#define GA 3
#define GB 1
#define HL 0
#define EH 0
#define MG 4
#define SG 0x88
#define LAG2 38
#define NP 8
__device__ __forceinline__ int nib(uint32_t t, int i) { return (t >> (4 * i)) & 15; }
__device__ __forceinline__ int w_block(int up, int m) { return m < 2 ? 2 * up + m : 4 + up; }
__host__ __device__ constexpr int w2_at(int v) { return UNIT * (v == 1 ? 0 : 0x0811030C18ull >> (v - (v > 1)) % 5 * 8 & 255); }
__host__ __device__ constexpr int hid_at(int m, int g) { return UNIT * ((g ? 0x0200150710ull : 0x010B14060Full) >> m % 5 * 8 & 255); }
__host__ __device__ constexpr int x1_at(int k) { return k < 4 ? 22 * UNIT + 4096 * k : OFF_BX + UNIT; }
__host__ __device__ constexpr uint32_t w2_desc(int v) { return (DB + w2_at(v)) >> 4 | UNIT << 12; }
__host__ __device__ constexpr int a_at(int n) { return WSLOT * (0x54323251041032ull >> 4 * n & 15); }
__host__ __device__ constexpr int second(int v) { return 0xDCBA657498ull >> 4 * v & 15; }

#define WINS "4444444444443444444"
#define ORDER "k1v1f0q0q1q2q3q4k2v2f1k3v3f2k4v4f3w0f4"
constexpr int NL = sizeof(ORDER) / 2, TA = 16, M8 = 3 << TA / 8;
__host__ __device__ constexpr int load_bar(int e) { return e < 0 ? B_KV : ORDER[2 * e + 1] - '0' + (ORDER[2 * e] == 'q' ? B_Q : ORDER[2 * e] == 'f' ? B_FRAW : ORDER[2 * e] == 'w' ? B_WM : B_KV); }
__host__ __device__ constexpr int load_gate(int e, int w) {
  int i = e, sum = 0;
  while (i >= -1 && sum + (i < 0 ? 8 : ORDER[2 * i] == 'w' ? 10 : 4) <= 4 * w) { sum += i < 0 ? 8 : ORDER[2 * i] == 'w' ? 10 : 4; i--; }
  for (; i >= -1; i--) {
    bool ok = i < e;
    for (int k = e; k < NL; k++) ok = ok && load_bar(k) != load_bar(i);
    if (ok) return load_bar(i);
  }
  return -1;
}
template <int E> __device__ __forceinline__ void loads(const Ptrs& P, const Maps& maps, uint32_t base) {
  if constexpr (E < NL) {
    constexpr int r = ORDER[2 * E + 1] - '0';
    constexpr char x = ORDER[2 * E];
    const int c0 = 128 * r + 64 * (blockIdx.x & 1), c1 = 2 * (blockIdx.x & 126);
    constexpr int g = load_gate(E, WINS[E] - '0');
    if (g >= 0 && (E == 0 || g != load_gate(E - 1, WINS[E ? E - 1 : 0] - '0'))) mbar_wait(BAR(g < 0 ? 0 : g));
    if (elect()) {
      if (x == 'k') { tma3d(base + tab(T_KV, r), &maps.km, c0, c1, 0, BAR(B_KV + r)); tma3d(base + tab(T_KV, r) + KV_H, &maps.kh, c0, c1 - 1, 5, BAR(B_KV + r)); }
      if (x == 'v') tma3d(base + tab(T_KV, r) + KV_V, &maps.v, c0, c1, 0, BAR(B_KV + r));
      if (x == 'q') tma3d(base + OFF_Q + 4096 * r, &maps.q, c0, c1, 0, BAR(B_Q + r));
      if (x == 'f') tma3d(base + tab(T_F, r) + F_E, &maps.fm, 0, 0, 128 * r + blockIdx.x, BAR(B_FRAW + r));
      if (x == 'w') tma3d(base + OFF_WM, &maps.wmp, mod_col(TA + (blockIdx.x >> 3)), 80 * (blockIdx.x & 7), 0, BAR(B_WM));
    }
    loads<E + 1>(P, maps, base);
  }
}

template <int U> __device__ __forceinline__ void cstep(float* acc, const uint32_t* A, uint64_t db) {
  const uint32_t* a = A + 4 * U;
  const uint64_t d = db + 16 * U;
  if (U == 4) { wg_rs64_0(acc + 96, A, db + 192, 0); wg_rs48_0(acc + 96, A + 4, db + 208, 1); wg_rs32_0(acc + 96, A + 8, db + 224, 1); wg_rs16_0(acc + 96, A + 12, db + 240, 1); }
  if (U <= 4) wg_rs192_0(acc, a, d, U);
  if (U == 5) wg_rs176_0(acc, a, d, 1);
  if (U == 6) wg_rs160_0(acc, a, d, 1);
  if (U == 7) wg_rs144_0(acc, a, d, 1);
  if (U == 8) wg_rs128_0(acc, a, d, 1);
  if (U == 9) wg_rs112_0(acc, a, d, 1);
  if (U == 10) wg_rs96_0(acc, a, d, 1);
  if (U == 11) wg_rs80_0(acc, a, d, 1);
  if (U == 12) wg_rs64_0(acc, a, d, 1);
  if (U == 13) wg_rs48_0(acc, a, d, 1);
  if (U == 14) wg_rs32_0(acc, a, d, 1);
  if (U == 15) wg_rs16_0(acc, a, d, 1);
}
template <int U0, int U1> __device__ __forceinline__ void csteps(float* acc, const uint32_t* A, uint64_t db) {
  cstep<U0>(acc, A, db);
  if constexpr (U0 > U1) csteps<U0 - 1, U1>(acc, A, db);
}
template <int U0, int U1> __device__ __forceinline__ void cload(uint32_t* A, uint32_t fa) {
  asm volatile("{ld.shared.b32 %0, [%4+%5]; ld.shared.b32 %1, [%4+%5+128]; ld.shared.b32 %2, [%4+%5+16]; ld.shared.b32 %3, [%4+%5+144];}"
               : "=r"(A[4 * U0]), "=r"(A[4 * U0 + 1]), "=r"(A[4 * U0 + 2]), "=r"(A[4 * U0 + 3]) : "r"(fa), "n"(256 * U0) : "memory");
  if constexpr (U0 > U1) cload<U0 - 1, U1>(A, fa);
}

template <int NK> __device__ __forceinline__ void mod_gemv(Scratch* G, uint32_t wm, int p, int part, int w, int lane, uint32_t par) {
  float d[4] = {};
  fence_regs(d);
  wg_fence();
#pragma unroll 1
  for (int k = 0; k < NK; k += 5) {
#pragma unroll
    for (int i = 0; i < 5; i++) wg_ss8_10(d, mkdesc(DB + wm + 2048 * (k + i), 16, 1024, 1), mkdesc(DB + OFF_CV + 32 * (k + i), 16, 128, 0), 1);
  }
  wg_commit();
  const int ch = mod_ch(p) + 16 * w + (lane >> 2);
  uint32_t* dst = (p < 40 ? &G->modc[ch & 127][p >> 3][4 * (p & 6)] : (uint32_t*)&G->modv[p >= 50][ch]) + part;
  wg_wait<0>();
  fence_regs(d);
  if (!(lane & 3)) {
    publish(dst, (__float_as_uint(d[0]) & ~1u) | par);
    publish(dst + (p < 40 ? 1280 : 16), (__float_as_uint(d[2]) & ~1u) | par);
    if (NK == 20 && p < 40 && (p & 6) == 6) {
      dst = (uint32_t*)&G->modv[2][ch] + part;
      publish(dst, (__float_as_uint(d[0]) & ~1u) | par);
      publish(dst + 16, (__float_as_uint(d[2]) & ~1u) | par);
    }
  }
}
__device__ __forceinline__ void mod_fetch(Scratch* G, uint32_t base, uint32_t epoch, uint32_t m8, uint32_t c, uint32_t c1) {
  REGION_IDS;
  const uint32_t* mp = &G->modc[bid][0][lane];
  auto unused = [&]() { return (lane & 6) && !(m8 >> c & 1); };
#pragma unroll 1
  for (int it = 0; c < c1 && it < SPIN_LIMIT; it++) {
    uint32_t m = ld_relaxed32(mp + 32 * c);
    const uint32_t m1 = ld_relaxed32(mp + 32 * min(c + 1, c1 - 1));
#pragma unroll 1
    for (int k = 0; k < 2 && c < c1 && __all_sync(~0u, unused() || !((m ^ epoch) & 1)); k++) {
      float x = unused() ? 0.f : __uint_as_float(m);
      x += __shfl_xor_sync(~0u, x, 1); x += __shfl_xor_sync(~0u, x, 2); x += __shfl_xor_sync(~0u, x, 4);
      const uint32_t y = __byte_perm(badd2(pack_bf16(0.f, x), (lane & 8) * 0x07F00000u), 0, 0x3232), ga = __shfl_sync(~0u, y, 16);
      sts32(base + OFF_MODR + 16 * c + 4 * (lane >> 3), lane < 16 ? bmul2(y, ga) : y);
      arrive1(BAR(B_MODR + c));
      if (lane >= 30 && (m8 >> c & 1)) publish((uint32_t*)&G->modv[2][128 * c + bid] + (lane & 1), ((lane & 1 ? 0 : __float_as_uint(x)) & ~1u) | (epoch & 1));
      m = m1;
      c++;
    }
  }
}
__device__ __forceinline__ void add4(uint4& y, const uint4& z) { y.x = badd2(y.x, z.x); y.y = badd2(y.y, z.y); y.z = badd2(y.z, z.z); y.w = badd2(y.w, z.w); }
template <bool FIRST> __device__ __forceinline__ void e_round(Scratch* G, uint32_t base, uint32_t sa, uint4*& gp, uint4* q, int c, int w, uint32_t tag, uint32_t epoch) {
  constexpr int QO = -D_ * 256;
  mbar_wait(BAR(B_MODR + c));
  const uint4 co = lds128(base + OFF_MODR + 16 * c);
  mbar_wait(BAR(B_PFULL + c));
  const uint32_t pb = sa + tab(T_P, c);
  uint4 l[2][6];
  auto load = [&](int hf, int k) { l[hf][k] = lds128((k < 4 ? pb + 4096 * k : sa + OFF_MR + 4096 * (k - 4)) + 2048 * hf); };
#pragma unroll
  for (int hf = 0; hf < 2; hf++) {
    uint4 &y = l[hf][0], &z = l[hf][4], &m = l[hf][5];
    load(hf, 0);
    if (!FIRST) {
      load(hf, 1);
      add4(y, l[hf][1]);
      load(hf, 2); load(hf, 3);
      add4(l[hf][2], l[hf][3]);
      add4(y, l[hf][2]);
    }
    load(hf, 4); load(hf, 5);
    if (FIRST) {
#pragma unroll 1
      for (int it = 0; __any_sync(~0u, ((z.x >> 15 ^ epoch) | (m.x ^ epoch)) & tag) && it < SPIN_LIMIT; it++) {
        const uint4* sp = (const uint4*)G->st1 + (opaque(sa) - base >> 4) + 128 * hf;
        z = ld_relaxed128(sp);
        m = ld_relaxed128(sp + 256);
        sts128(sa + OFF_MR + 2048 * hf, z.x, z.y, z.z, z.w);
        sts128(sa + OFF_MR + 2048 * hf + 4096, m.x, m.y, m.z, m.w);
      }
      z.x &= 0xFFFF7FFFu;
      sts32(sa + OFF_MR + 2048 * hf, z.x);
    }
#pragma unroll 1
    for (int it = 0; __any_sync(~0u, (q[hf].x ^ epoch) & tag) && it < SPIN_LIMIT; it++) {
      q[hf] = ld_relaxed128(gp + QO + 128 * hf);
    }
    y.x = bfma2(bfma2(bfma2(q[hf].x, z.x, m.x), co.y, co.x), y.x, q[hf].x);
    auto hint = [&]() {
      __syncwarp();
      asm volatile("{.reg .pred p; elect.sync _|p, 0xffffffff; @p red.relaxed.gpu.global.add.u32 [%0], 1; @p mbarrier.arrive.shared::cta.b64 _, [%1];}"
                   ::"l"(G->xsh[c][2 * w + (blockIdx.x >> 6)]), "r"(BAR(B_PEMPTY + c)), "r"(y.x) : "memory");
    };
    if (hf && !EH) hint();
    y.y = bfma2(bfma2(bfma2(q[hf].y, z.y, m.y), co.y, co.x), y.y, q[hf].y);
    y.z = bfma2(bfma2(bfma2(q[hf].z, z.z, m.z), co.y, co.x), y.z, q[hf].z);
    y.w = bfma2(bfma2(bfma2(q[hf].w, z.w, m.w), co.y, co.x), y.w, q[hf].w);
    st_relaxed128(gp + 128 * hf, set_tag(bmul2(y.x, co.w), tag, epoch), bmul2(y.y, co.w), bmul2(y.z, co.w), bmul2(y.w, co.w));
    if (hf && EH == 1) hint();
    asm volatile("{.reg .pred p; .reg .b32 t; setp.ne.u32 p, %5, 0; max.u32 t, %1, 1; @!p st.relaxed.gpu.global.v4.u32 [%0+%6], {t,%2,%3,%4}; @p st.relaxed.gpu.global.v4.u32 [%0+%7], {t,%2,%3,%4};}"
                 ::"l"(gp + 128 * hf), "r"(y.x), "r"(y.y), "r"(y.z), "r"(y.w), "r"(epoch & 1), "n"(D_ * 4096), "n"(D_ * 8192) : "memory");
    if (hf && EH == 2) hint();
    if (c < 4) q[hf] = ld_relaxed128(gp + QO + 32768 + 128 * hf);
  }
  gp += 32768;
}
__device__ __forceinline__ void q_stats(uint32_t base, int w) {
  REGION_IDS;
  float s0 = 0.f, s1 = 0.f, q0 = 0.f, q1 = 0.f;
  const uint32_t a = OFF_Q + 1024 * w + 128 * (lane & 7) + (((lane >> 3) ^ (lane & 7)) << 4);
  const uint32_t ra = mapa(base + OFF_ST + 128 * (bid & 1) + 64 * (lane & 1) + 16 * w + 8 * (lane >> 2), lane >> 1 & 1), rb = mapa(BAR(B_ST1), lane >> 1 & 1);
  if (w == 3 && elect()) mbar_expect_tx(BAR(B_ST1), 256);
#pragma unroll 1
  for (int k = 0; k < 5; k++) {
    mbar_wait(BAR(B_Q + k));
    const uint32_t o = opaque(base + 4096 * k);
    const uint4 x = lds128(o + a), y = lds128(o + (a ^ 64));
    const uint32_t e[8] = {x.x, x.y, x.z, x.w, y.x, y.y, y.z, y.w};
#pragma unroll
    for (int i = 0; i < 8; i++) { const float lo = bf_lo(e[i]), hi = bf_hi(e[i]); s0 += lo; s1 += hi; q0 = fmaf(lo, lo, q0); q1 = fmaf(hi, hi, q1); }
  }
  s0 += s1; q0 += q1;
  arrive1(BAR(B_STD));
  s0 += __shfl_xor_sync(~0u, s0, 8); q0 += __shfl_xor_sync(~0u, q0, 8);
  s0 += __shfl_xor_sync(~0u, s0, 16); q0 += __shfl_xor_sync(~0u, q0, 16);
  if (lane < 8) asm volatile("st.async.shared::cluster.mbarrier::complete_tx::bytes.v2.b32 [%0], {%1,%2}, [%3];" ::"r"(ra), "r"(__float_as_uint(s0)), "r"(__float_as_uint(q0)), "r"(rb) : "memory");
}
__device__ __forceinline__ void short_conv(Scratch* G, uint32_t base, int s, int w, uint32_t par, uint32_t xh) {
  REGION_IDS;
  const uint32_t a = base + tab(T_KV, s) + 128 * (lane & 3) + ((w ^ (lane & 3)) << 4) + 4 * (lane & 16) + (lane & 12), keep = ~(lane & 1);
  uint4* dst = G->xr + (128 * s + 64 * (bid & 1) + 8 * w + 2 * (lane & 16) + (lane >> 1 & 6)) * 256 + 255 - 4 * (bid >> 1) - (lane & 3);
  mbar_wait(BAR(B_KV));
  mbar_wait(BAR(B_KV + s));
  const uint4 wv = lds128(base + OFF_TAP + 512 * s + 64 * w + 16 * (lane & 16) + 4 * (lane & 12));
  uint32_t kk[11], r[8];
#pragma unroll
  for (int k = 0; k < 11; k++) kk[k] = k < 3 ? lds32((a ^ (64 * (k & 1))) + KV_H + 512 * k) : lds32((a ^ (64 * (~k & 1))) + 512 * (k - 3));
  if (xh == 0 && elect()) red_hint(G->hint[s][4 * (bid & 1) + w]);
#pragma unroll
  for (int k = 0; k < 8; k++) r[k] = lds32((a ^ (64 * (k & 1))) + KV_V + 512 * k);
  arrive1(BAR(B_SC + s));
  const uint32_t w0 = __byte_perm(wv.x, wv.z, 0x5410), w1 = __byte_perm(wv.x, wv.z, 0x7632),
                 w2 = __byte_perm(wv.y, wv.w, 0x5410), w3 = __byte_perm(wv.y, wv.w, 0x7632);
#pragma unroll
  for (int k = 0; k < 8; k++) r[k] = bmul2(bfma2(kk[k + 3], w0, bfma2(kk[k + 2], w1, bfma2(kk[k + 1], w2, bmul2(kk[k], w3)))), r[k]);
  const uint32_t bit = ~par >> 7 & lane & 1;
  if (xh == 1 && elect()) red_hint(G->hint[s][4 * (bid & 1) + w]);
  st_relaxed128(dst, (__byte_perm(r[7], r[6], 0x5410) & keep) | bit, __byte_perm(r[5], r[4], 0x5410), __byte_perm(r[3], r[2], 0x5410), __byte_perm(r[1], r[0], 0x5410));
  st_relaxed128(dst + 256, (__byte_perm(r[7], r[6], 0x7632) & keep) | bit, __byte_perm(r[5], r[4], 0x7632), __byte_perm(r[3], r[2], 0x7632), __byte_perm(r[1], r[0], 0x7632));
  if (xh == 2 && elect()) red_hint(G->hint[s][4 * (bid & 1) + w]);
}
__device__ __forceinline__ void silu_vector(const bf16* c, int n, uint32_t base) {
  REGION_IDS;
  if (tid < n) {
    const uint32_t x = ldg32(c + 2 * tid);
    sts32(base + OFF_CV + 4 * tid, pack_bf16(silu_f(bf_lo(x)), silu_f(bf_hi(x))));
  }
  fence_async_smem();
}

template <int FIRST> __global__ void __cluster_dims__(2, 1, 1) __launch_bounds__(512, 1) k_fused(const __grid_constant__ Ptrs P, const __grid_constant__ Maps maps) {
  Scratch* const G = P.g;
  extern __shared__ __align__(1024) uint8_t smem_raw[];
  const uint32_t t_start = clock();
  const uint32_t base = __shfl_sync(~0u, smem_u32(smem_raw), 0);
  if (threadIdx.x == 416 && blockIdx.x + FIRST < 128) {
    const int c0 = 64 * (blockIdx.x & 1), c1 = 2 * (blockIdx.x & 126);
    mbar_init<1>(BAR(B_KV), 1);
    mbar_expect_tx(BAR(B_KV), 12288);
    tma3d(base + tab(T_KV, 0), &maps.km, c0, c1, 0, BAR(B_KV));
    tma3d(base + tab(T_KV, 0) + KV_V, &maps.v, c0, c1, 0, BAR(B_KV));
    tma3d(base + tab(T_KV, 0) + KV_H, &maps.kh, c0, c1 - 1, 5, BAR(B_KV));
    tma3d(base + OFF_TAP, &maps.tap, 0, blockIdx.x & 1, 0, BAR(B_KV));
  }
  if ((base & 0xFFFFFFu) != DB) __trap();
  const int wid = __shfl_sync(~0u, threadIdx.x >> 5, 0), wg = wid >> 2, w = wid & 3;
  if (blockIdx.x + FIRST >= 128) {
    REGION_IDS;
    auto unit = [&](int n) { return 4 * (P.hl[n >> 2] >> 8 * (n & 3) & 255) + (bid & 3); };
    auto fetch = [&](int n, int b) {
      if (unit(n) < 120 && elect()) {
        mbar_expect_tx(BAR(n), 40960);
#pragma unroll 1
        for (int k = 0; k < 5; k++) tma3d(base + 40960 * b + 8192 * k, &maps.wm, mod_col(unit(n) >> 1), 320 * (bid & 1) + 64 * k, 0, BAR(n));
      }
    };
    if (wid == 0) {
      mbar_init<4>(BAR(0), 1);
#pragma unroll 1
      for (int n = 0; n < 4; n++) { wait_clock(t_start + (P.hstart & 0xFFFF) + n * (P.hstart >> 16)); fetch(n, n); }
      mbar_init<28>(BAR(4), 1);
    }
    const uint32_t par = ~ld_relaxed32(G->hint[7][0]) >> 7 & 1;
    silu_vector(P.c + 320 * (bid & 1), 160, base);
    __syncthreads();
#pragma unroll 1
    for (int n = wg; unit(n) < 120; n += 4) {
      mbar_wait(BAR(n));
      mod_gemv<20>(G, 40960 * (n % 5), unit(n) >> 1, bid & 1, w, lane, par);
      named_bar(1 + wg, 128);
      if (w == 0) {
        wait_clock(t_start + P.hpause);
        if (n == 0) fetch(4, 4);
        fetch(n + 5, n % 5);
      }
    }
    return;
  }
  mbar_init<3>(BAR(wid < 15 ? 4 * wid + 1 : B_SC + 1), wid < 8 ? 1 : 4);
  mbar_init<1>(BAR(!wid ? B_SC + 4 : wid < 15 ? 4 * wid : B_SC), wid && wid < 8 ? 1 : 4);
  if (wid == 0) mbar_init<2>(BAR(B_SC + 5), 4);
  asm volatile("fence.mbarrier_init.release.cluster; bar.sync 0, 512;" ::: "memory");
  asm volatile("barrier.cluster.arrive.relaxed.aligned;" ::: "memory");
#define LAUNCHES const uint32_t launches = ld_relaxed32(G->hint[7][blockIdx.x >> 4])
#define EPOCH ((__shfl_sync(~0u, launches, 0) >> 7) + 1)
  if (wg < 2) {
    asm volatile("setmaxnreg.inc.sync.aligned.u32 224;");
    LAUNCHES;
    uint32_t par = launches;
    {
      float acc[128];
      uint32_t A[64];
#pragma unroll
      for (int i = 0; i < 64; i++) asm volatile("" : "=r"(A[i]));
      int c = wg;
#pragma unroll 1
      for (uint64_t prog = P.prog[wg]; prog; prog >>= 8) {
        REGION_IDS;
        const int s = prog & 7;
        if (s < 5) short_conv(G, base, s, w, par, P.xh);
        if (prog == P.prog[wg]) cluster_wait();
        if (prog & 16) {
          mbar_wait(BAR(B_QTD));
          mbar_wait(BAR(B_WM));
          mod_gemv<5>(G, OFF_WM, TA + (bid >> 3), bid & 7, w, lane, ~par >> 7 & 1);
          arrive1(BAR(B_G));
        }
        if (prog & 8) q_stats(base, w);
        if (prog & 32) {
          const int L = 16 * w + (lane >> 2) + 2 * (lane & 3) - 7;
          const uint32_t fo = base + ((L & 1) ? F_O + 2 * (L + 1) : F_E + 2 * L);
          mbar_wait(BAR(B_FRDY + c));
          cload<0, 0>(A, fo + tab(T_F, c));
          cload<15, 1>(A, fo + tab(T_F, c));
          arrive1(BAR(B_FL + c));
        }
        if (!(prog & 64)) continue;
        uint32_t xo;
#pragma unroll 1
        for (int it = 0; it < SPIN_LIMIT; it++) {
          xo = tab(T_X, opaque(c));
          mbar_wait(BAR(B_XR + c), it & 1);
          const uint32_t tag = lds32(base + xo + 32 * i0);
          wg_fence();
          csteps<0, 0>(acc, A, mkdesc(DB + xo, 16, 128, 0));
          csteps<15, 6>(acc, A, mkdesc(DB + xo, 16, 128, 0));
          wg_commit();
          if (bar_all(1 + wg, (tag ^ par >> 7) & 1)) break;
          wg_wait<0>();
          if (w == 0 && elect()) { mbar_expect_tx(BAR(B_XR + c), 4096); bulk_load(base + xo, G->xr + (128 * c + bid) * 256, 4096, BAR(B_XR + c)); }
        }
        wg_fence();
        csteps<5, 1>(acc, A, mkdesc(DB + tab(T_X, opaque(c)), 16, 128, 0));
        wg_commit();
        mbar_wait(BAR(opaque(B_SC + (c == 2 ? 3 : c))));
        wg_wait<0>();
        fence_regs(acc);
        const uint32_t pb = base + tab(T_P, c) + 4096 * w;
#pragma unroll
        for (int k = 0; k < 8; k++) {
          uint32_t p[4];
#pragma unroll
          for (int e = 0; e < 4; e++) { const int i = 4 * k + e; p[e] = i < 31 ? pack_bf16(acc[4 * i] + acc[4 * i + 6], acc[4 * i + 1] + acc[4 * i + 7]) : pack_bf16(acc[124], acc[125]); }
          if (k == 0 && (lane & 3) < w) p[0] = 0;
          stmatrix_x4_t(k == 0 ? pb + 16 * ((255 - lane + 2 * w) & 255) : pb + 16 * (255 - lane + 2 * w) - 512 * k, p[0], p[1], p[2], p[3]);
        }
        arrive1(BAR(B_PFULL + c));
        c += 2;
      }
    }
    par = ~par >> 7 & 1;
    const uint32_t ao = ((blockIdx.x ^ wg) & 1) * UNIT;
    uint32_t ck;
    { REGION_IDS; ck = base + ao + lane * 128 + (((2 * w) ^ (lane & 7)) << 4); }
    const uint32_t abd = DB + ao;
    auto tags = [&](int as, bool first) { return (lds32(ck + as) ^ par) | (lds32(ck + as + (first ? 4096 : 256)) ^ par); };
    int role;
    { int h, j, r; ffn_role(h, j, r); role = (2 * r + (h ^ wg)) * 8 + 4 * h + j; }
    auto a_tile = [&](int as, int n, bool first) {
#pragma unroll 1
      for (int it = 0; __any_sync(~0u, tags(as, first) & 1) && it < SPIN_LIMIT; it++) {
        if (elect()) {
          mbar_expect_tx(BAR(B_RETRY + wid), UNIT);
          if (first) tma2d(base + ao + as, &maps.xs, 8 * role & ~63, 64 * n, BAR(B_RETRY + wid));
          else bulk_load(base + as, G->hh + ((role & ~3) + ((role + n) & 3)) * 1536 + (n >> 2) * 512, UNIT, BAR(B_RETRY + wid));
        }
        mbar_wait(BAR(B_RETRY + wid), par >> 1);
        par ^= 2;
      }
    };
    float acc[128], acb[64];
    int ws = 0;
    float d[8];
    uint32_t *ud0, *ud1;
    unsigned* uh;
    {
      REGION_IDS;
      const int r = role >> 4, row = (r & 14) + (lane >> 2 & 1);
      ud0 = &G->uv[role & 7][32 * row + 4 * ((2 * w ^ row) & 7) + (lane & 3)];
      ud1 = ud0 + 512 * w_block(r & 1, 2);
      ud0 += 512 * w_block(r & 1, wg);
      uh = G->hint[8][role & 7];
      asm volatile("" : "+l"(ud0), "+l"(ud1), "+l"(uh));
    }
    auto step = [&](int n, int uv) {
      const int as = a_at(n);
      const uint64_t da = mkdesc(abd + as, 16, 1024, 1), db = mkdesc(DB + OFF_R + ws, 4096, 1024, 1);
      mbar_wait(BAR(B_FULL + 2 * n));
      a_tile(as, n, true);
      if (uv == 1) { mbar_wait(BAR(B_UVB)); mbar_wait(BAR(B_CO)); }
      wg_fence();
#pragma unroll
      for (int k = 0; k < 4; k++) {
        wg_ss64_11(acc + 96, da + 128 * k, db + 768 + 128 * (k & 1) + 1024 * (k >> 1), k ? 1 : n);
        if (k == GA - 1) { wg_commit(); wg_wait<1>(); if (elect()) mbar_arrive(BAR(B_EMPTY + 2 * n - 1)); if (uv == 2) fence_regs(d); }
      }
      if (uv == 1) {
#pragma unroll
        for (int k = 0; k < 5; k++) {
          wg_ss8_10(d, mkdesc(DB + OFF_UV + 2048 * wg + 6144 * k, 16, 1024, 1), mkdesc(DB + OFF_CO + 64 * k, 32, 128, 0), k);
        }
        if (!wg) {
#pragma unroll
          for (int k = 0; k < 5; k++) wg_ss8_10(d + 4, mkdesc(DB + OFF_UV + 4096 + 6144 * k, 16, 1024, 1), mkdesc(DB + OFF_CO + 64 * k, 32, 128, 0), k);
        }
      }
#pragma unroll
      for (int k = 0; k < 4; k++) wg_ss192_11(acc, da + 128 * k, db + 128 * (k & 1) + 1024 * (k >> 1), k ? 1 : n);
      wg_commit();
      ws = ws == 4 * WSLOT ? 0 : ws + 2 * WSLOT;
      if (uv == 2) {
        split(P.ulo, 30);
        REGION_IDS;
        const uint32_t tag = !(lane & 3);
        if (elect()) red_hint(uh);
        uint32_t x[4];
#pragma unroll
        for (int k = 0; k < 4; k++) asm volatile("movmatrix.sync.aligned.m8n8.trans.b16 %0, %1;" : "=r"(x[k]) : "r"(pack_bf16(d[2 * k], d[2 * k + 1])));
        const uint32_t y1 = __shfl_up_sync(~0u, x[1], 8), y3 = __shfl_up_sync(~0u, x[3], 8);
        if (lane < 16) {
          st_relaxed32((uint32_t*)((uint64_t)ud0 ^ 2 * (lane & 8)), set_tag(lane < 8 ? x[0] : y1, tag, par));
          if (!wg) st_relaxed32((uint32_t*)((uint64_t)ud1 ^ 2 * (lane & 8)), set_tag(lane < 8 ? x[2] : y3, tag, par));
        }
      }
    };
#pragma unroll 1
    for (int n = 0; n < UVS; n++) step(n, 0);
    step(UVS, 1);
    step(UVS + 1, 2);
#pragma unroll 1
    for (int n = UVS + 2; n < 10; n++) step(n, 0);
    float o[80];
    uint32_t fr[3][16], bo;
    {
      REGION_IDS;
      float r0, r1, s0, s1;
      const int id = role, j = role;
      uint4* const hdst = G->hh + id * 1536 + 128 * w + (lane ^ lane >> 3);
      const uint32_t keep = ~(~lane & 1), bit = par & ~keep;
      bo = 1024 + ((j & 1) << 23);
      auto own = [&](int i) { wg_rs160_1(o, fr[i >> 2] + 4 * (i & 3), mkdesc(DB + w2_at(i / 4) + (i & 3) * 2048, UNIT, bo, 1), i); };
      auto hint = [&](int v) { asm volatile("{.reg .pred p; setp.eq.u32 p, %1, 0; @p red.relaxed.gpu.global.add.u32 [%0], 1;}" ::"l"(&G->hhf[id * 8 + v]), "r"(lane) : "memory"); };
      auto put = [&](int v, int k) {
        uint32_t* x = fr[v] + 2 * k;
        const uint32_t t0 = (x[k / 2] & keep) | bit, t1 = (x[5 + k / 2] & keep) | bit;
        x[k / 2] = t0; x[5 + k / 2] = t1;
        st_relaxed128(hdst + 512 * v + 8 * k, x[0], x[2], x[4], x[6]);
        st_relaxed128(hdst + 512 * v + 8 * k + 64, x[1], x[3], x[5], x[7]);
      };
      auto move = [&](uint32_t* x, int n) {
#pragma unroll
        for (int k = 0; k < n; k++) asm volatile("mul.rn.f32 %0, %0, %1;" : "+r"(x[k]) : "f"(P.one));
      };
      auto act = [&](int i) {
        const int v = i >> 3, k = 7 - (i & 7);
        const float *g = v < 2 ? acc + 32 * v + 4 * k : acb + 4 * k, *up = g + (v < 2 ? 64 : 32);
        fr[v][2 * k] = pack_bf16(silu2(g[0], r0, s0) * up[0], silu2(g[1], r0, s0) * up[1]);
        fr[v][2 * k + 1] = pack_bf16(silu2(g[2], r1, s1) * up[2], silu2(g[3], r1, s1) * up[3]);
        if (!(k & 3)) { put(v, k); if (!k && !(HL >> v & 1)) hint(v); if (i == 15) { move(fr[0], 16); } }
        else asm volatile("" : "+r"(fr[v][2 * k]), "+r"(fr[v][2 * k + 1]));
      };
#pragma unroll
      for (int v = 0; v < 10; v++) {
        mbar_wait(BAR(B_FULL + 20 + v));
        if (v == XP) {
          mbar_wait(BAR(B_EXT));
          wg_fence();
          wg_ss192_01(acc, mkdesc(DB + OFF_AX + 1024 * opaque(wg), 0, 128, 0), mkdesc(DB + OFF_BX, 2048, 1024, 1), 1);
          wg_ss64_01(acc + 96, mkdesc(DB + OFF_AX + 1024 * opaque(wg), 0, 128, 0), mkdesc(DB + OFF_BX + 6144, 2048, 1024, 1), 1);
          wg_commit();
          r0 = 0.5f * __uint_as_float(lds32(base + OFF_RT + 256 * wg + 64 * w + (lane & 28)));
          r1 = 0.5f * __uint_as_float(lds32(base + OFF_RT + 256 * wg + 64 * w + 32 + (lane & 28)));
          s0 = 2.f * r0 * r0;
          s1 = 2.f * r1 * r1;
        }
        wg_fence();
#pragma unroll
        for (int k = 0; k < 4; k++) {
          wg_ss128_11(acb, mkdesc(opaque(abd) + a_at(second(v)) + k * 2048, 16, 1024, 1), mkdesc(DB + OFF_R + WSLOT * ((v + 2) % 6) + k * 2048, UNIT, 1024, 1), v + k);
          if (k == GB - 1) { wg_commit(); wg_wait<1>(); if (v == XP) fence_regs(acc); if (elect()) mbar_arrive(BAR(B_EMPTY + 19 + v)); }
        }
        if (v == 9) wg_ss128_01(acb, mkdesc(DB + OFF_AX + 1024 * opaque(wg), 0, 128, 0), mkdesc(DB + OFF_BX + UNIT, 2048, 1024, 1), 1);
        wg_commit();
        split(P.ulo, v);
        if (v == XP + NP / 2 && (HL & 1)) hint(0);
        if (v == XP + NP && (HL & 2)) hint(1);
#pragma unroll
        for (int i = 0; i < 16; i++) if (v >= XP && i * NP / 16 == v - XP) act(i);
      }
#pragma unroll
      for (int v = 0; v < 3; v++) {
        mbar_wait(BAR(B_FULL + 30 + v));
        wg_fence();
#pragma unroll
        for (int i = 0; i < 4; i++) {
          own(4 * v + i);
          if (i == GB - 1) { wg_commit(); wg_wait<1>(); if (v == 0) fence_regs(acb); if (elect()) mbar_arrive(BAR(B_EMPTY + 29 + v)); }
        }
        wg_commit();
        split(P.ulo, 10 + v);
        if (v == 0 && XP + NP == 10 && (HL & 2)) hint(1);
        if (v == 2 && (HL & 4)) hint(2);
#pragma unroll
        for (int i = 0; i < 4; i++) if (v < 2) act(16 + 4 * v + i);
      }
      ck = base + 2048 * w + 516 * (lane >> 3) + 144 * (lane >> 2 & 1) + 32 * (lane & 3);
    }
    uint32_t x1[40], gb[20];
    if (!wg) {
      REGION_IDS;
      mbar_wait(BAR(B_GB));
#pragma unroll
      for (int k = 0; k < 5; k++) {
        const uint4 g = lds128(base + OFF_GB + 80 * (lane & 3) + 16 * k);
        gb[4 * k] = g.x; gb[4 * k + 1] = g.y; gb[4 * k + 2] = g.z; gb[4 * k + 3] = g.w;
      }
    }
#pragma unroll 1
    for (int u = 33; u < 42; u++) {
      const int x = P.hid[wg][u - 33], as = x & ~15;
      const uint64_t wd = mkdesc(0, 0, bo, 1) | P.w2t[u - 30].x;
      mbar_wait(BAR(B_FULL + u));
      a_tile(as, x & 15, false);
      if (wg || u < LAG2) {
        wg_fence();
#pragma unroll
        for (int kk = 0; kk < 4; kk++) {
          wg_ss160_01(o, mkdesc(DB + as + kk / 2 * 512 + (kk & 1) * 32, 16, 1024, 2), wd + kk * 128, 1);
          if (kk == GB - 1) { wg_commit(); wg_wait<1>(); if (elect()) mbar_arrive(BAR(B_EMPTY + u - 1)); }
        }
        wg_commit();
        if (u == 41 && elect()) mbar_arrive(BAR(B_LAG));
      }
      if (u == LAG2 - 1 && !wg) {
        REGION_IDS;
        const uint32_t xa = base + (lane >> 4) * 1024 + (lane & 7) * 128 + (((2 * w + ((lane >> 3) & 1)) ^ (lane & 7)) << 4);
        mbar_wait(BAR(B_FULL + 42));
        wg_wait<0>();
        if (elect()) mbar_arrive(BAR(B_EMPTY + LAG2 - 1));
#pragma unroll
        for (int k = 0; k < 10; k++) ldmatrix_x4_t(x1 + 4 * k, xa + x1_at(k / 2) + (k & 1) * 2048);
      }
    }
    REGION_IDS;
    const int h = role >> 2 & 1, j = role & 3;
    const uint32_t xb = base + OFF_XCH + 5120 * w;
    if (wg) {
      const uint32_t rdst = mapa(xb + 16 * lane, h ^ 1), rbar = mapa(BAR(B_FULL + 1), h ^ 1);
      mbar_wait(BAR(B_XFREE));
      wg_wait<0>();
      fence_regs(o);
#pragma unroll
      for (int k = 0; k < 10; k++)
        asm volatile("st.async.shared::cluster.mbarrier::complete_tx::bytes.v4.b32 [%0], {%1,%2,%3,%4}, [%5];" ::"r"(rdst + 512 * k), "r"(pack_bf16(o[8 * k], o[8 * k + 1])),
                     "r"(pack_bf16(o[8 * k + 2], o[8 * k + 3])), "r"(pack_bf16(o[8 * k + 4], o[8 * k + 5])), "r"(pack_bf16(o[8 * k + 6], o[8 * k + 7])), "r"(rbar + 16 * (k / 4)) : "memory");
    } else {
      mbar_wait(BAR(B_LAG));
      wg_fence();
#pragma unroll
      for (int i = 4 * LAG2; i < 168; i++) wg_ss160_01(o, mkdesc(DB + hid_at(i / 4 - 33, 0) + (i & 2) * 256 + (i & 1) * 32, 16, 1024, 2), mkdesc(DB + w2_at(i / 4 - 30) + (i & 3) * 2048, UNIT, bo, 1), 1);
      wg_commit();
      const int row = (8 * role & ~63) + 16 * w;
      auto merge = [&](int e0, int e1) {
#pragma unroll
        for (int e = e0; e < e1; e++) {
          if (e % 4 == 0) mbar_wait_cluster(BAR(B_FULL + 1 + e / 2));
          const uint4 p = lds128(xb + 16 * lane + 512 * e);
          x1[4 * e] = bfma2(gb[2 * e], p.x, x1[4 * e]); x1[4 * e + 1] = bfma2(gb[2 * e], p.y, x1[4 * e + 1]);
          x1[4 * e + 2] = bfma2(gb[2 * e + 1], p.z, x1[4 * e + 2]); x1[4 * e + 3] = bfma2(gb[2 * e + 1], p.w, x1[4 * e + 3]);
        }
        __syncwarp();
      };
      merge(0, MG);
      wg_wait<0>();
      fence_regs(o);
#pragma unroll
      for (int k = 0; k < 10; k++) {
        if (k >= MG && k % 4 == 0) merge(k, k < 8 ? k + 4 : 10);
        uint32_t y[4];
#pragma unroll
        for (int e = 0; e < 4; e++) y[e] = bfma2(gb[2 * k + e / 2], pack_bf16(o[8 * k + 2 * e], o[8 * k + 2 * e + 1]), x1[4 * k + e]);
        stmatrix_x4(k < 8 ? xb + 2048 * (k >> 2) + (lane & 15) * 128 + (((2 * (k & 3) + (lane >> 4)) ^ (lane & 7) ^ 4 * (j & 1)) << 4)
                          : xb + 4096 + (lane & 15) * 64 + (((2 * (k & 1) + (lane >> 4)) ^ (lane >> 1 & 3)) << 4), y[0], y[1], y[2], y[3]);
        if ((SG >> k & 1) || k == 9) {
          fence_async_smem();
          __syncwarp();
#pragma unroll
          for (int b = 0; b < 3; b++) {
            const int e = b < 2 ? 4 * b + 3 : 9;
            if (e <= k && !(SG & ((1 << k) - 1) & ~((1 << e) - 1)) && lane == 0) tma2d_store(b < 2 ? &maps.outa : &maps.outb, b < 2 ? 128 * j + 64 * b : 512 + 32 * j, row, xb + 2048 * b);
          }
        }
      }
      if (lane == 0) { bulk_commit(); bulk_wait_read(); }
    }
  } else if (wg == 2) {
    asm volatile("setmaxnreg.dec.sync.aligned.u32 40;");
    mbar_init<15>(BAR(B_FULL + 15 * w), 1);
    mbar_init<11>(BAR(B_EMPTY - 1 + 11 * w), 8);
    asm volatile("fence.mbarrier_init.release.cluster;" ::: "memory");
    LAUNCHES;
    silu_vector(P.c + 80 * (blockIdx.x & 7) - 512, 296, base - 1024);
    const uint32_t epoch = EPOCH;
    if (w == 2) rank_pair(G, base, epoch, true);
    cluster_wait();
    {
      REGION_IDS;
      const uint32_t tag = opaque(~lane & 1);
      auto q_t = [&]() {
        const int tr = 4 * (lane & 1) + (lane >> 1 & 3);
        uint32_t a = base + OFF_Q + 128 * ((lane & 24) + tr) + ((w ^ tr) << 4);
        uint4* dst = G->qt + (64 * (bid & 1) + 8 * w + (lane >> 2)) * 256 + 4 * (bid >> 1) + (lane & 3);
#pragma unroll 1
        for (int c = 0; c < 5; c++) {
          mbar_wait(BAR(B_Q + c));
#pragma unroll
          for (int k = 0; k < 2; k++) {
            uint32_t x[4];
            ldmatrix_x4_t(x, a ^ (64 * k));
            st_relaxed128(dst + 8192 * k, set_tag(x[0], tag, epoch), x[1], x[2], x[3]);
          }
          a += 4096;
          dst += 32768;
        }
        arrive1(BAR(B_QTD));
      };
      q_t();
      if (w == 3) {
        mbar_wait_cluster(BAR(B_ST1));
        if (lane < 8) red_hint(G->hint[5][lane]);
        const uint2 x = lds64(base + OFF_ST + 8 * (lane & 15)), y = lds64(base + OFF_ST + 128 + 8 * (lane & 15));
        float m, sd;
        ln_final(__uint_as_float(x.x) + __uint_as_float(y.x), __uint_as_float(x.y) + __uint_as_float(y.y), m, sd);
        sd = rbf(rcpf(sd));
        const uint32_t mr = pack_bf16(sd, -rbf(m) * sd), tg = lane & 7 ? 0 : lane & 8 ? 1 : 0x8000;
        const uint32_t o = __byte_perm(__shfl_sync(~0u, mr, 2 * lane & 14), __shfl_sync(~0u, mr, (2 * lane & 14) + 1), (lane & 8) ? 0x7632 : 0x5410);
        if (lane < 16) st_relaxed32(&G->st1[lane >> 3][8 * bid + (lane & 7)], (o & ~tg) | ((epoch & 1) * tg));
      }
      if (w == 2) rank_pair(G, base, epoch, false);
      if (w == 1) mod_fetch(G, base, epoch, M8, 0, 1);
    }
    {
      REGION_IDS;
      const uint32_t tag = opaque(~lane & 1), sa = opaque(base + 16 * i0);
      uint4 q[2];
      mbar_wait(BAR(B_PFULL));
#pragma unroll 1
      for (uint32_t a = sa + tab(T_P, 0); a < sa + tab(T_P, 0) + 4096; a += 2048) {
        uint4 y = lds128(a), z = lds128(a + 4096), u = lds128(a + 8192);
        const uint4 v = lds128(a + 12288);
        add4(y, z); add4(u, v); add4(y, u);
        sts128(a, y.x, y.y, y.z, y.w);
      }
      uint4* gp = G->xs + 256 * bid + (sa - base >> 4);
      q[0] = ld_relaxed128(gp - D_ * 256);
      q[1] = ld_relaxed128(gp - D_ * 256 + 128);
      mbar_wait(BAR(B_MR));
      e_round<true>(G, base, sa, gp, q, 0, w, tag, epoch);
#pragma unroll 1
      for (int c = 1; c < 5; c++) e_round<false>(G, base, sa, gp, q, c, w, tag, epoch);
    }
    int h, j, r;
    ffn_role(h, j, r);
    arrive1(BAR(B_ED));
    {
      REGION_IDS;
      float s0 = 0.f, q0 = 0.f, s1 = 0.f, q1 = 0.f;
#pragma unroll 1
      for (int c = 2; c < 5; c++) {
        const uint32_t buf = base + OFF_SX + 4096 * (c - 2), b = BAR(B_SX + c);
        uint32_t x[8];
#pragma unroll 1
        for (int it = 0; it < SPIN_LIMIT; it++) {
          mbar_wait(b, it & 1);
#pragma unroll
          for (int i = 0; i < 8; i++) x[i] = lds32(buf + 1024 * w + 4 * lane + 128 * i);
          if (bar_all(3, (lane & 7) || min(min(min(x[0], x[1]), min(x[2], x[3])), min(min(x[4], x[5]), min(x[6], x[7]))))) break;
          if (w == 0 && elect()) { mbar_expect_tx(b, 4096); tma2d(buf, &maps.x1s, 128 * r + 64 * h, D_ * (epoch & 1) + 128 * c + 32 * j, b); }
        }
#pragma unroll
        for (int i = 0; i < 8; i++) { const float lo = bf_lo(x[i]), hi = bf_hi(x[i]); s0 += lo; q0 = fmaf(lo, lo, q0); s1 += hi; q1 = fmaf(hi, hi, q1); }
      }
      sts128(base + OFF_MR + 1024 * w + 16 * lane, __float_as_uint(s0), __float_as_uint(q0), __float_as_uint(s1), __float_as_uint(q1));
      arrive1(BAR(B_S2));
    }
    {
      REGION_IDS;
      const uint32_t* sp = &G->st2[2 * r + (h ^ (w >> 1))][0][2 * (i0 & 63)];
      uint2 x[4];
      int it;
#pragma unroll 1
      for (it = 0; it < SPIN_LIMIT; it++) {
        mbar_wait(BAR(B_BX), it & 1);
        uint32_t y = 0;
#pragma unroll
        for (int k = 0; k < 3; k++) y |= lds32(base + OFF_BX + 32 * i0 + 4096 * k) ^ epoch;
        if (bar_all(3, !(y & 1))) break;
        if (w == 0 && elect()) { mbar_expect_tx(BAR(B_BX), 12288); bulk_load(base + OFF_BX, G->uv[4 * h + j], 12288, BAR(B_BX)); }
      }
      it = 0;
#pragma unroll 1
      do {
#pragma unroll
        for (int k = 0; k < 4; k++) x[k] = ld_relaxed64(sp + 128 * k);
      } while (__any_sync(~0u, ((x[0].x ^ epoch) | (x[1].x ^ epoch) | (x[2].x ^ epoch) | (x[3].x ^ epoch)) & 1) && ++it < SPIN_LIMIT);
      float m, sd;
      ln_final((__uint_as_float(x[0].x) + __uint_as_float(x[1].x)) + (__uint_as_float(x[2].x) + __uint_as_float(x[3].x)),
               (__uint_as_float(x[0].y) + __uint_as_float(x[1].y)) + (__uint_as_float(x[2].y) + __uint_as_float(x[3].y)), m, sd);
      const uint32_t e = pack_bf16(-m, sd);
      sts128(base + OFF_AX + 16 * i0, e, e, e, e);
      sts32(base + OFF_RT + 4 * i0, __float_as_uint(rcpf(sd)));
      fence_async_smem();
      arrive1(BAR(B_EXT));
      {
        uint2 g0, g1;
        int it = 0;
#pragma unroll 1
        do {
          g0 = ld_relaxed64(&G->modv[1][128 * j + i0]);
          g1 = ld_relaxed64(&G->modv[1][512 + 32 * j + lane]);
        } while (__any_sync(~0u, ((g0.x ^ epoch) | (g0.y ^ epoch) | (g1.x ^ epoch) | (g1.y ^ epoch)) & 1) && ++it < SPIN_LIMIT);
        const uint32_t a = base + OFF_GB + 40 * (lane & 6) + 2 * (lane & 1) + (lane >> 3) * 4;
        asm volatile("st.shared.u16 [%0], %1; st.shared.u16 [%2], %3;" ::"r"(a + 16 * (w ^ (j & 1))), "h"((uint16_t)(mod_sum(g0) >> 16)), "r"(a + 64), "h"((uint16_t)(mod_sum(g1) >> 16)) : "memory");
        arrive1(BAR(B_GB));
      }
      const int id = 16 * r + 4 * h + ((j + 1 + w) & 3);
#pragma unroll 1
      for (int q = w == 3 ? 3 : 0; q < 3; q++) {
        const int m = 3 * q + w;
        const uint4* src = G->hh + id * 1536 + 512 * q;
        it = 0;
#pragma unroll 1
        while (__any_sync(~0u, ld_relaxed32(&G->hhf[8 * id + 64 * (lane & 1) + q]) != 4 * epoch) && ++it < SPIN_LIMIT);
        mbar_wait(BAR(P.hid[2][m]));
        if (elect()) {
          bulk_load(base + (P.hid[h][m] & ~15), src, UNIT, BAR(B_FULL + 33 + m));
          bulk_load(base + (P.hid[h ^ 1][m] & ~15), src + 8 * 1536, UNIT, BAR(B_FULL + 33 + m));
        }
      }
    }
  } else {
    asm volatile("setmaxnreg.dec.sync.aligned.u32 24;");
    if (w >= 2) {
      LAUNCHES;
      uint32_t epoch;
      {
        REGION_IDS;
        uint32_t dv;
        asm volatile("ld.global.nc.u16 %0, [%1];" : "=r"(dv) : "l"(P.ssmd + 128 * (lane & 7) % D_ + bid));
        if (lane < 5) sts128(base + tab(T_F, lane) + (w & 1) * (F_O - F_E) + F_E - 16, 0, 0, 0, 0);
        epoch = EPOCH;
        __syncwarp();
#pragma unroll 1
        for (int c = 0; c < 5; c++) {
          const float d = i0 == 64 ? bf_lo(dv) : 0.f;
          dv = __shfl_down_sync(~0u, dv, 1);
          const uint32_t a = base + tab(T_F, c) + 16 * (i0 - 64);
          mbar_wait(BAR(B_FRAW + c));
#pragma unroll
          for (int k = 0; k < 4; k++) {
            uint4 x = lds128(a + F_E + 1024 * k);
            const uint32_t pv = lds32(a + F_E - 4 + 1024 * k);
            if (k == 0) { x.x = pack_bf16(bf_lo(x.x) + d, bf_hi(x.x)); sts32(a + F_E, x.x); }
            sts128(a + F_O + 1024 * k, __byte_perm(pv, x.x, 0x5432), __byte_perm(x.x, x.y, 0x5432), __byte_perm(x.y, x.z, 0x5432), __byte_perm(x.z, x.w, 0x5432));
          }
          __syncwarp();
          if (elect()) mbar_arrive2(BAR(B_FRDY + c));
          if (c == 0 && w == 3) {
#pragma unroll 1
            for (int k = 0; k < 13; k++) prefetch_map(&maps.w1a + k);
          }
        }
      }
      REGION_IDS;
      int h, j, r;
      ffn_role(h, j, r);
      cluster_wait();
      if (w == 2) {
        const unsigned* fp = G->xsh[lane < 10 ? lane >> 1 : 0][(r & 6) + (lane & 1)];
        uint32_t rdy = 0;
        mbar_wait(BAR(B_SC + 4));
#pragma unroll 1
        for (int e = 0; e < 14; e++) {
          const uint32_t x = P.adep[e], n = x >> 21 & 15, s = base + (x >> 25 << 13), b = BAR(B_FULL + (x >> 16 & 31));
          mbar_wait(BAR(opaque(x & 255)));
          mbar_wait(BAR(opaque(x >> 8 & 255)));
          const uint32_t f = BAR(B_FULL + 7 + 2 * (e < 7 ? e : e - 7));
          if (elect()) mbar_arrive_remote(mapa(f, h ^ 1));
#pragma unroll 1
          for (int it = 0; !(rdy >> n & 1) && it < SPIN_LIMIT; it++) rdy = __ballot_sync(~0u, ld_relaxed32(fp) == 64 * epoch);
          mbar_wait(f, e >= 7);
          if (elect()) asm volatile("cp.async.bulk.tensor.2d.shared::cluster.global.mbarrier::complete_tx::bytes.multicast::cluster [%0], [%1, {%3,%4}], [%2], %5;"
                                    ::"r"(s + UNIT * h), "l"(&maps.xs), "r"(b), "r"(128 * r + 64 * h), "r"(64 * n), "h"((uint16_t)3) : "memory");
        }
#pragma unroll 1
        for (int v = 0; v < 12; v++) {
          const int q = v * 11 >> 5, e = v - 3 * q, k32 = 24 * h + (q ? 6 * ((j + 1 + e) & 3) + 2 * q - 2 : 6 * j + 2 * e);
          const uint2 x = P.w2t[v];
          mbar_wait(BAR(x.y));
          if (elect()) {
            mbar_expect_tx(BAR(B_FULL + 30 + v), q ? W2TILE + 2 * UNIT : W2TILE);
#pragma unroll
            for (int k = 0; k < 3; k++) tma5d(base - DB + 16 * (x.x & 0xFFFF) + UNIT * k, &maps.w2a + (q > 0), k < 2 ? 128 * j + 64 * k : 512 + 32 * (j & 2), k32, BAR(B_FULL + 30 + v));
          }
        }
      } else {
        float s0 = 0.f, q0 = 0.f, s1 = 0.f, q1 = 0.f;
        uint32_t nl = 0, np = 0, ph = 0;
#pragma unroll 1
        for (uint32_t seq = 0x94; seq > 1; seq >>= 1) {
          const uint32_t c = seq & 1 ? np : nl, buf = base + OFF_SX + 4096 * (c < 4 ? c & 1 : 2), b = BAR(opaque(B_SX + c));
          int it = 0;
          if (seq & 1) {
            mbar_wait(b, ph >> c & 1);
            ph ^= 1 << c;
            const uint32_t a = buf + 32 * lane;
            if (__all_sync(~0u, min(min(lds32(a), lds32(a + 1024)), min(lds32(a + 2048), lds32(a + 3072)))) || ph > SPIN_LIMIT) {
#pragma unroll 1
              for (uint32_t o = buf + 4 * lane; o < buf + 4096; o += 1024) {
                uint32_t x[8];
#pragma unroll
                for (int i = 0; i < 8; i++) x[i] = lds32(o + 128 * i);
#pragma unroll
                for (int i = 0; i < 8; i++) { const float lo = bf_lo(x[i]), hi = bf_hi(x[i]); s0 += lo; q0 = fmaf(lo, lo, q0); s1 += hi; q1 = fmaf(hi, hi, q1); }
              }
              np++;
              continue;
            }
            ph += 4;
            seq = 2 * seq + 1;
          } else {
#pragma unroll 1
            while (__any_sync(~0u, ld_relaxed32(G->xsh[c][(r & 6) + (j >> 1)]) != 64 * epoch) && ++it < SPIN_LIMIT);
            if (++nl == 5) mbar_wait(BAR(B_PEMPTY + 4));
          }
          if (elect()) { mbar_expect_tx(b, 4096); tma2d(buf, &maps.x1s, 128 * r + 64 * h, D_ * (epoch & 1) + 128 * c + 32 * j, b); }
        }
        mbar_wait(BAR(B_S2));
#pragma unroll
        for (int k = 0; k < 4; k++) {
          const uint4 x = lds128(base + OFF_MR + 1024 * k + 16 * lane);
          s0 += __uint_as_float(x.x); q0 += __uint_as_float(x.y); s1 += __uint_as_float(x.z); q1 += __uint_as_float(x.w);
        }
        asm volatile("{.reg .b128 t, x; .reg .b64 a, b; mov.b64 a, {%1,%2}; mov.b64 b, {%3,%4}; mov.b128 x, {a,b}; atom.relaxed.gpu.global.exch.b128 t, [%0], x;}"
                     ::"l"(&G->st2[2 * r + h][j][4 * lane]), "r"((__float_as_uint(s0) & ~1u) | (epoch & 1)), "f"(q0), "r"((__float_as_uint(s1) & ~1u) | (epoch & 1)), "f"(q1) : "memory");
        mbar_wait(BAR(B_EMPTY + 2 * UVS + 1));
        sts128(base + OFF_CO + 16 * lane, 0, 0, 0, 0);
        fence_async_smem();
        __syncwarp();
        if (elect()) {
#pragma unroll 1
          for (int k = 0; k < 40; k++) asm volatile("cp.async.bulk.global.shared::cta.bulk_group [%0], [%1], 512;" ::"l"(G->x1[~epoch & 1] + 1280 * blockIdx.x + 32 * k), "r"(base + OFF_CO) : "memory");
          bulk_commit();
          bulk_wait_read();
        }
      }
    } else if (w == 0) {
      LAUNCHES;
      uint32_t epoch;
      {
        REGION_IDS;
        const unsigned* hp = G->hint[0][4 * (bid >> 6) + (bid >> 3 & 3)];
        uint32_t v = ld_relaxed32(hp + 256 * min(lane, 5));
        if (lane < 3) sts128(base + tab(T_X, lane) + 4096, 0, 0, 0, 0);
        if (lane && lane <= B_WM) mbar_expect_tx(BAR(lane), lane < B_FRAW ? 9728 : lane == B_WM ? 10240 : 4096);
        epoch = EPOCH;
        fence_async_smem();
        const uint32_t rdy = __ballot_sync(~0u, v == epoch << 6) & 31;
        uint32_t nx = 0, mr = 1;
#pragma unroll 1
        for (int it = 0; (nx < 5 || mr) && it < SPIN_LIMIT; it++) {
          const bool second = nx == 5 || (lane && mr && nx >= P.mq);
          if (!(rdy >> nx & 1)) v = ld_relaxed32(hp + 256 * (second ? 5 : nx));
          const uint32_t ok = __ballot_sync(~0u, v == epoch << (second ? 7 : 6)) | (rdy >> nx & 1);
          if (nx < 5 && (ok & 1)) {
            if (nx >= 3) mbar_wait(BAR(B_PFULL - 3 + nx));
            if (elect()) { mbar_expect_tx(BAR(B_XR + nx), 4096); bulk_load(base + tab(T_X, nx), G->xr + (128 * nx + bid) * 256, 4096, BAR(B_XR + nx)); }
          }
          if (mr && (nx == 5 || nx >= P.mq) && (ok & 2) && !(rdy >> nx & 1)) {
            if (elect()) { mbar_expect_tx(BAR(B_MR), 8192); bulk_load(base + OFF_MR, G->st1, 8192, BAR(B_MR)); mbar_arrive(BAR(B_QTOK)); }
            mr = 0;
          }
          if (nx < 5) nx += ok & 1;
        }
        mod_fetch(G, base, epoch, M8, 2, 5);
      }
      REGION_IDS;
      int h, j, r;
      ffn_role(h, j, r);
      cluster_wait();
      if (elect()) mbar_expect_tx(BAR(B_UVB), 30720);
#pragma unroll 1
      for (int k = 0; k < 5; k++) {
        mbar_wait(BAR(opaque(B_EMPTY + nib(P.uvd, k))));
        if (elect()) tma3d(base + OFF_UV + 6144 * k, &maps.w1u + (r & 1), 0, 40 * (r & 14) + 16 * k, 3 * (4 * h + j), BAR(B_UVB));
      }
      mbar_wait(BAR(B_G));
      {
        const uint2* mp = &G->modv[lane & 4 ? 0 : 2][40 * (r & 14) + (lane & 24) + 2 * (lane & 3)];
        uint4 v[3];
        int it = 0;
#pragma unroll 1
        do {
          v[0] = ld_relaxed128(mp); v[1] = ld_relaxed128(mp + 32); v[2] = ld_relaxed128(mp + 64 - (lane & 16));
        } while (__any_sync(~0u, ((v[0].x ^ epoch) | (v[0].y ^ epoch) | (v[0].z ^ epoch) | (v[0].w ^ epoch) | (v[1].x ^ epoch) | (v[1].y ^ epoch) | (v[1].z ^ epoch) | (v[1].w ^ epoch) |
                                  (v[2].x ^ epoch) | (v[2].y ^ epoch) | (v[2].z ^ epoch) | (v[2].w ^ epoch)) & 1) && ++it < SPIN_LIMIT);
#pragma unroll
        for (int i = 0; i < 3; i++)
          sts32(base + OFF_CO + 128 * i + 4 * lane, badd2(pack_bf16(__uint_as_float(v[i].x) + __uint_as_float(v[i].y), __uint_as_float(v[i].z) + __uint_as_float(v[i].w)), lane & 4 ? 0 : 0x3F803F80u));
      }
      fence_async_smem();
      arrive1(BAR(B_CO));
      ffn_role(h, j, r);
      mbar_wait(BAR(B_ED));
      int it = 0;
#pragma unroll 1
      while (__any_sync(~0u, ld_relaxed32(G->hint[8][4 * h + j]) != 128 * epoch) && ++it < SPIN_LIMIT);
      if (elect()) { mbar_expect_tx(BAR(B_BX), 12288); bulk_load(base + OFF_BX, G->uv[4 * h + j], 12288, BAR(B_BX)); }
      asm volatile("fence.acq_rel.gpu;" ::: "memory");
      if (lane < 8) red_hint(G->hint[7][lane]);
      unsigned x;
      it = 0;
#pragma unroll 1
      do { asm volatile("ld.acquire.gpu.global.u32 %0, [%1];" : "=r"(x) : "l"(G->hint[7][bid >> 4]) : "memory"); } while (__any_sync(~0u, x != 128 * epoch) && ++it < SPIN_LIMIT);
      fence_async_all();
      const int ch = D_ * (epoch & 1);
      mbar_wait(BAR(P.xdep));
      if (elect()) {
        mbar_expect_tx(BAR(B_FULL + 42), 20480);
#pragma unroll
        for (int k = 0; k < 4; k++) tma2d(base + x1_at(k), &maps.x1b, 128 * r + 64 * h, ch + 128 * j + 32 * (k ^ (j & 1)), BAR(B_FULL + 42));
        tma2d(base + x1_at(4), &maps.x1b, 128 * r + 64 * h, ch + 512 + 32 * j, BAR(B_FULL + 42));
        mbar_expect_tx(BAR(B_FULL + 1), 8192); mbar_expect_tx(BAR(B_FULL + 3), 8192); mbar_expect_tx(BAR(B_FULL + 5), 4096);
      }
      mbar_wait(BAR(B_EMPTY + 37));
      if (elect()) mbar_arrive_remote(mapa(BAR(B_XFREE), h ^ 1));
    } else {
      LAUNCHES;
      {
        REGION_IDS;
        loads<0>(P, maps, base);
      }
      cluster_wait();
      int h, j, r;
      ffn_role(h, j, r);
      mbar_wait(BAR(B_QTD));
      mbar_wait(BAR(B_STD));
      mbar_wait(BAR(B_SC));
      mbar_wait(BAR(B_SC + 2));
      mbar_wait(BAR(B_FL));
#pragma unroll 1
      for (int u = 0; u < 30; u++) {
        if (u == P.mpos) mod_fetch(G, base, EPOCH, M8, 1, 2);
        if (u < 6) wait_clock(t_start + P.wt0 + u * P.wpace);
        const uint32_t x = P.wdep[u], b = x >> 8 & 1;
        uint32_t s = base + OFF_R + WSLOT * (x >> 9 & 7), f = BAR(B_FULL + (b ? u : u & ~1)), n = x & 0xC000, y = x >> 16, z = 3 * (4 * h + j) + 2 * b;
        const CUtensorMap* m = &maps.w1a + 5 * b;
        asm volatile("{.reg .pred p, q; .reg .b32 i, t; .reg .b64 m; mov.u32 i, 0; add.u32 t, %0, 8192; add.u64 m, %1, 128; elect.sync _|q, 0xffffffff;"
                     "W: mbarrier.try_wait.parity.shared::cta.b64 p, [%6], 0; @p bra.uni D; add.u32 i, i, 1; setp.lt.u32 p, i, %7; @p bra.uni W; D:"
                     "setp.ne.and.u32 p, %3, 0, q; @p mbarrier.arrive.expect_tx.shared::cta.b64 _, [%2], %3;"
                     "@q cp.async.bulk.tensor.3d.shared::cluster.global.mbarrier::complete_tx::bytes [%0], [%1, {0,%4,%5}], [%2];"
                     "@q cp.async.bulk.tensor.3d.shared::cluster.global.mbarrier::complete_tx::bytes [t], [m, {0,%4,%5}], [%2];}"
                     ::"r"(s), "l"(m), "r"(f), "r"(n), "r"(y), "r"(z), "r"(BAR(opaque(x & 255))), "n"(SPIN_LIMIT) : "memory");
      }
    }
  }
}

typedef CUresult (*EncFn)(CUtensorMap*, CUtensorMapDataType, cuuint32_t, void*, const cuuint64_t*, const cuuint64_t*, const cuuint32_t*,
                          const cuuint32_t*, CUtensorMapInterleave, CUtensorMapSwizzle, CUtensorMapL2promotion, CUtensorMapFloatOOBfill);
static int enc_err = 0;
static void enc(EncFn fn, CUtensorMap* m, const void* p, int rank, const cuuint64_t* gd, const cuuint64_t* gs, const cuuint32_t* bd, CUtensorMapSwizzle sw) {
  cuuint32_t es[5] = {1, 1, 1, 1, 1};
  enc_err = 2 * enc_err + (fn(m, CU_TENSOR_MAP_DATA_TYPE_BFLOAT16, rank, (void*)p, gd, gs, bd, es, CU_TENSOR_MAP_INTERLEAVE_NONE, sw,
                              CU_TENSOR_MAP_L2_PROMOTION_L2_128B, CU_TENSOR_MAP_FLOAT_OOB_FILL_NONE) != CUDA_SUCCESS);
}

extern "C" void kernel_launch(void* const* d_in, const int* in_sizes, int n_in, void* d_out, int out_size) {
  const bf16 *q = (const bf16*)d_in[0], *k = (const bf16*)d_in[1], *v = (const bf16*)d_in[2], *shift = (const bf16*)d_in[3],
             *ssmk = (const bf16*)d_in[4], *ssmd = (const bf16*)d_in[5], *w1 = (const bf16*)d_in[7], *w3 = (const bf16*)d_in[8],
             *w2 = (const bf16*)d_in[9], *c = (const bf16*)d_in[10], *wmod = (const bf16*)d_in[11];
  EncFn fn = nullptr;
  cudaDriverEntryPointQueryResult qr;
  cudaGetDriverEntryPoint("cuTensorMapEncodeTiled", (void**)&fn, cudaEnableDefault, &qr);
  Scratch* pg;
  cudaGetSymbolAddress((void**)&pg, g_s);
  Maps maps;
  enc_err = 0;
  const CUtensorMapSwizzle S128 = CU_TENSOR_MAP_SWIZZLE_128B;
  { cuuint64_t gd[3] = {D_, S_ / 8, 8}, gs[2] = {D_ * 16, D_ * 2}; cuuint32_t b[3] = {64, 4, 8};
    enc(fn, &maps.km, k, 3, gd, gs, b, S128);
    enc(fn, &maps.v, v, 3, gd, gs, b, S128);
    enc(fn, &maps.q, q, 3, gd, gs, b, S128);
    b[2] = 3;
    enc(fn, &maps.kh, k, 3, gd, gs, b, S128); }
  { cuuint64_t gd[3] = {256, 8, D_}, gs[2] = {512, 4096}; cuuint32_t b[3] = {256, 8, 1};
    enc(fn, &maps.fm, ssmk, 3, gd, gs, b, CU_TENSOR_MAP_SWIZZLE_NONE); }
  { cuuint64_t gd[3] = {256, 2, 5}, gs[2] = {512, 1024}; cuuint32_t b[3] = {256, 1, 5};
    enc(fn, &maps.tap, shift, 3, gd, gs, b, CU_TENSOR_MAP_SWIZZLE_NONE); }
  { cuuint64_t gd[3] = {6 * D_, D_, 1}, gs[2] = {6 * D_ * 2, 6 * D_ * 2 * D_}; cuuint32_t b[3] = {64, 64, 1};
    enc(fn, &maps.wm, wmod, 3, gd, gs, b, S128);
    b[1] = 80;
    enc(fn, &maps.wmp, wmod, 3, gd, gs, b, S128); }
  { cuuint64_t gd[3] = {64, D_, F_ / 64}, gs[2] = {F_ * 2, 128}; cuuint32_t b[3] = {64, 16, 3};
    enc(fn, &maps.w1u, w1, 3, gd, gs, b, S128);
    enc(fn, &maps.w3u, w3, 3, gd, gs, b, S128);
    b[1] = 32; b[2] = 2;
    enc(fn, &maps.w1a, w1, 3, gd, gs, b, S128);
    enc(fn, &maps.w3a, w3, 3, gd, gs, b, S128);
    b[1] = 64; b[2] = 1;
    enc(fn, &maps.w1b, w1, 3, gd, gs, b, S128);
    enc(fn, &maps.w3b, w3, 3, gd, gs, b, S128); }
  { cuuint64_t gd[2] = {S_, D_}, gs[1] = {S_ * 2}; cuuint32_t b1[2] = {64, 64}, b2[2] = {64, 32};
    enc(fn, &maps.xs, pg->xs, 2, gd, gs, b1, S128);
    gd[1] = 2 * D_;
    enc(fn, &maps.x1b, pg->x1, 2, gd, gs, b2, S128);
    enc(fn, &maps.x1s, pg->x1, 2, gd, gs, b2, CU_TENSOR_MAP_SWIZZLE_NONE); }
  { cuuint64_t gd[5] = {D_, 2, 4, 4, 48}, gs[4] = {D_ * 2, D_ * 4, D_ * 16, D_ * 64}; cuuint32_t b[5] = {64, 2, 4, 4, 2};
    enc(fn, &maps.w2a, w2, 5, gd, gs, b, S128);
    gs[1] = D_ * 16; gs[2] = D_ * 4;
    enc(fn, &maps.w2b, w2, 5, gd, gs, b, S128); }
  { cuuint64_t gd[2] = {D_, S_}, gs[1] = {D_ * 2}; cuuint32_t b1[2] = {64, 16}, b2[2] = {32, 16};
    enc(fn, &maps.outa, d_out, 2, gd, gs, b1, S128);
    enc(fn, &maps.outb, d_out, 2, gd, gs, b2, CU_TENSOR_MAP_SWIZZLE_64B); }
  if (enc_err) return;
  cudaFuncSetAttribute(k_fused<0>, cudaFuncAttributeMaxDynamicSharedMemorySize, SMEM_BYTES);
  cudaFuncSetAttribute(k_fused<128>, cudaFuncAttributeMaxDynamicSharedMemorySize, SMEM_BYTES);
  cudaLaunchConfig_t cfg = {132, 512, SMEM_BYTES};
  cudaLaunchAttribute at = {cudaLaunchAttributeClusterDimension};
  at.val.clusterDim.x = 2; at.val.clusterDim.y = at.val.clusterDim.z = 1;
  cfg.attrs = &at; cfg.numAttrs = 1;
  int nc = 0;
  cudaOccupancyMaxActiveClusters(&nc, k_fused<0>, &cfg);
  Ptrs P = {c, ssmd, pg, {0x676360, 0x746209}, {}, 32, 3, 0, B_EMPTY + 32, 0 | 0 << 16, 0, {}, 0x33511, 0, 11400, 900, 1.f};
  const char* ho = "abcdefghijklmnopqrstuvwxyz{|}~";
  memset(P.hl, 255, sizeof(P.hl));
  for (int k = 0, n = 0; k < 30; k++) {
    const int i = ho[k] - 'a';
    if (i >= 20 || !(M8 >> i / 4 & 1)) ((uint8_t*)P.hl)[n++] = i;
  }
  for (int u = 0; u < 30; u++) P.wdep[u] = (u < 4 ? B_FL + 1 + u / 3 : u < 6 ? B_G : B_EMPTY + (u < 26 ? (u - 6) | 1 : u - 6)) | (u >= 20) << 8 | u % 6 << 9 | (u < 20 ? 3 * (~u & 1) : 1 + (u >= 26)) << 14 | (u < 20 ? 32 * u : 64 * (second(u - 20) % 10)) << 16;
  const int adep[14] = {B_PEMPTY, B_PEMPTY, B_PFULL + 4, B_PEMPTY + 1, B_PEMPTY + 2, B_EMPTY + 5, B_EMPTY + 7, B_PEMPTY + 3, B_EMPTY + 2 * UVS + 1, B_EMPTY + 2 * UVS + 1, B_EMPTY + 20, B_EMPTY + 21, B_EMPTY + 22, B_EMPTY + 23};
  const char *ad = "--*--d----uvwx", *wd = "255679:<=>?@", *hd = "789;;>?@A";
  for (int n = 0; n < 14; n++) P.adep[n] = adep[n] | (ad[n] == '-' ? adep[n] : ad[n] == '*' ? B_PFULL + 3 : B_EMPTY + ad[n] - 'a') << 8 | (n < 10 ? 2 * n : n + 16) << 16 | n % 10 << 21 | a_at(n) / UNIT << 25;
  for (int v = 0; v < 12; v++) P.w2t[v] = make_uint2(w2_desc(v), B_EMPTY + 20 + wd[v] - '0');
  for (int m = 0; m < 9; m++) { P.hid[0][m] = hid_at(m, 0) | m / 3 * 4 | (m % 3 + 1); P.hid[1][m] = hid_at(m, 1) | m / 3 * 4 | (m % 3 + 1); P.hid[2][m] = B_EMPTY + 20 + hd[m] - '0'; }
  if (nc < 66) k_fused<128><<<4, 512, SMEM_BYTES, cudaStreamPerThread>>>(P, maps);
  k_fused<0><<<nc < 66 ? 128 : 132, 512, SMEM_BYTES, cudaStreamPerThread>>>(P, maps);
}
```

```cpp
#include <cuda_runtime.h>
#include <cuda.h>
#include <cuda_bf16.h>
#include <stdint.h>
#include <stdlib.h>
#include <string.h>

typedef __nv_bfloat16 bf16;
constexpr int S_ = 2048, D_ = 640, F_ = 1536;

struct Scratch {
  uint32_t st1[2][1024];
  uint32_t st2[32][4][128];
  uint32_t modc[128][5][32];
  uint2 modv[3][D_];
  uint32_t uv[8][3072];
  unsigned hint[9][8][32];
  unsigned xsh[5][8][32], hhf[256 * 8], key[256];
  uint4 xr[D_ * 256];
  uint4 qt[D_ * 256];
  uint4 xs[D_ * 256];
  uint4 x1[2][D_ * 256];
  uint4 hh[32 * 8 * 1536];
};
__device__ __align__(1024) Scratch g_s;

__device__ __forceinline__ uint32_t smem_u32(const void* p) { return (uint32_t)__cvta_generic_to_shared(p); }
__device__ __forceinline__ void mbar_expect_tx(uint32_t b, uint32_t n) { asm volatile("mbarrier.arrive.expect_tx.shared::cta.b64 _, [%0], %1;" ::"r"(b), "r"(n) : "memory"); }
__device__ __forceinline__ void mbar_arrive(uint32_t b) { asm volatile("mbarrier.arrive.shared::cta.b64 _, [%0];" ::"r"(b) : "memory"); }
__device__ __forceinline__ void mbar_arrive2(uint32_t b) { asm volatile("mbarrier.arrive.shared::cta.b64 _, [%0], 2;" ::"r"(b) : "memory"); }
__device__ __forceinline__ uint32_t mapa(uint32_t a, uint32_t cta) { uint32_t r; asm volatile("mapa.shared::cluster.u32 %0, %1, %2;" : "=r"(r) : "r"(a), "r"(cta)); return r; }
__device__ __forceinline__ void mbar_arrive_remote(uint32_t rb) { asm volatile("mbarrier.arrive.shared::cluster.b64 _, [%0];" ::"r"(rb) : "memory"); }
constexpr int SPIN_LIMIT = 1 << 16;
template <int N> __device__ __forceinline__ void mbar_init(uint32_t b, uint32_t count) {
#pragma unroll
  for (int i = 0; i < N; i++) asm volatile("mbarrier.init.shared::cta.b64 [%0], %1;" ::"r"(b + 8 * i), "r"(count) : "memory");
}
__device__ __forceinline__ bool elect() { uint32_t p; asm volatile("{.reg .pred q; elect.sync _|q, 0xffffffff; selp.u32 %0, 1, 0, q;}" : "=r"(p)); return p; }
__device__ __forceinline__ void arrive1(uint32_t b) { __syncwarp(); if (elect()) mbar_arrive(b); }
__device__ __forceinline__ bool mbar_test(uint32_t b) {
  uint32_t ok;
  asm volatile("{.reg .pred p; mbarrier.test_wait.parity.shared::cta.b64 p, [%1], 0; selp.u32 %0,1,0,p;}" : "=r"(ok) : "r"(b) : "memory");
  return ok;
}
#define WAIT_LOOP(sem) "{.reg .pred p; mov.u32 %0, 0; W: mbarrier.try_wait.parity" sem ".shared::cta.b64 p, [%1], %2; @p bra.uni D; add.u32 %0, %0, 1; setp.lt.u32 p, %0, %3; @p bra.uni W; D:}"
__device__ __forceinline__ void mbar_wait(uint32_t b, uint32_t ph = 0) {
  int it;
  asm volatile(WAIT_LOOP("") : "=&r"(it) : "r"(b), "r"(ph), "n"(SPIN_LIMIT) : "memory");
}
__device__ __forceinline__ void mbar_wait_cluster(uint32_t b, uint32_t ph = 0) {
  int it;
  asm volatile(WAIT_LOOP(".acquire.cluster") : "=&r"(it) : "r"(b), "r"(ph), "n"(SPIN_LIMIT) : "memory");
}
__device__ __forceinline__ void wait_clock(uint32_t t) {
  asm volatile("{.reg .pred p; .reg .s32 d; W: mov.u32 d, %%clock; sub.s32 d, d, %0; setp.lt.s32 p, d, 0; @p bra.uni W;}" ::"r"(t) : "memory");
}
__device__ __forceinline__ void tma2d(uint32_t dst, const CUtensorMap* m, int c0, int c1, uint32_t bar) {
  asm volatile("cp.async.bulk.tensor.2d.shared::cluster.global.mbarrier::complete_tx::bytes [%0], [%1, {%3,%4}], [%2];" ::"r"(dst), "l"(m), "r"(bar), "r"(c0), "r"(c1) : "memory");
}
__device__ __forceinline__ void tma3d(uint32_t dst, const CUtensorMap* m, int c0, int c1, int c2, uint32_t bar) {
  asm volatile("cp.async.bulk.tensor.3d.shared::cluster.global.mbarrier::complete_tx::bytes [%0], [%1, {%3,%4,%5}], [%2];" ::"r"(dst), "l"(m), "r"(bar), "r"(c0), "r"(c1), "r"(c2) : "memory");
}
__device__ __forceinline__ void tma5d(uint32_t dst, const CUtensorMap* m, int c0, int c4, uint32_t bar) {
  asm volatile("cp.async.bulk.tensor.5d.shared::cluster.global.mbarrier::complete_tx::bytes [%0], [%1, {%4,%3,%3,%3,%5}], [%2];" ::"r"(dst), "l"(m), "r"(bar), "r"(0), "r"(c0), "r"(c4) : "memory");
}
__device__ __forceinline__ void tma2d_store(const CUtensorMap* m, int c0, int c1, uint32_t src) {
  asm volatile("cp.async.bulk.tensor.2d.global.shared::cta.bulk_group [%0, {%2,%3}], [%1];" ::"l"(m), "r"(src), "r"(c0), "r"(c1) : "memory");
}
__device__ __forceinline__ void bulk_load(uint32_t dst, const void* src, uint32_t bytes, uint32_t bar) {
  asm volatile("cp.async.bulk.shared::cluster.global.mbarrier::complete_tx::bytes [%0], [%1], %2, [%3];" ::"r"(dst), "l"(src), "r"(bytes), "r"(bar) : "memory");
}
__device__ __forceinline__ void prefetch_map(const CUtensorMap* m) { asm volatile("prefetch.tensormap [%0];" ::"l"(m) : "memory"); }
__device__ __forceinline__ void bulk_commit() { asm volatile("cp.async.bulk.commit_group;" ::: "memory"); }
__device__ __forceinline__ void bulk_wait_read() { asm volatile("cp.async.bulk.wait_group.read 0;" ::: "memory"); }
__device__ __forceinline__ void fence_async_smem() { asm volatile("fence.proxy.async.shared::cta;" ::: "memory"); }
__device__ __forceinline__ void fence_async_all() { asm volatile("fence.proxy.async.global;" ::: "memory"); }
__device__ __forceinline__ void named_bar(int id, int n) { asm volatile("bar.sync %0, %1;" ::"r"(id), "r"(n) : "memory"); }
__device__ __forceinline__ bool bar_all(int id, bool v) {
  uint32_t r;
  asm volatile("{.reg .pred p, q; setp.ne.u32 p, %2, 0; bar.red.and.pred q, %1, 128, p; selp.u32 %0, 1, 0, q;}" : "=r"(r) : "r"(id), "r"((uint32_t)v) : "memory");
  return __all_sync(~0u, r);
}
__device__ __forceinline__ void cluster_wait() { asm volatile("barrier.cluster.wait.aligned;" ::: "memory"); }
__device__ __forceinline__ void wg_fence() { asm volatile("wgmma.fence.sync.aligned;" ::: "memory"); }
__device__ __forceinline__ void wg_commit() { asm volatile("wgmma.commit_group.sync.aligned;" ::: "memory"); }
template <int N> __device__ __forceinline__ void wg_wait() { asm volatile("wgmma.wait_group.sync.aligned %0;" ::"n"(N) : "memory"); }
template <int N> __device__ __forceinline__ void fence_regs(float (&a)[N]) {
#pragma unroll
  for (int i = 0; i < N; i++) asm volatile("" : "+f"(a[i])::"memory");
}
__device__ __forceinline__ uint64_t mkdesc(uint32_t addr, uint32_t lbo, uint32_t sbo, uint32_t swz) {
  uint32_t lo = (addr >> 4) | ((lbo >> 4) << 16), hi = (sbo >> 4) | (swz << 30);
  return ((uint64_t)hi << 32) | lo;
}
__device__ __forceinline__ void stmatrix_x4(uint32_t a, uint32_t r0, uint32_t r1, uint32_t r2, uint32_t r3) {
  asm volatile("stmatrix.sync.aligned.m8n8.x4.shared.b16 [%0], {%1,%2,%3,%4};" ::"r"(a), "r"(r0), "r"(r1), "r"(r2), "r"(r3) : "memory");
}
__device__ __forceinline__ void stmatrix_x4_t(uint32_t a, uint32_t r0, uint32_t r1, uint32_t r2, uint32_t r3) {
  asm volatile("stmatrix.sync.aligned.m8n8.x4.trans.shared.b16 [%0], {%1,%2,%3,%4};" ::"r"(a), "r"(r0), "r"(r1), "r"(r2), "r"(r3) : "memory");
}
__device__ __forceinline__ void ldmatrix_x4_t(uint32_t* r, uint32_t a) {
  asm volatile("ldmatrix.sync.aligned.m8n8.x4.trans.shared.b16 {%0,%1,%2,%3}, [%4];" : "=r"(r[0]), "=r"(r[1]), "=r"(r[2]), "=r"(r[3]) : "r"(a) : "memory");
}
__device__ __forceinline__ uint32_t lds32(uint32_t a) { uint32_t v; asm volatile("ld.shared.b32 %0, [%1];" : "=r"(v) : "r"(a) : "memory"); return v; }
__device__ __forceinline__ uint2 lds64(uint32_t a) { uint2 v; asm volatile("ld.shared.v2.b32 {%0,%1}, [%2];" : "=r"(v.x), "=r"(v.y) : "r"(a) : "memory"); return v; }
__device__ __forceinline__ uint4 lds128(uint32_t a) { uint4 v; asm volatile("ld.shared.v4.b32 {%0,%1,%2,%3}, [%4];" : "=r"(v.x), "=r"(v.y), "=r"(v.z), "=r"(v.w) : "r"(a) : "memory"); return v; }
__device__ __forceinline__ void sts32(uint32_t a, uint32_t v) { asm volatile("st.shared.b32 [%0], %1;" ::"r"(a), "r"(v) : "memory"); }
__device__ __forceinline__ void sts64(uint32_t a, uint32_t x, uint32_t y) { asm volatile("st.shared.v2.b32 [%0], {%1,%2};" ::"r"(a), "r"(x), "r"(y) : "memory"); }
__device__ __forceinline__ void sts128(uint32_t a, uint32_t x, uint32_t y, uint32_t z, uint32_t w) { asm volatile("st.shared.v4.b32 [%0], {%1,%2,%3,%4};" ::"r"(a), "r"(x), "r"(y), "r"(z), "r"(w) : "memory"); }
__device__ __forceinline__ uint4 ld_relaxed128(const void* p) { uint4 v; asm volatile("ld.relaxed.gpu.global.v4.u32 {%0,%1,%2,%3}, [%4];" : "=r"(v.x), "=r"(v.y), "=r"(v.z), "=r"(v.w) : "l"(p) : "memory"); return v; }
__device__ __forceinline__ uint2 ld_relaxed64(const void* p) { uint2 v; asm volatile("ld.relaxed.gpu.global.v2.u32 {%0,%1}, [%2];" : "=r"(v.x), "=r"(v.y) : "l"(p) : "memory"); return v; }
__device__ __forceinline__ uint32_t ld_relaxed32(const void* p) { uint32_t v; asm volatile("ld.relaxed.gpu.global.u32 %0, [%1];" : "=r"(v) : "l"(p) : "memory"); return v; }
__device__ __forceinline__ void st_relaxed128(void* p, uint32_t x, uint32_t y, uint32_t z, uint32_t w) { asm volatile("st.relaxed.gpu.global.v4.u32 [%0], {%1,%2,%3,%4};" ::"l"(p), "r"(x), "r"(y), "r"(z), "r"(w) : "memory"); }
__device__ __forceinline__ void st_relaxed32(void* p, uint32_t x) { asm volatile("st.relaxed.gpu.global.u32 [%0], %1;" ::"l"(p), "r"(x) : "memory"); }
__device__ __forceinline__ void red_hint(unsigned* p) { asm volatile("red.relaxed.gpu.global.add.u32 [%0], 1;" ::"l"(p) : "memory"); }
__device__ __forceinline__ void publish(uint32_t* p, uint32_t x) { asm volatile("{.reg .b32 t; atom.relaxed.gpu.global.exch.b32 t, [%0], %1;}" ::"l"(p), "r"(x) : "memory"); }
__device__ __forceinline__ uint32_t ldg32(const void* p) { uint32_t v; asm volatile("ld.global.nc.L1::no_allocate.b32 %0, [%1];" : "=r"(v) : "l"(p)); return v; }
__device__ __forceinline__ uint32_t pack_bf16(float lo, float hi) { uint32_t r; asm("cvt.rn.bf16x2.f32 %0, %1, %2;" : "=r"(r) : "f"(hi), "f"(lo)); return r; }
__device__ __forceinline__ float bf_lo(uint32_t v) { return __uint_as_float(v << 16); }
__device__ __forceinline__ float bf_hi(uint32_t v) { return __uint_as_float(v & 0xFFFF0000u); }
__device__ __forceinline__ uint32_t bmul2(uint32_t a, uint32_t b) { uint32_t r; asm("mul.rn.bf16x2 %0, %1, %2;" : "=r"(r) : "r"(a), "r"(b)); return r; }
__device__ __forceinline__ uint32_t badd2(uint32_t a, uint32_t b) { uint32_t r; asm("add.rn.bf16x2 %0, %1, %2;" : "=r"(r) : "r"(a), "r"(b)); return r; }
__device__ __forceinline__ uint32_t bfma2(uint32_t a, uint32_t b, uint32_t c) { uint32_t r; asm("fma.rn.bf16x2 %0, %1, %2, %3;" : "=r"(r) : "r"(a), "r"(b), "r"(c)); return r; }
__device__ __forceinline__ uint32_t set_tag(uint32_t x, uint32_t mask, uint32_t e) { uint32_t r; asm("lop3.b32 %0, %1, %2, %3, 0xB8;" : "=r"(r) : "r"(x), "r"(mask), "r"(e)); return r; }
__device__ __forceinline__ uint32_t opaque(uint32_t x) { asm volatile("" : "+r"(x)); return x; }
__device__ __forceinline__ float rbf(float x) { return __bfloat162float(__float2bfloat16(x)); }
__device__ __forceinline__ float silu_f(float x) {
  float e, r;
  asm("ex2.approx.ftz.f32 %0, %1;" : "=f"(e) : "f"(x * -1.4426950408889634f));
  asm("rcp.approx.ftz.f32 %0, %1;" : "=f"(r) : "f"(1.f + e));
  return x * r;
}
__device__ __forceinline__ float silu2(float g, float a, float b) {
  float t;
  asm("tanh.approx.f32 %0, %1;" : "=f"(t) : "f"(g * a));
  return fmaf(g * b, t, g * b);
}
__device__ __forceinline__ void pin(int off, uint32_t x) { asm volatile("{.reg .pred p; setp.lt.s32 p, %0, 0; @p st.shared.b32 [%0], %1;}" ::"r"(off), "r"(x) : "memory"); }
__device__ __forceinline__ void pin4(int off, const uint32_t* x) { asm volatile("{.reg .pred p; setp.lt.s32 p, %0, 0; @p st.shared.v4.b32 [%0], {%1,%2,%3,%4};}" ::"r"(off), "r"(x[0]), "r"(x[1]), "r"(x[2]), "r"(x[3]) : "memory"); }
__device__ __forceinline__ void split(int x, int n) { asm volatile("{.reg .pred p; setp.eq.s32 p, %0, %1; @p trap;}" ::"r"(x), "r"(~n) : "memory"); }
__device__ __forceinline__ void ln_final(float s, float q, float& m, float& sd) {
  m = s * (1.f / D_);
  asm("sqrt.approx.f32 %0, %1;" : "=f"(sd) : "f"(rbf(rbf(fmaxf(fmaf(-m, m, q * (1.f / D_)), 0.f)) + 1e-5f)));
  sd = rbf(sd);
}
__device__ __forceinline__ float rcpf(float x) { float r; asm("rcp.approx.f32 %0, %1;" : "=f"(r) : "f"(x)); return r; }

__device__ __forceinline__ void wg_rs16_0(float* d, const uint32_t* a, uint64_t db, int sc) {
  asm volatile("{.reg .pred p; setp.ne.b32 p, %13, 0; wgmma.mma_async.sync.aligned.m64n16k16.f32.bf16.bf16 {%0,%1,%2,%3,%4,%5,%6,%7}, {%8,%9,%10,%11}, %12, p, 1, 1, 0;}"
    : "+f"(d[0]),"+f"(d[1]),"+f"(d[2]),"+f"(d[3]),"+f"(d[4]),"+f"(d[5]),"+f"(d[6]),"+f"(d[7]) : "r"(a[0]),"r"(a[1]),"r"(a[2]),"r"(a[3]),"l"(db),"r"(sc));
}
__device__ __forceinline__ void wg_rs32_0(float* d, const uint32_t* a, uint64_t db, int sc) {
  asm volatile("{.reg .pred p; setp.ne.b32 p, %21, 0; wgmma.mma_async.sync.aligned.m64n32k16.f32.bf16.bf16 {%0,%1,%2,%3,%4,%5,%6,%7,%8,%9,%10,%11,%12,%13,%14,%15}, {%16,%17,%18,%19}, %20, p, 1, 1, 0;}"
    : "+f"(d[0]),"+f"(d[1]),"+f"(d[2]),"+f"(d[3]),"+f"(d[4]),"+f"(d[5]),"+f"(d[6]),"+f"(d[7]),"+f"(d[8]),"+f"(d[9]),"+f"(d[10]),"+f"(d[11]),"+f"(d[12]),"+f"(d[13]),"+f"(d[14]),"+f"(d[15]) : "r"(a[0]),"r"(a[1]),"r"(a[2]),"r"(a[3]),"l"(db),"r"(sc));
}
__device__ __forceinline__ void wg_rs48_0(float* d, const uint32_t* a, uint64_t db, int sc) {
  asm volatile("{.reg .pred p; setp.ne.b32 p, %29, 0; wgmma.mma_async.sync.aligned.m64n48k16.f32.bf16.bf16 {%0,%1,%2,%3,%4,%5,%6,%7,%8,%9,%10,%11,%12,%13,%14,%15,%16,%17,%18,%19,%20,%21,%22,%23}, {%24,%25,%26,%27}, %28, p, 1, 1, 0;}"
    : "+f"(d[0]),"+f"(d[1]),"+f"(d[2]),"+f"(d[3]),"+f"(d[4]),"+f"(d[5]),"+f"(d[6]),"+f"(d[7]),"+f"(d[8]),"+f"(d[9]),"+f"(d[10]),"+f"(d[11]),"+f"(d[12]),"+f"(d[13]),"+f"(d[14]),"+f"(d[15]),"+f"(d[16]),"+f"(d[17]),"+f"(d[18]),"+f"(d[19]),"+f"(d[20]),"+f"(d[21]),"+f"(d[22]),"+f"(d[23]) : "r"(a[0]),"r"(a[1]),"r"(a[2]),"r"(a[3]),"l"(db),"r"(sc));
}
__device__ __forceinline__ void wg_rs64_0(float* d, const uint32_t* a, uint64_t db, int sc) {
  asm volatile("{.reg .pred p; setp.ne.b32 p, %37, 0; wgmma.mma_async.sync.aligned.m64n64k16.f32.bf16.bf16 {%0,%1,%2,%3,%4,%5,%6,%7,%8,%9,%10,%11,%12,%13,%14,%15,%16,%17,%18,%19,%20,%21,%22,%23,%24,%25,%26,%27,%28,%29,%30,%31}, {%32,%33,%34,%35}, %36, p, 1, 1, 0;}"
    : "+f"(d[0]),"+f"(d[1]),"+f"(d[2]),"+f"(d[3]),"+f"(d[4]),"+f"(d[5]),"+f"(d[6]),"+f"(d[7]),"+f"(d[8]),"+f"(d[9]),"+f"(d[10]),"+f"(d[11]),"+f"(d[12]),"+f"(d[13]),"+f"(d[14]),"+f"(d[15]),"+f"(d[16]),"+f"(d[17]),"+f"(d[18]),"+f"(d[19]),"+f"(d[20]),"+f"(d[21]),"+f"(d[22]),"+f"(d[23]),"+f"(d[24]),"+f"(d[25]),"+f"(d[26]),"+f"(d[27]),"+f"(d[28]),"+f"(d[29]),"+f"(d[30]),"+f"(d[31]) : "r"(a[0]),"r"(a[1]),"r"(a[2]),"r"(a[3]),"l"(db),"r"(sc));
}
__device__ __forceinline__ void wg_rs80_0(float* d, const uint32_t* a, uint64_t db, int sc) {
  asm volatile("{.reg .pred p; setp.ne.b32 p, %45, 0; wgmma.mma_async.sync.aligned.m64n80k16.f32.bf16.bf16 {%0,%1,%2,%3,%4,%5,%6,%7,%8,%9,%10,%11,%12,%13,%14,%15,%16,%17,%18,%19,%20,%21,%22,%23,%24,%25,%26,%27,%28,%29,%30,%31,%32,%33,%34,%35,%36,%37,%38,%39}, {%40,%41,%42,%43}, %44, p, 1, 1, 0;}"
    : "+f"(d[0]),"+f"(d[1]),"+f"(d[2]),"+f"(d[3]),"+f"(d[4]),"+f"(d[5]),"+f"(d[6]),"+f"(d[7]),"+f"(d[8]),"+f"(d[9]),"+f"(d[10]),"+f"(d[11]),"+f"(d[12]),"+f"(d[13]),"+f"(d[14]),"+f"(d[15]),"+f"(d[16]),"+f"(d[17]),"+f"(d[18]),"+f"(d[19]),"+f"(d[20]),"+f"(d[21]),"+f"(d[22]),"+f"(d[23]),"+f"(d[24]),"+f"(d[25]),"+f"(d[26]),"+f"(d[27]),"+f"(d[28]),"+f"(d[29]),"+f"(d[30]),"+f"(d[31]),"+f"(d[32]),"+f"(d[33]),"+f"(d[34]),"+f"(d[35]),"+f"(d[36]),"+f"(d[37]),"+f"(d[38]),"+f"(d[39]) : "r"(a[0]),"r"(a[1]),"r"(a[2]),"r"(a[3]),"l"(db),"r"(sc));
}
__device__ __forceinline__ void wg_rs96_0(float* d, const uint32_t* a, uint64_t db, int sc) {
  asm volatile("{.reg .pred p; setp.ne.b32 p, %53, 0; wgmma.mma_async.sync.aligned.m64n96k16.f32.bf16.bf16 {%0,%1,%2,%3,%4,%5,%6,%7,%8,%9,%10,%11,%12,%13,%14,%15,%16,%17,%18,%19,%20,%21,%22,%23,%24,%25,%26,%27,%28,%29,%30,%31,%32,%33,%34,%35,%36,%37,%38,%39,%40,%41,%42,%43,%44,%45,%46,%47}, {%48,%49,%50,%51}, %52, p, 1, 1, 0;}"
    : "+f"(d[0]),"+f"(d[1]),"+f"(d[2]),"+f"(d[3]),"+f"(d[4]),"+f"(d[5]),"+f"(d[6]),"+f"(d[7]),"+f"(d[8]),"+f"(d[9]),"+f"(d[10]),"+f"(d[11]),"+f"(d[12]),"+f"(d[13]),"+f"(d[14]),"+f"(d[15]),"+f"(d[16]),"+f"(d[17]),"+f"(d[18]),"+f"(d[19]),"+f"(d[20]),"+f"(d[21]),"+f"(d[22]),"+f"(d[23]),"+f"(d[24]),"+f"(d[25]),"+f"(d[26]),"+f"(d[27]),"+f"(d[28]),"+f"(d[29]),"+f"(d[30]),"+f"(d[31]),"+f"(d[32]),"+f"(d[33]),"+f"(d[34]),"+f"(d[35]),"+f"(d[36]),"+f"(d[37]),"+f"(d[38]),"+f"(d[39]),"+f"(d[40]),"+f"(d[41]),"+f"(d[42]),"+f"(d[43]),"+f"(d[44]),"+f"(d[45]),"+f"(d[46]),"+f"(d[47]) : "r"(a[0]),"r"(a[1]),"r"(a[2]),"r"(a[3]),"l"(db),"r"(sc));
}
__device__ __forceinline__ void wg_rs112_0(float* d, const uint32_t* a, uint64_t db, int sc) {
  asm volatile("{.reg .pred p; setp.ne.b32 p, %61, 0; wgmma.mma_async.sync.aligned.m64n112k16.f32.bf16.bf16 {%0,%1,%2,%3,%4,%5,%6,%7,%8,%9,%10,%11,%12,%13,%14,%15,%16,%17,%18,%19,%20,%21,%22,%23,%24,%25,%26,%27,%28,%29,%30,%31,%32,%33,%34,%35,%36,%37,%38,%39,%40,%41,%42,%43,%44,%45,%46,%47,%48,%49,%50,%51,%52,%53,%54,%55}, {%56,%57,%58,%59}, %60, p, 1, 1, 0;}"
    : "+f"(d[0]),"+f"(d[1]),"+f"(d[2]),"+f"(d[3]),"+f"(d[4]),"+f"(d[5]),"+f"(d[6]),"+f"(d[7]),"+f"(d[8]),"+f"(d[9]),"+f"(d[10]),"+f"(d[11]),"+f"(d[12]),"+f"(d[13]),"+f"(d[14]),"+f"(d[15]),"+f"(d[16]),"+f"(d[17]),"+f"(d[18]),"+f"(d[19]),"+f"(d[20]),"+f"(d[21]),"+f"(d[22]),"+f"(d[23]),"+f"(d[24]),"+f"(d[25]),"+f"(d[26]),"+f"(d[27]),"+f"(d[28]),"+f"(d[29]),"+f"(d[30]),"+f"(d[31]),"+f"(d[32]),"+f"(d[33]),"+f"(d[34]),"+f"(d[35]),"+f"(d[36]),"+f"(d[37]),"+f"(d[38]),"+f"(d[39]),"+f"(d[40]),"+f"(d[41]),"+f"(d[42]),"+f"(d[43]),"+f"(d[44]),"+f"(d[45]),"+f"(d[46]),"+f"(d[47]),"+f"(d[48]),"+f"(d[49]),"+f"(d[50]),"+f"(d[51]),"+f"(d[52]),"+f"(d[53]),"+f"(d[54]),"+f"(d[55]) : "r"(a[0]),"r"(a[1]),"r"(a[2]),"r"(a[3]),"l"(db),"r"(sc));
}
__device__ __forceinline__ void wg_rs128_0(float* d, const uint32_t* a, uint64_t db, int sc) {
  asm volatile("{.reg .pred p; setp.ne.b32 p, %69, 0; wgmma.mma_async.sync.aligned.m64n128k16.f32.bf16.bf16 {%0,%1,%2,%3,%4,%5,%6,%7,%8,%9,%10,%11,%12,%13,%14,%15,%16,%17,%18,%19,%20,%21,%22,%23,%24,%25,%26,%27,%28,%29,%30,%31,%32,%33,%34,%35,%36,%37,%38,%39,%40,%41,%42,%43,%44,%45,%46,%47,%48,%49,%50,%51,%52,%53,%54,%55,%56,%57,%58,%59,%60,%61,%62,%63}, {%64,%65,%66,%67}, %68, p, 1, 1, 0;}"
    : "+f"(d[0]),"+f"(d[1]),"+f"(d[2]),"+f"(d[3]),"+f"(d[4]),"+f"(d[5]),"+f"(d[6]),"+f"(d[7]),"+f"(d[8]),"+f"(d[9]),"+f"(d[10]),"+f"(d[11]),"+f"(d[12]),"+f"(d[13]),"+f"(d[14]),"+f"(d[15]),"+f"(d[16]),"+f"(d[17]),"+f"(d[18]),"+f"(d[19]),"+f"(d[20]),"+f"(d[21]),"+f"(d[22]),"+f"(d[23]),"+f"(d[24]),"+f"(d[25]),"+f"(d[26]),"+f"(d[27]),"+f"(d[28]),"+f"(d[29]),"+f"(d[30]),"+f"(d[31]),"+f"(d[32]),"+f"(d[33]),"+f"(d[34]),"+f"(d[35]),"+f"(d[36]),"+f"(d[37]),"+f"(d[38]),"+f"(d[39]),"+f"(d[40]),"+f"(d[41]),"+f"(d[42]),"+f"(d[43]),"+f"(d[44]),"+f"(d[45]),"+f"(d[46]),"+f"(d[47]),"+f"(d[48]),"+f"(d[49]),"+f"(d[50]),"+f"(d[51]),"+f"(d[52]),"+f"(d[53]),"+f"(d[54]),"+f"(d[55]),"+f"(d[56]),"+f"(d[57]),"+f"(d[58]),"+f"(d[59]),"+f"(d[60]),"+f"(d[61]),"+f"(d[62]),"+f"(d[63]) : "r"(a[0]),"r"(a[1]),"r"(a[2]),"r"(a[3]),"l"(db),"r"(sc));
}
__device__ __forceinline__ void wg_rs144_0(float* d, const uint32_t* a, uint64_t db, int sc) {
  asm volatile("{.reg .pred p; setp.ne.b32 p, %77, 0; wgmma.mma_async.sync.aligned.m64n144k16.f32.bf16.bf16 {%0,%1,%2,%3,%4,%5,%6,%7,%8,%9,%10,%11,%12,%13,%14,%15,%16,%17,%18,%19,%20,%21,%22,%23,%24,%25,%26,%27,%28,%29,%30,%31,%32,%33,%34,%35,%36,%37,%38,%39,%40,%41,%42,%43,%44,%45,%46,%47,%48,%49,%50,%51,%52,%53,%54,%55,%56,%57,%58,%59,%60,%61,%62,%63,%64,%65,%66,%67,%68,%69,%70,%71}, {%72,%73,%74,%75}, %76, p, 1, 1, 0;}"
    : "+f"(d[0]),"+f"(d[1]),"+f"(d[2]),"+f"(d[3]),"+f"(d[4]),"+f"(d[5]),"+f"(d[6]),"+f"(d[7]),"+f"(d[8]),"+f"(d[9]),"+f"(d[10]),"+f"(d[11]),"+f"(d[12]),"+f"(d[13]),"+f"(d[14]),"+f"(d[15]),"+f"(d[16]),"+f"(d[17]),"+f"(d[18]),"+f"(d[19]),"+f"(d[20]),"+f"(d[21]),"+f"(d[22]),"+f"(d[23]),"+f"(d[24]),"+f"(d[25]),"+f"(d[26]),"+f"(d[27]),"+f"(d[28]),"+f"(d[29]),"+f"(d[30]),"+f"(d[31]),"+f"(d[32]),"+f"(d[33]),"+f"(d[34]),"+f"(d[35]),"+f"(d[36]),"+f"(d[37]),"+f"(d[38]),"+f"(d[39]),"+f"(d[40]),"+f"(d[41]),"+f"(d[42]),"+f"(d[43]),"+f"(d[44]),"+f"(d[45]),"+f"(d[46]),"+f"(d[47]),"+f"(d[48]),"+f"(d[49]),"+f"(d[50]),"+f"(d[51]),"+f"(d[52]),"+f"(d[53]),"+f"(d[54]),"+f"(d[55]),"+f"(d[56]),"+f"(d[57]),"+f"(d[58]),"+f"(d[59]),"+f"(d[60]),"+f"(d[61]),"+f"(d[62]),"+f"(d[63]),"+f"(d[64]),"+f"(d[65]),"+f"(d[66]),"+f"(d[67]),"+f"(d[68]),"+f"(d[69]),"+f"(d[70]),"+f"(d[71]) : "r"(a[0]),"r"(a[1]),"r"(a[2]),"r"(a[3]),"l"(db),"r"(sc));
}
__device__ __forceinline__ void wg_rs160_0(float* d, const uint32_t* a, uint64_t db, int sc) {
  asm volatile("{.reg .pred p; setp.ne.b32 p, %85, 0; wgmma.mma_async.sync.aligned.m64n160k16.f32.bf16.bf16 {%0,%1,%2,%3,%4,%5,%6,%7,%8,%9,%10,%11,%12,%13,%14,%15,%16,%17,%18,%19,%20,%21,%22,%23,%24,%25,%26,%27,%28,%29,%30,%31,%32,%33,%34,%35,%36,%37,%38,%39,%40,%41,%42,%43,%44,%45,%46,%47,%48,%49,%50,%51,%52,%53,%54,%55,%56,%57,%58,%59,%60,%61,%62,%63,%64,%65,%66,%67,%68,%69,%70,%71,%72,%73,%74,%75,%76,%77,%78,%79}, {%80,%81,%82,%83}, %84, p, 1, 1, 0;}"
    : "+f"(d[0]),"+f"(d[1]),"+f"(d[2]),"+f"(d[3]),"+f"(d[4]),"+f"(d[5]),"+f"(d[6]),"+f"(d[7]),"+f"(d[8]),"+f"(d[9]),"+f"(d[10]),"+f"(d[11]),"+f"(d[12]),"+f"(d[13]),"+f"(d[14]),"+f"(d[15]),"+f"(d[16]),"+f"(d[17]),"+f"(d[18]),"+f"(d[19]),"+f"(d[20]),"+f"(d[21]),"+f"(d[22]),"+f"(d[23]),"+f"(d[24]),"+f"(d[25]),"+f"(d[26]),"+f"(d[27]),"+f"(d[28]),"+f"(d[29]),"+f"(d[30]),"+f"(d[31]),"+f"(d[32]),"+f"(d[33]),"+f"(d[34]),"+f"(d[35]),"+f"(d[36]),"+f"(d[37]),"+f"(d[38]),"+f"(d[39]),"+f"(d[40]),"+f"(d[41]),"+f"(d[42]),"+f"(d[43]),"+f"(d[44]),"+f"(d[45]),"+f"(d[46]),"+f"(d[47]),"+f"(d[48]),"+f"(d[49]),"+f"(d[50]),"+f"(d[51]),"+f"(d[52]),"+f"(d[53]),"+f"(d[54]),"+f"(d[55]),"+f"(d[56]),"+f"(d[57]),"+f"(d[58]),"+f"(d[59]),"+f"(d[60]),"+f"(d[61]),"+f"(d[62]),"+f"(d[63]),"+f"(d[64]),"+f"(d[65]),"+f"(d[66]),"+f"(d[67]),"+f"(d[68]),"+f"(d[69]),"+f"(d[70]),"+f"(d[71]),"+f"(d[72]),"+f"(d[73]),"+f"(d[74]),"+f"(d[75]),"+f"(d[76]),"+f"(d[77]),"+f"(d[78]),"+f"(d[79]) : "r"(a[0]),"r"(a[1]),"r"(a[2]),"r"(a[3]),"l"(db),"r"(sc));
}
__device__ __forceinline__ void wg_rs176_0(float* d, const uint32_t* a, uint64_t db, int sc) {
  asm volatile("{.reg .pred p; setp.ne.b32 p, %93, 0; wgmma.mma_async.sync.aligned.m64n176k16.f32.bf16.bf16 {%0,%1,%2,%3,%4,%5,%6,%7,%8,%9,%10,%11,%12,%13,%14,%15,%16,%17,%18,%19,%20,%21,%22,%23,%24,%25,%26,%27,%28,%29,%30,%31,%32,%33,%34,%35,%36,%37,%38,%39,%40,%41,%42,%43,%44,%45,%46,%47,%48,%49,%50,%51,%52,%53,%54,%55,%56,%57,%58,%59,%60,%61,%62,%63,%64,%65,%66,%67,%68,%69,%70,%71,%72,%73,%74,%75,%76,%77,%78,%79,%80,%81,%82,%83,%84,%85,%86,%87}, {%88,%89,%90,%91}, %92, p, 1, 1, 0;}"
    : "+f"(d[0]),"+f"(d[1]),"+f"(d[2]),"+f"(d[3]),"+f"(d[4]),"+f"(d[5]),"+f"(d[6]),"+f"(d[7]),"+f"(d[8]),"+f"(d[9]),"+f"(d[10]),"+f"(d[11]),"+f"(d[12]),"+f"(d[13]),"+f"(d[14]),"+f"(d[15]),"+f"(d[16]),"+f"(d[17]),"+f"(d[18]),"+f"(d[19]),"+f"(d[20]),"+f"(d[21]),"+f"(d[22]),"+f"(d[23]),"+f"(d[24]),"+f"(d[25]),"+f"(d[26]),"+f"(d[27]),"+f"(d[28]),"+f"(d[29]),"+f"(d[30]),"+f"(d[31]),"+f"(d[32]),"+f"(d[33]),"+f"(d[34]),"+f"(d[35]),"+f"(d[36]),"+f"(d[37]),"+f"(d[38]),"+f"(d[39]),"+f"(d[40]),"+f"(d[41]),"+f"(d[42]),"+f"(d[43]),"+f"(d[44]),"+f"(d[45]),"+f"(d[46]),"+f"(d[47]),"+f"(d[48]),"+f"(d[49]),"+f"(d[50]),"+f"(d[51]),"+f"(d[52]),"+f"(d[53]),"+f"(d[54]),"+f"(d[55]),"+f"(d[56]),"+f"(d[57]),"+f"(d[58]),"+f"(d[59]),"+f"(d[60]),"+f"(d[61]),"+f"(d[62]),"+f"(d[63]),"+f"(d[64]),"+f"(d[65]),"+f"(d[66]),"+f"(d[67]),"+f"(d[68]),"+f"(d[69]),"+f"(d[70]),"+f"(d[71]),"+f"(d[72]),"+f"(d[73]),"+f"(d[74]),"+f"(d[75]),"+f"(d[76]),"+f"(d[77]),"+f"(d[78]),"+f"(d[79]),"+f"(d[80]),"+f"(d[81]),"+f"(d[82]),"+f"(d[83]),"+f"(d[84]),"+f"(d[85]),"+f"(d[86]),"+f"(d[87]) : "r"(a[0]),"r"(a[1]),"r"(a[2]),"r"(a[3]),"l"(db),"r"(sc));
}
__device__ __forceinline__ void wg_rs192_0(float* d, const uint32_t* a, uint64_t db, int sc) {
  asm volatile("{.reg .pred p; setp.ne.b32 p, %101, 0; wgmma.mma_async.sync.aligned.m64n192k16.f32.bf16.bf16 {%0,%1,%2,%3,%4,%5,%6,%7,%8,%9,%10,%11,%12,%13,%14,%15,%16,%17,%18,%19,%20,%21,%22,%23,%24,%25,%26,%27,%28,%29,%30,%31,%32,%33,%34,%35,%36,%37,%38,%39,%40,%41,%42,%43,%44,%45,%46,%47,%48,%49,%50,%51,%52,%53,%54,%55,%56,%57,%58,%59,%60,%61,%62,%63,%64,%65,%66,%67,%68,%69,%70,%71,%72,%73,%74,%75,%76,%77,%78,%79,%80,%81,%82,%83,%84,%85,%86,%87,%88,%89,%90,%91,%92,%93,%94,%95}, {%96,%97,%98,%99}, %100, p, 1, 1, 0;}"
    : "+f"(d[0]),"+f"(d[1]),"+f"(d[2]),"+f"(d[3]),"+f"(d[4]),"+f"(d[5]),"+f"(d[6]),"+f"(d[7]),"+f"(d[8]),"+f"(d[9]),"+f"(d[10]),"+f"(d[11]),"+f"(d[12]),"+f"(d[13]),"+f"(d[14]),"+f"(d[15]),"+f"(d[16]),"+f"(d[17]),"+f"(d[18]),"+f"(d[19]),"+f"(d[20]),"+f"(d[21]),"+f"(d[22]),"+f"(d[23]),"+f"(d[24]),"+f"(d[25]),"+f"(d[26]),"+f"(d[27]),"+f"(d[28]),"+f"(d[29]),"+f"(d[30]),"+f"(d[31]),"+f"(d[32]),"+f"(d[33]),"+f"(d[34]),"+f"(d[35]),"+f"(d[36]),"+f"(d[37]),"+f"(d[38]),"+f"(d[39]),"+f"(d[40]),"+f"(d[41]),"+f"(d[42]),"+f"(d[43]),"+f"(d[44]),"+f"(d[45]),"+f"(d[46]),"+f"(d[47]),"+f"(d[48]),"+f"(d[49]),"+f"(d[50]),"+f"(d[51]),"+f"(d[52]),"+f"(d[53]),"+f"(d[54]),"+f"(d[55]),"+f"(d[56]),"+f"(d[57]),"+f"(d[58]),"+f"(d[59]),"+f"(d[60]),"+f"(d[61]),"+f"(d[62]),"+f"(d[63]),"+f"(d[64]),"+f"(d[65]),"+f"(d[66]),"+f"(d[67]),"+f"(d[68]),"+f"(d[69]),"+f"(d[70]),"+f"(d[71]),"+f"(d[72]),"+f"(d[73]),"+f"(d[74]),"+f"(d[75]),"+f"(d[76]),"+f"(d[77]),"+f"(d[78]),"+f"(d[79]),"+f"(d[80]),"+f"(d[81]),"+f"(d[82]),"+f"(d[83]),"+f"(d[84]),"+f"(d[85]),"+f"(d[86]),"+f"(d[87]),"+f"(d[88]),"+f"(d[89]),"+f"(d[90]),"+f"(d[91]),"+f"(d[92]),"+f"(d[93]),"+f"(d[94]),"+f"(d[95]) : "r"(a[0]),"r"(a[1]),"r"(a[2]),"r"(a[3]),"l"(db),"r"(sc));
}
__device__ __forceinline__ void wg_ss192_11(float* d, uint64_t da, uint64_t db, int sc) {
  asm volatile("{.reg .pred p; setp.ne.b32 p, %98, 0; wgmma.mma_async.sync.aligned.m64n192k16.f32.bf16.bf16 {%0,%1,%2,%3,%4,%5,%6,%7,%8,%9,%10,%11,%12,%13,%14,%15,%16,%17,%18,%19,%20,%21,%22,%23,%24,%25,%26,%27,%28,%29,%30,%31,%32,%33,%34,%35,%36,%37,%38,%39,%40,%41,%42,%43,%44,%45,%46,%47,%48,%49,%50,%51,%52,%53,%54,%55,%56,%57,%58,%59,%60,%61,%62,%63,%64,%65,%66,%67,%68,%69,%70,%71,%72,%73,%74,%75,%76,%77,%78,%79,%80,%81,%82,%83,%84,%85,%86,%87,%88,%89,%90,%91,%92,%93,%94,%95}, %96, %97, p, 1, 1, 1, 1;}"
    : "+f"(d[0]),"+f"(d[1]),"+f"(d[2]),"+f"(d[3]),"+f"(d[4]),"+f"(d[5]),"+f"(d[6]),"+f"(d[7]),"+f"(d[8]),"+f"(d[9]),"+f"(d[10]),"+f"(d[11]),"+f"(d[12]),"+f"(d[13]),"+f"(d[14]),"+f"(d[15]),"+f"(d[16]),"+f"(d[17]),"+f"(d[18]),"+f"(d[19]),"+f"(d[20]),"+f"(d[21]),"+f"(d[22]),"+f"(d[23]),"+f"(d[24]),"+f"(d[25]),"+f"(d[26]),"+f"(d[27]),"+f"(d[28]),"+f"(d[29]),"+f"(d[30]),"+f"(d[31]),"+f"(d[32]),"+f"(d[33]),"+f"(d[34]),"+f"(d[35]),"+f"(d[36]),"+f"(d[37]),"+f"(d[38]),"+f"(d[39]),"+f"(d[40]),"+f"(d[41]),"+f"(d[42]),"+f"(d[43]),"+f"(d[44]),"+f"(d[45]),"+f"(d[46]),"+f"(d[47]),"+f"(d[48]),"+f"(d[49]),"+f"(d[50]),"+f"(d[51]),"+f"(d[52]),"+f"(d[53]),"+f"(d[54]),"+f"(d[55]),"+f"(d[56]),"+f"(d[57]),"+f"(d[58]),"+f"(d[59]),"+f"(d[60]),"+f"(d[61]),"+f"(d[62]),"+f"(d[63]),"+f"(d[64]),"+f"(d[65]),"+f"(d[66]),"+f"(d[67]),"+f"(d[68]),"+f"(d[69]),"+f"(d[70]),"+f"(d[71]),"+f"(d[72]),"+f"(d[73]),"+f"(d[74]),"+f"(d[75]),"+f"(d[76]),"+f"(d[77]),"+f"(d[78]),"+f"(d[79]),"+f"(d[80]),"+f"(d[81]),"+f"(d[82]),"+f"(d[83]),"+f"(d[84]),"+f"(d[85]),"+f"(d[86]),"+f"(d[87]),"+f"(d[88]),"+f"(d[89]),"+f"(d[90]),"+f"(d[91]),"+f"(d[92]),"+f"(d[93]),"+f"(d[94]),"+f"(d[95]) : "l"(da),"l"(db),"r"(sc));
}
__device__ __forceinline__ void wg_ss192_01(float* d, uint64_t da, uint64_t db, int sc) {
  asm volatile("{.reg .pred p; setp.ne.b32 p, %98, 0; wgmma.mma_async.sync.aligned.m64n192k16.f32.bf16.bf16 {%0,%1,%2,%3,%4,%5,%6,%7,%8,%9,%10,%11,%12,%13,%14,%15,%16,%17,%18,%19,%20,%21,%22,%23,%24,%25,%26,%27,%28,%29,%30,%31,%32,%33,%34,%35,%36,%37,%38,%39,%40,%41,%42,%43,%44,%45,%46,%47,%48,%49,%50,%51,%52,%53,%54,%55,%56,%57,%58,%59,%60,%61,%62,%63,%64,%65,%66,%67,%68,%69,%70,%71,%72,%73,%74,%75,%76,%77,%78,%79,%80,%81,%82,%83,%84,%85,%86,%87,%88,%89,%90,%91,%92,%93,%94,%95}, %96, %97, p, 1, 1, 0, 1;}"
    : "+f"(d[0]),"+f"(d[1]),"+f"(d[2]),"+f"(d[3]),"+f"(d[4]),"+f"(d[5]),"+f"(d[6]),"+f"(d[7]),"+f"(d[8]),"+f"(d[9]),"+f"(d[10]),"+f"(d[11]),"+f"(d[12]),"+f"(d[13]),"+f"(d[14]),"+f"(d[15]),"+f"(d[16]),"+f"(d[17]),"+f"(d[18]),"+f"(d[19]),"+f"(d[20]),"+f"(d[21]),"+f"(d[22]),"+f"(d[23]),"+f"(d[24]),"+f"(d[25]),"+f"(d[26]),"+f"(d[27]),"+f"(d[28]),"+f"(d[29]),"+f"(d[30]),"+f"(d[31]),"+f"(d[32]),"+f"(d[33]),"+f"(d[34]),"+f"(d[35]),"+f"(d[36]),"+f"(d[37]),"+f"(d[38]),"+f"(d[39]),"+f"(d[40]),"+f"(d[41]),"+f"(d[42]),"+f"(d[43]),"+f"(d[44]),"+f"(d[45]),"+f"(d[46]),"+f"(d[47]),"+f"(d[48]),"+f"(d[49]),"+f"(d[50]),"+f"(d[51]),"+f"(d[52]),"+f"(d[53]),"+f"(d[54]),"+f"(d[55]),"+f"(d[56]),"+f"(d[57]),"+f"(d[58]),"+f"(d[59]),"+f"(d[60]),"+f"(d[61]),"+f"(d[62]),"+f"(d[63]),"+f"(d[64]),"+f"(d[65]),"+f"(d[66]),"+f"(d[67]),"+f"(d[68]),"+f"(d[69]),"+f"(d[70]),"+f"(d[71]),"+f"(d[72]),"+f"(d[73]),"+f"(d[74]),"+f"(d[75]),"+f"(d[76]),"+f"(d[77]),"+f"(d[78]),"+f"(d[79]),"+f"(d[80]),"+f"(d[81]),"+f"(d[82]),"+f"(d[83]),"+f"(d[84]),"+f"(d[85]),"+f"(d[86]),"+f"(d[87]),"+f"(d[88]),"+f"(d[89]),"+f"(d[90]),"+f"(d[91]),"+f"(d[92]),"+f"(d[93]),"+f"(d[94]),"+f"(d[95]) : "l"(da),"l"(db),"r"(sc));
}
__device__ __forceinline__ void wg_ss64_11(float* d, uint64_t da, uint64_t db, int sc) {
  asm volatile("{.reg .pred p; setp.ne.b32 p, %34, 0; wgmma.mma_async.sync.aligned.m64n64k16.f32.bf16.bf16 {%0,%1,%2,%3,%4,%5,%6,%7,%8,%9,%10,%11,%12,%13,%14,%15,%16,%17,%18,%19,%20,%21,%22,%23,%24,%25,%26,%27,%28,%29,%30,%31}, %32, %33, p, 1, 1, 1, 1;}"
    : "+f"(d[0]),"+f"(d[1]),"+f"(d[2]),"+f"(d[3]),"+f"(d[4]),"+f"(d[5]),"+f"(d[6]),"+f"(d[7]),"+f"(d[8]),"+f"(d[9]),"+f"(d[10]),"+f"(d[11]),"+f"(d[12]),"+f"(d[13]),"+f"(d[14]),"+f"(d[15]),"+f"(d[16]),"+f"(d[17]),"+f"(d[18]),"+f"(d[19]),"+f"(d[20]),"+f"(d[21]),"+f"(d[22]),"+f"(d[23]),"+f"(d[24]),"+f"(d[25]),"+f"(d[26]),"+f"(d[27]),"+f"(d[28]),"+f"(d[29]),"+f"(d[30]),"+f"(d[31]) : "l"(da),"l"(db),"r"(sc));
}
__device__ __forceinline__ void wg_ss64_01(float* d, uint64_t da, uint64_t db, int sc) {
  asm volatile("{.reg .pred p; setp.ne.b32 p, %34, 0; wgmma.mma_async.sync.aligned.m64n64k16.f32.bf16.bf16 {%0,%1,%2,%3,%4,%5,%6,%7,%8,%9,%10,%11,%12,%13,%14,%15,%16,%17,%18,%19,%20,%21,%22,%23,%24,%25,%26,%27,%28,%29,%30,%31}, %32, %33, p, 1, 1, 0, 1;}"
    : "+f"(d[0]),"+f"(d[1]),"+f"(d[2]),"+f"(d[3]),"+f"(d[4]),"+f"(d[5]),"+f"(d[6]),"+f"(d[7]),"+f"(d[8]),"+f"(d[9]),"+f"(d[10]),"+f"(d[11]),"+f"(d[12]),"+f"(d[13]),"+f"(d[14]),"+f"(d[15]),"+f"(d[16]),"+f"(d[17]),"+f"(d[18]),"+f"(d[19]),"+f"(d[20]),"+f"(d[21]),"+f"(d[22]),"+f"(d[23]),"+f"(d[24]),"+f"(d[25]),"+f"(d[26]),"+f"(d[27]),"+f"(d[28]),"+f"(d[29]),"+f"(d[30]),"+f"(d[31]) : "l"(da),"l"(db),"r"(sc));
}
__device__ __forceinline__ void wg_ss128_11(float* d, uint64_t da, uint64_t db, int sc) {
  asm volatile("{.reg .pred p; setp.ne.b32 p, %66, 0; wgmma.mma_async.sync.aligned.m64n128k16.f32.bf16.bf16 {%0,%1,%2,%3,%4,%5,%6,%7,%8,%9,%10,%11,%12,%13,%14,%15,%16,%17,%18,%19,%20,%21,%22,%23,%24,%25,%26,%27,%28,%29,%30,%31,%32,%33,%34,%35,%36,%37,%38,%39,%40,%41,%42,%43,%44,%45,%46,%47,%48,%49,%50,%51,%52,%53,%54,%55,%56,%57,%58,%59,%60,%61,%62,%63}, %64, %65, p, 1, 1, 1, 1;}"
    : "+f"(d[0]),"+f"(d[1]),"+f"(d[2]),"+f"(d[3]),"+f"(d[4]),"+f"(d[5]),"+f"(d[6]),"+f"(d[7]),"+f"(d[8]),"+f"(d[9]),"+f"(d[10]),"+f"(d[11]),"+f"(d[12]),"+f"(d[13]),"+f"(d[14]),"+f"(d[15]),"+f"(d[16]),"+f"(d[17]),"+f"(d[18]),"+f"(d[19]),"+f"(d[20]),"+f"(d[21]),"+f"(d[22]),"+f"(d[23]),"+f"(d[24]),"+f"(d[25]),"+f"(d[26]),"+f"(d[27]),"+f"(d[28]),"+f"(d[29]),"+f"(d[30]),"+f"(d[31]),"+f"(d[32]),"+f"(d[33]),"+f"(d[34]),"+f"(d[35]),"+f"(d[36]),"+f"(d[37]),"+f"(d[38]),"+f"(d[39]),"+f"(d[40]),"+f"(d[41]),"+f"(d[42]),"+f"(d[43]),"+f"(d[44]),"+f"(d[45]),"+f"(d[46]),"+f"(d[47]),"+f"(d[48]),"+f"(d[49]),"+f"(d[50]),"+f"(d[51]),"+f"(d[52]),"+f"(d[53]),"+f"(d[54]),"+f"(d[55]),"+f"(d[56]),"+f"(d[57]),"+f"(d[58]),"+f"(d[59]),"+f"(d[60]),"+f"(d[61]),"+f"(d[62]),"+f"(d[63]) : "l"(da),"l"(db),"r"(sc));
}
__device__ __forceinline__ void wg_ss128_01(float* d, uint64_t da, uint64_t db, int sc) {
  asm volatile("{.reg .pred p; setp.ne.b32 p, %66, 0; wgmma.mma_async.sync.aligned.m64n128k16.f32.bf16.bf16 {%0,%1,%2,%3,%4,%5,%6,%7,%8,%9,%10,%11,%12,%13,%14,%15,%16,%17,%18,%19,%20,%21,%22,%23,%24,%25,%26,%27,%28,%29,%30,%31,%32,%33,%34,%35,%36,%37,%38,%39,%40,%41,%42,%43,%44,%45,%46,%47,%48,%49,%50,%51,%52,%53,%54,%55,%56,%57,%58,%59,%60,%61,%62,%63}, %64, %65, p, 1, 1, 0, 1;}"
    : "+f"(d[0]),"+f"(d[1]),"+f"(d[2]),"+f"(d[3]),"+f"(d[4]),"+f"(d[5]),"+f"(d[6]),"+f"(d[7]),"+f"(d[8]),"+f"(d[9]),"+f"(d[10]),"+f"(d[11]),"+f"(d[12]),"+f"(d[13]),"+f"(d[14]),"+f"(d[15]),"+f"(d[16]),"+f"(d[17]),"+f"(d[18]),"+f"(d[19]),"+f"(d[20]),"+f"(d[21]),"+f"(d[22]),"+f"(d[23]),"+f"(d[24]),"+f"(d[25]),"+f"(d[26]),"+f"(d[27]),"+f"(d[28]),"+f"(d[29]),"+f"(d[30]),"+f"(d[31]),"+f"(d[32]),"+f"(d[33]),"+f"(d[34]),"+f"(d[35]),"+f"(d[36]),"+f"(d[37]),"+f"(d[38]),"+f"(d[39]),"+f"(d[40]),"+f"(d[41]),"+f"(d[42]),"+f"(d[43]),"+f"(d[44]),"+f"(d[45]),"+f"(d[46]),"+f"(d[47]),"+f"(d[48]),"+f"(d[49]),"+f"(d[50]),"+f"(d[51]),"+f"(d[52]),"+f"(d[53]),"+f"(d[54]),"+f"(d[55]),"+f"(d[56]),"+f"(d[57]),"+f"(d[58]),"+f"(d[59]),"+f"(d[60]),"+f"(d[61]),"+f"(d[62]),"+f"(d[63]) : "l"(da),"l"(db),"r"(sc));
}
__device__ __forceinline__ void wg_ss96_01(float* d, uint64_t da, uint64_t db, int sc) {
  asm volatile("{.reg .pred p; setp.ne.b32 p, %50, 0; wgmma.mma_async.sync.aligned.m64n96k16.f32.bf16.bf16 {%0,%1,%2,%3,%4,%5,%6,%7,%8,%9,%10,%11,%12,%13,%14,%15,%16,%17,%18,%19,%20,%21,%22,%23,%24,%25,%26,%27,%28,%29,%30,%31,%32,%33,%34,%35,%36,%37,%38,%39,%40,%41,%42,%43,%44,%45,%46,%47}, %48, %49, p, 1, 1, 0, 1;}"
    : "+f"(d[0]),"+f"(d[1]),"+f"(d[2]),"+f"(d[3]),"+f"(d[4]),"+f"(d[5]),"+f"(d[6]),"+f"(d[7]),"+f"(d[8]),"+f"(d[9]),"+f"(d[10]),"+f"(d[11]),"+f"(d[12]),"+f"(d[13]),"+f"(d[14]),"+f"(d[15]),"+f"(d[16]),"+f"(d[17]),"+f"(d[18]),"+f"(d[19]),"+f"(d[20]),"+f"(d[21]),"+f"(d[22]),"+f"(d[23]),"+f"(d[24]),"+f"(d[25]),"+f"(d[26]),"+f"(d[27]),"+f"(d[28]),"+f"(d[29]),"+f"(d[30]),"+f"(d[31]),"+f"(d[32]),"+f"(d[33]),"+f"(d[34]),"+f"(d[35]),"+f"(d[36]),"+f"(d[37]),"+f"(d[38]),"+f"(d[39]),"+f"(d[40]),"+f"(d[41]),"+f"(d[42]),"+f"(d[43]),"+f"(d[44]),"+f"(d[45]),"+f"(d[46]),"+f"(d[47]) : "l"(da),"l"(db),"r"(sc));
}
__device__ __forceinline__ void wg_rs64_1(float* d, const uint32_t* a, uint64_t db, int sc) {
  asm volatile("{.reg .pred p; setp.ne.b32 p, %37, 0; wgmma.mma_async.sync.aligned.m64n64k16.f32.bf16.bf16 {%0,%1,%2,%3,%4,%5,%6,%7,%8,%9,%10,%11,%12,%13,%14,%15,%16,%17,%18,%19,%20,%21,%22,%23,%24,%25,%26,%27,%28,%29,%30,%31}, {%32,%33,%34,%35}, %36, p, 1, 1, 1;}"
    : "+f"(d[0]),"+f"(d[1]),"+f"(d[2]),"+f"(d[3]),"+f"(d[4]),"+f"(d[5]),"+f"(d[6]),"+f"(d[7]),"+f"(d[8]),"+f"(d[9]),"+f"(d[10]),"+f"(d[11]),"+f"(d[12]),"+f"(d[13]),"+f"(d[14]),"+f"(d[15]),"+f"(d[16]),"+f"(d[17]),"+f"(d[18]),"+f"(d[19]),"+f"(d[20]),"+f"(d[21]),"+f"(d[22]),"+f"(d[23]),"+f"(d[24]),"+f"(d[25]),"+f"(d[26]),"+f"(d[27]),"+f"(d[28]),"+f"(d[29]),"+f"(d[30]),"+f"(d[31]) : "r"(a[0]),"r"(a[1]),"r"(a[2]),"r"(a[3]),"l"(db),"r"(sc));
}
__device__ __forceinline__ void wg_rs96_1(float* d, const uint32_t* a, uint64_t db, int sc) {
  asm volatile("{.reg .pred p; setp.ne.b32 p, %53, 0; wgmma.mma_async.sync.aligned.m64n96k16.f32.bf16.bf16 {%0,%1,%2,%3,%4,%5,%6,%7,%8,%9,%10,%11,%12,%13,%14,%15,%16,%17,%18,%19,%20,%21,%22,%23,%24,%25,%26,%27,%28,%29,%30,%31,%32,%33,%34,%35,%36,%37,%38,%39,%40,%41,%42,%43,%44,%45,%46,%47}, {%48,%49,%50,%51}, %52, p, 1, 1, 1;}"
    : "+f"(d[0]),"+f"(d[1]),"+f"(d[2]),"+f"(d[3]),"+f"(d[4]),"+f"(d[5]),"+f"(d[6]),"+f"(d[7]),"+f"(d[8]),"+f"(d[9]),"+f"(d[10]),"+f"(d[11]),"+f"(d[12]),"+f"(d[13]),"+f"(d[14]),"+f"(d[15]),"+f"(d[16]),"+f"(d[17]),"+f"(d[18]),"+f"(d[19]),"+f"(d[20]),"+f"(d[21]),"+f"(d[22]),"+f"(d[23]),"+f"(d[24]),"+f"(d[25]),"+f"(d[26]),"+f"(d[27]),"+f"(d[28]),"+f"(d[29]),"+f"(d[30]),"+f"(d[31]),"+f"(d[32]),"+f"(d[33]),"+f"(d[34]),"+f"(d[35]),"+f"(d[36]),"+f"(d[37]),"+f"(d[38]),"+f"(d[39]),"+f"(d[40]),"+f"(d[41]),"+f"(d[42]),"+f"(d[43]),"+f"(d[44]),"+f"(d[45]),"+f"(d[46]),"+f"(d[47]) : "r"(a[0]),"r"(a[1]),"r"(a[2]),"r"(a[3]),"l"(db),"r"(sc));
}
__device__ __forceinline__ void wg_ss160_01(float* d, uint64_t da, uint64_t db, int sc) {
  asm volatile("{.reg .pred p; setp.ne.b32 p, %82, 0; wgmma.mma_async.sync.aligned.m64n160k16.f32.bf16.bf16 {%0,%1,%2,%3,%4,%5,%6,%7,%8,%9,%10,%11,%12,%13,%14,%15,%16,%17,%18,%19,%20,%21,%22,%23,%24,%25,%26,%27,%28,%29,%30,%31,%32,%33,%34,%35,%36,%37,%38,%39,%40,%41,%42,%43,%44,%45,%46,%47,%48,%49,%50,%51,%52,%53,%54,%55,%56,%57,%58,%59,%60,%61,%62,%63,%64,%65,%66,%67,%68,%69,%70,%71,%72,%73,%74,%75,%76,%77,%78,%79}, %80, %81, p, 1, 1, 0, 1;}"
    : "+f"(d[0]),"+f"(d[1]),"+f"(d[2]),"+f"(d[3]),"+f"(d[4]),"+f"(d[5]),"+f"(d[6]),"+f"(d[7]),"+f"(d[8]),"+f"(d[9]),"+f"(d[10]),"+f"(d[11]),"+f"(d[12]),"+f"(d[13]),"+f"(d[14]),"+f"(d[15]),"+f"(d[16]),"+f"(d[17]),"+f"(d[18]),"+f"(d[19]),"+f"(d[20]),"+f"(d[21]),"+f"(d[22]),"+f"(d[23]),"+f"(d[24]),"+f"(d[25]),"+f"(d[26]),"+f"(d[27]),"+f"(d[28]),"+f"(d[29]),"+f"(d[30]),"+f"(d[31]),"+f"(d[32]),"+f"(d[33]),"+f"(d[34]),"+f"(d[35]),"+f"(d[36]),"+f"(d[37]),"+f"(d[38]),"+f"(d[39]),"+f"(d[40]),"+f"(d[41]),"+f"(d[42]),"+f"(d[43]),"+f"(d[44]),"+f"(d[45]),"+f"(d[46]),"+f"(d[47]),"+f"(d[48]),"+f"(d[49]),"+f"(d[50]),"+f"(d[51]),"+f"(d[52]),"+f"(d[53]),"+f"(d[54]),"+f"(d[55]),"+f"(d[56]),"+f"(d[57]),"+f"(d[58]),"+f"(d[59]),"+f"(d[60]),"+f"(d[61]),"+f"(d[62]),"+f"(d[63]),"+f"(d[64]),"+f"(d[65]),"+f"(d[66]),"+f"(d[67]),"+f"(d[68]),"+f"(d[69]),"+f"(d[70]),"+f"(d[71]),"+f"(d[72]),"+f"(d[73]),"+f"(d[74]),"+f"(d[75]),"+f"(d[76]),"+f"(d[77]),"+f"(d[78]),"+f"(d[79]) : "l"(da),"l"(db),"r"(sc));
}
__device__ __forceinline__ void wg_rs160_1(float* d, const uint32_t* a, uint64_t db, int sc) {
  asm volatile("{.reg .pred p; setp.ne.b32 p, %85, 0; wgmma.mma_async.sync.aligned.m64n160k16.f32.bf16.bf16 {%0,%1,%2,%3,%4,%5,%6,%7,%8,%9,%10,%11,%12,%13,%14,%15,%16,%17,%18,%19,%20,%21,%22,%23,%24,%25,%26,%27,%28,%29,%30,%31,%32,%33,%34,%35,%36,%37,%38,%39,%40,%41,%42,%43,%44,%45,%46,%47,%48,%49,%50,%51,%52,%53,%54,%55,%56,%57,%58,%59,%60,%61,%62,%63,%64,%65,%66,%67,%68,%69,%70,%71,%72,%73,%74,%75,%76,%77,%78,%79}, {%80,%81,%82,%83}, %84, p, 1, 1, 1;}"
    : "+f"(d[0]),"+f"(d[1]),"+f"(d[2]),"+f"(d[3]),"+f"(d[4]),"+f"(d[5]),"+f"(d[6]),"+f"(d[7]),"+f"(d[8]),"+f"(d[9]),"+f"(d[10]),"+f"(d[11]),"+f"(d[12]),"+f"(d[13]),"+f"(d[14]),"+f"(d[15]),"+f"(d[16]),"+f"(d[17]),"+f"(d[18]),"+f"(d[19]),"+f"(d[20]),"+f"(d[21]),"+f"(d[22]),"+f"(d[23]),"+f"(d[24]),"+f"(d[25]),"+f"(d[26]),"+f"(d[27]),"+f"(d[28]),"+f"(d[29]),"+f"(d[30]),"+f"(d[31]),"+f"(d[32]),"+f"(d[33]),"+f"(d[34]),"+f"(d[35]),"+f"(d[36]),"+f"(d[37]),"+f"(d[38]),"+f"(d[39]),"+f"(d[40]),"+f"(d[41]),"+f"(d[42]),"+f"(d[43]),"+f"(d[44]),"+f"(d[45]),"+f"(d[46]),"+f"(d[47]),"+f"(d[48]),"+f"(d[49]),"+f"(d[50]),"+f"(d[51]),"+f"(d[52]),"+f"(d[53]),"+f"(d[54]),"+f"(d[55]),"+f"(d[56]),"+f"(d[57]),"+f"(d[58]),"+f"(d[59]),"+f"(d[60]),"+f"(d[61]),"+f"(d[62]),"+f"(d[63]),"+f"(d[64]),"+f"(d[65]),"+f"(d[66]),"+f"(d[67]),"+f"(d[68]),"+f"(d[69]),"+f"(d[70]),"+f"(d[71]),"+f"(d[72]),"+f"(d[73]),"+f"(d[74]),"+f"(d[75]),"+f"(d[76]),"+f"(d[77]),"+f"(d[78]),"+f"(d[79]) : "r"(a[0]),"r"(a[1]),"r"(a[2]),"r"(a[3]),"l"(db),"r"(sc));
}
__device__ __forceinline__ void wg_ss8_10(float* d, uint64_t da, uint64_t db, int sc) {
  asm volatile("{.reg .pred p; setp.ne.b32 p, %6, 0; wgmma.mma_async.sync.aligned.m64n8k16.f32.bf16.bf16 {%0,%1,%2,%3}, %4, %5, p, 1, 1, 1, 0;}"
    : "+f"(d[0]),"+f"(d[1]),"+f"(d[2]),"+f"(d[3]) : "l"(da),"l"(db),"r"(sc));
}
__device__ __forceinline__ void wg_ss8_if(float* d, uint64_t da, uint64_t db, int sc, int skip) {
  asm volatile("{.reg .pred p, q; setp.ne.b32 p, %6, 0; setp.eq.b32 q, %7, 0; @q wgmma.mma_async.sync.aligned.m64n8k16.f32.bf16.bf16 {%0,%1,%2,%3}, %4, %5, p, 1, 1, 1, 0;}"
    : "+f"(d[0]),"+f"(d[1]),"+f"(d[2]),"+f"(d[3]) : "l"(da),"l"(db),"r"(sc),"r"(skip));
}

constexpr uint32_t DB = 1024;
constexpr int UNIT = 8192, WSLOT = 16384, W2TILE = 24576, OFF_R = 12 * UNIT;
constexpr int OFF_PB = 26 * UNIT;
constexpr int OFF_CV = OFF_PB + 16384, OFF_ST = OFF_CV + 768, OFF_TS = OFF_ST + 256, OFF_MODR = OFF_TS + 512, OFF_ROLE = OFF_MODR + 80, OFF_BAR = OFF_ROLE + 16, SMEM_BYTES = OFF_BAR + 1400;
constexpr int OFF_BX = OFF_PB, OFF_AX = OFF_BX + 12288, OFF_RT = OFF_AX + 2048, OFF_GB = OFF_RT + 512, OFF_CO = OFF_CV;
constexpr int OFF_UV = 4 * UNIT, OFF_SX = 24 * UNIT, OFF_XCH = 12 * UNIT;
constexpr int OFF_Q = 99328, KV_V = 4096, KV_H = 8192, F_E = 128, F_O = 4288, OFF_WM = 20 * UNIT, OFF_TAP = 12672, OFF_MR = 25 * UNIT;
constexpr uint64_t pk5(int a, int b, int c, int d, int e) { return (uint64_t)(a / 128) | (uint64_t)(b / 128) << 12 | (uint64_t)(c / 128) << 24 | (uint64_t)(d / 128) << 36 | (uint64_t)(e / 128) << 48; }
constexpr uint64_t T_KV = pk5(119808, 16384, 130048, 65536, 49152), T_F = pk5(140288, 90368, 148736, 81920, OFF_PB), T_X = pk5(0, 4224, 8448, 0, 4224),
                   T_P = pk5(32768, 16384, 65536, 81920, OFF_PB);
__host__ __device__ __forceinline__ uint32_t tab(uint64_t t, int c) { return ((uint32_t)(t >> (12 * c)) & 0xFFF) << 7; }
enum { B_KV = 0, B_FRAW = 5, B_Q = 10, B_WM = 15, B_XR = 17, B_MR = B_XR + 5, B_QTOK, B_ST1, B_MODR, B_ROLE = B_MODR + 5, B_FL = 32, B_PFULL = B_FL + 5, B_PEMPTY = B_PFULL + 5, B_FRDY = B_PEMPTY + 5,
       B_G = B_FRDY + 5, B_EXT = B_G + 2, B_QTD, B_ED, B_S2 = B_ED + 2, B_GB, B_FULL = 60, B_RETRY = B_FULL + 43, B_XFREE = B_RETRY + 8, B_BX, B_UVB, B_CO, B_SX, B_EMPTY = 121, B_SC = 164, B_STD = B_SC + 5, B_LAG, B_LAST };
static_assert(B_ROLE < B_FL && B_GB < B_FULL && B_SX + 5 <= B_EMPTY - 1 && OFF_MR == OFF_SX + 8192 && SMEM_BYTES <= 232448, "barrier groups");
#define BAR(i) (base + OFF_BAR + 8 * (i))

struct Maps { CUtensorMap km, v, q, fm, wmp, kh, tap, wm, w1a, w3a, xs, w1u, w3u, w1b, w3b, x1s, x1b, w2a, w2b, outa, outb; };
struct Ptrs { const bf16 *c, *ssmd; Scratch* g; uint64_t prog[2]; uint32_t gate[5]; int ulo; uint32_t mq, xh, xdep, hstart, hpause, hl[8], uvd, mpos, wt0, wpace; float one; uint32_t wdep[30], adep[14]; uint2 w2t[12]; int hid[4][9]; };

#define REGION_IDS int tid, lane, bid; \
  asm volatile("mov.u32 %0, %%tid.x;" : "=r"(tid)); asm volatile("mov.u32 %0, %%laneid;" : "=r"(lane)); asm volatile("mov.u32 %0, %%ctaid.x;" : "=r"(bid)); \
  const int i0 = tid & 127; (void)i0; (void)lane; (void)bid

#define ffn_role(h, j, r) do { \
  mbar_wait(BAR(B_ROLE)); \
  r = __shfl_sync(~0u, lds32(base + OFF_ROLE), 0); \
  asm volatile("mov.u32 %0, %%ctaid.x;" : "=r"(h)); \
  h &= 1; j = r >> 4; r &= 15; } while (0)
__device__ __forceinline__ void rank_pair(Scratch* G, uint32_t base, uint32_t epoch, bool put) {
  REGION_IDS;
  uint32_t t;
  asm volatile("mov.u32 %0, %%smid;" : "=r"(t));
  t >>= 1;
  const uint32_t q = (t - 32) * 37 >> 8, g = t < 32 ? t & 7 : t < 60 ? t - 31 - 7 * q : t < 62 ? t - 54 : 0;
  const uint32_t key = epoch << 20 | (g & 3) << 18 | (g & 4) << 15 | (t & 127) << 6 | bid >> 1;
  if (put) {
    if (lane == (bid & 1) * 99) publish(&G->key[bid >> 1], key);
    return;
  }
  uint2 x;
  int it = 0;
#pragma unroll 1
  do x = ld_relaxed64(&G->key[2 * lane]); while (__any_sync(~0u, ((x.x ^ key) | (x.y ^ key)) >> 20) && ++it < SPIN_LIMIT);
  t = __shfl_sync(~0u, bid & 2 ? x.y : x.x, bid >> 2);
  sts32(base + OFF_ROLE, __popc(__ballot_sync(~0u, x.x < t)) + __popc(__ballot_sync(~0u, x.y < t)));
  arrive1(BAR(B_ROLE));
}
__device__ __forceinline__ int mod_ch(int p) { return p < 40 ? (p >> 3) * 128 + (p & 1) * 64 : 64 * (p < 50 ? p - 40 : p - 50); }
__device__ __forceinline__ int mod_col(int p) { return mod_ch(p) + 640 * (p < 40 ? 0x4210 >> (2 * (p & 6)) & 7 : p < 50 ? 3 : 5); }
__device__ __forceinline__ uint32_t mod_sum(uint2 v) { return pack_bf16(0.f, __uint_as_float(v.x) + __uint_as_float(v.y)); }
#define UVS 5
#define XP 2
#define GA 3
#define GB 1
#define HL 0
#define EH 0
#define MG 4
#define SG 0x88
#define SPL 41
#define NP 8
__device__ __forceinline__ int nib(uint32_t t, int i) { return (t >> (4 * i)) & 15; }
__device__ __forceinline__ int w_block(int up, int m) { return m < 2 ? 2 * up + m : 4 + up; }
__host__ __device__ constexpr int w2_at(int v) { return UNIT * (v == 1 ? 0 : 0x0811030C18ull >> (v - (v > 1)) % 5 * 8 & 255); }
__host__ __device__ constexpr int hid_at(int m, int g) { return UNIT * ((g ? 0x0200150710ull : 0x010B14060Full) >> m % 5 * 8 & 255); }
__host__ __device__ constexpr int x1_at(int k) { return k < 4 ? 22 * UNIT + 4096 * k : OFF_BX + UNIT; }
__host__ __device__ constexpr uint32_t w2_desc(int v) { return (DB + w2_at(v)) >> 4 | UNIT << 12; }
__host__ __device__ constexpr int a_at(int n) { return WSLOT * (0x54323251041032ull >> 4 * n & 15); }
__host__ __device__ constexpr int second(int v) { return 0xDCBA657498ull >> 4 * v & 15; }

#define WINS "4444444444443444444"
#define ORDER "k1v1f0q0q1q2q3q4k2v2f1k3v3f2k4v4f3w0f4"
constexpr int NL = sizeof(ORDER) / 2, TA = 16, M8 = 3 << TA / 8;
__host__ __device__ constexpr int load_bar(int e) { return e < 0 ? B_KV : ORDER[2 * e + 1] - '0' + (ORDER[2 * e] == 'q' ? B_Q : ORDER[2 * e] == 'f' ? B_FRAW : ORDER[2 * e] == 'w' ? B_WM : B_KV); }
__host__ __device__ constexpr int load_gate(int e, int w) {
  int i = e, sum = 0;
  while (i >= -1 && sum + (i < 0 ? 8 : ORDER[2 * i] == 'w' ? 10 : 4) <= 4 * w) { sum += i < 0 ? 8 : ORDER[2 * i] == 'w' ? 10 : 4; i--; }
  for (; i >= -1; i--) {
    bool ok = i < e;
    for (int k = e; k < NL; k++) ok = ok && load_bar(k) != load_bar(i);
    if (ok) return load_bar(i);
  }
  return -1;
}
template <int E> __device__ __forceinline__ void loads(const Ptrs& P, const Maps& maps, uint32_t base) {
  if constexpr (E < NL) {
    constexpr int r = ORDER[2 * E + 1] - '0';
    constexpr char x = ORDER[2 * E];
    const int c0 = 128 * r + 64 * (blockIdx.x & 1), c1 = 2 * (blockIdx.x & 126);
    constexpr int g = load_gate(E, WINS[E] - '0');
    if (g >= 0 && (E == 0 || g != load_gate(E - 1, WINS[E ? E - 1 : 0] - '0'))) mbar_wait(BAR(g < 0 ? 0 : g));
    if (elect()) {
      if (x == 'k') { tma3d(base + tab(T_KV, r), &maps.km, c0, c1, 0, BAR(B_KV + r)); tma3d(base + tab(T_KV, r) + KV_H, &maps.kh, c0, c1 - 1, 5, BAR(B_KV + r)); }
      if (x == 'v') tma3d(base + tab(T_KV, r) + KV_V, &maps.v, c0, c1, 0, BAR(B_KV + r));
      if (x == 'q') tma3d(base + OFF_Q + 4096 * r, &maps.q, c0, c1, 0, BAR(B_Q + r));
      if (x == 'f') tma3d(base + tab(T_F, r) + F_E, &maps.fm, 0, 0, 128 * r + blockIdx.x, BAR(B_FRAW + r));
      if (x == 'w') tma3d(base + OFF_WM, &maps.wmp, mod_col(TA + (blockIdx.x >> 3)), 80 * (blockIdx.x & 7), 0, BAR(B_WM));
    }
    loads<E + 1>(P, maps, base);
  }
}

template <int U> __device__ __forceinline__ void cstep(float* acc, const uint32_t* A, uint64_t db) {
  const uint32_t* a = A + 4 * U;
  const uint64_t d = db + 16 * U;
  if (U == 4) { wg_rs64_0(acc + 96, A, db + 192, 0); wg_rs48_0(acc + 96, A + 4, db + 208, 1); wg_rs32_0(acc + 96, A + 8, db + 224, 1); wg_rs16_0(acc + 96, A + 12, db + 240, 1); }
  if (U <= 4) wg_rs192_0(acc, a, d, U);
  if (U == 5) wg_rs176_0(acc, a, d, 1);
  if (U == 6) wg_rs160_0(acc, a, d, 1);
  if (U == 7) wg_rs144_0(acc, a, d, 1);
  if (U == 8) wg_rs128_0(acc, a, d, 1);
  if (U == 9) wg_rs112_0(acc, a, d, 1);
  if (U == 10) wg_rs96_0(acc, a, d, 1);
  if (U == 11) wg_rs80_0(acc, a, d, 1);
  if (U == 12) wg_rs64_0(acc, a, d, 1);
  if (U == 13) wg_rs48_0(acc, a, d, 1);
  if (U == 14) wg_rs32_0(acc, a, d, 1);
  if (U == 15) wg_rs16_0(acc, a, d, 1);
}
template <int U0, int U1> __device__ __forceinline__ void csteps(float* acc, const uint32_t* A, uint64_t db) {
  cstep<U0>(acc, A, db);
  if constexpr (U0 > U1) csteps<U0 - 1, U1>(acc, A, db);
}
template <int U0, int U1> __device__ __forceinline__ void cload(uint32_t* A, uint32_t fa) {
  asm volatile("{ld.shared.b32 %0, [%4+%5]; ld.shared.b32 %1, [%4+%5+128]; ld.shared.b32 %2, [%4+%5+16]; ld.shared.b32 %3, [%4+%5+144];}"
               : "=r"(A[4 * U0]), "=r"(A[4 * U0 + 1]), "=r"(A[4 * U0 + 2]), "=r"(A[4 * U0 + 3]) : "r"(fa), "n"(256 * U0) : "memory");
  if constexpr (U0 > U1) cload<U0 - 1, U1>(A, fa);
}

template <int NK> __device__ __forceinline__ void mod_gemv(Scratch* G, uint32_t wm, int p, int part, int w, int lane, uint32_t par) {
  float d[4] = {};
  fence_regs(d);
  wg_fence();
#pragma unroll 1
  for (int k = 0; k < NK; k += 5) {
#pragma unroll
    for (int i = 0; i < 5; i++) wg_ss8_10(d, mkdesc(DB + wm + 2048 * (k + i), 16, 1024, 1), mkdesc(DB + OFF_CV + 32 * (k + i), 16, 128, 0), 1);
  }
  wg_commit();
  const int ch = mod_ch(p) + 16 * w + (lane >> 2);
  uint32_t* dst = (p < 40 ? &G->modc[ch & 127][p >> 3][4 * (p & 6)] : (uint32_t*)&G->modv[p >= 50][ch]) + part;
  wg_wait<0>();
  fence_regs(d);
  if (!(lane & 3)) {
    publish(dst, (__float_as_uint(d[0]) & ~1u) | par);
    publish(dst + (p < 40 ? 1280 : 16), (__float_as_uint(d[2]) & ~1u) | par);
    if (NK == 20 && p < 40 && (p & 6) == 6) {
      dst = (uint32_t*)&G->modv[2][ch] + part;
      publish(dst, (__float_as_uint(d[0]) & ~1u) | par);
      publish(dst + 16, (__float_as_uint(d[2]) & ~1u) | par);
    }
  }
}
__device__ __forceinline__ void mod_fetch(Scratch* G, uint32_t base, uint32_t epoch, uint32_t m8, uint32_t c, uint32_t c1) {
  REGION_IDS;
  const uint32_t* mp = &G->modc[bid][0][lane];
  auto unused = [&]() { return (lane & 6) && !(m8 >> c & 1); };
#pragma unroll 1
  for (int it = 0; c < c1 && it < SPIN_LIMIT; it++) {
    uint32_t m = ld_relaxed32(mp + 32 * c);
    const uint32_t m1 = ld_relaxed32(mp + 32 * min(c + 1, c1 - 1));
#pragma unroll 1
    for (int k = 0; k < 2 && c < c1 && __all_sync(~0u, unused() || !((m ^ epoch) & 1)); k++) {
      float x = unused() ? 0.f : __uint_as_float(m);
      x += __shfl_xor_sync(~0u, x, 1); x += __shfl_xor_sync(~0u, x, 2); x += __shfl_xor_sync(~0u, x, 4);
      const uint32_t y = __byte_perm(badd2(pack_bf16(0.f, x), (lane & 8) * 0x07F00000u), 0, 0x3232), ga = __shfl_sync(~0u, y, 16);
      sts32(base + OFF_MODR + 16 * c + 4 * (lane >> 3), lane < 16 ? bmul2(y, ga) : y);
      arrive1(BAR(B_MODR + c));
      if (lane >= 30 && (m8 >> c & 1)) publish((uint32_t*)&G->modv[2][128 * c + bid] + (lane & 1), ((lane & 1 ? 0 : __float_as_uint(x)) & ~1u) | (epoch & 1));
      m = m1;
      c++;
    }
  }
}
__device__ __forceinline__ void add4(uint4& y, const uint4& z) { y.x = badd2(y.x, z.x); y.y = badd2(y.y, z.y); y.z = badd2(y.z, z.z); y.w = badd2(y.w, z.w); }
template <bool FIRST> __device__ __forceinline__ void e_round(Scratch* G, uint32_t base, uint32_t sa, uint4*& gp, uint4* q, int c, int w, uint32_t tag, uint32_t epoch) {
  constexpr int QO = -D_ * 256;
  mbar_wait(BAR(B_MODR + c));
  const uint4 co = lds128(base + OFF_MODR + 16 * c);
  mbar_wait(BAR(B_PFULL + c));
  const uint32_t pb = sa + tab(T_P, c);
  uint4 l[2][6];
  auto load = [&](int hf, int k) { l[hf][k] = lds128((k < 4 ? pb + 4096 * k : sa + OFF_MR + 4096 * (k - 4)) + 2048 * hf); };
#pragma unroll
  for (int hf = 0; hf < 2; hf++) {
    uint4 &y = l[hf][0], &z = l[hf][4], &m = l[hf][5];
    load(hf, 0);
    if (!FIRST) {
      load(hf, 1);
      add4(y, l[hf][1]);
      load(hf, 2); load(hf, 3);
      add4(l[hf][2], l[hf][3]);
      add4(y, l[hf][2]);
    }
    load(hf, 4); load(hf, 5);
    if (FIRST) {
#pragma unroll 1
      for (int it = 0; __any_sync(~0u, ((z.x >> 15 ^ epoch) | (m.x ^ epoch)) & tag) && it < SPIN_LIMIT; it++) {
        const uint4* sp = (const uint4*)G->st1 + (opaque(sa) - base >> 4) + 128 * hf;
        z = ld_relaxed128(sp);
        m = ld_relaxed128(sp + 256);
        sts128(sa + OFF_MR + 2048 * hf, z.x, z.y, z.z, z.w);
        sts128(sa + OFF_MR + 2048 * hf + 4096, m.x, m.y, m.z, m.w);
      }
      z.x &= 0xFFFF7FFFu;
      sts32(sa + OFF_MR + 2048 * hf, z.x);
    }
#pragma unroll 1
    for (int it = 0; __any_sync(~0u, (q[hf].x ^ epoch) & tag) && it < SPIN_LIMIT; it++) {
      q[hf] = ld_relaxed128(gp + QO + 128 * hf);
    }
    y.x = bfma2(bfma2(bfma2(q[hf].x, z.x, m.x), co.y, co.x), y.x, q[hf].x);
    auto hint = [&]() {
      __syncwarp();
      asm volatile("{.reg .pred p; elect.sync _|p, 0xffffffff; @p red.relaxed.gpu.global.add.u32 [%0], 1; @p mbarrier.arrive.shared::cta.b64 _, [%1];}"
                   ::"l"(G->xsh[c][2 * w + (blockIdx.x >> 6)]), "r"(BAR(B_PEMPTY + c)), "r"(y.x) : "memory");
    };
    if (hf && !EH) hint();
    y.y = bfma2(bfma2(bfma2(q[hf].y, z.y, m.y), co.y, co.x), y.y, q[hf].y);
    y.z = bfma2(bfma2(bfma2(q[hf].z, z.z, m.z), co.y, co.x), y.z, q[hf].z);
    y.w = bfma2(bfma2(bfma2(q[hf].w, z.w, m.w), co.y, co.x), y.w, q[hf].w);
    st_relaxed128(gp + 128 * hf, set_tag(bmul2(y.x, co.w), tag, epoch), bmul2(y.y, co.w), bmul2(y.z, co.w), bmul2(y.w, co.w));
    if (hf && EH == 1) hint();
    asm volatile("{.reg .pred p; .reg .b32 t; setp.ne.u32 p, %5, 0; max.u32 t, %1, 1; @!p st.relaxed.gpu.global.v4.u32 [%0+%6], {t,%2,%3,%4}; @p st.relaxed.gpu.global.v4.u32 [%0+%7], {t,%2,%3,%4};}"
                 ::"l"(gp + 128 * hf), "r"(y.x), "r"(y.y), "r"(y.z), "r"(y.w), "r"(epoch & 1), "n"(D_ * 4096), "n"(D_ * 8192) : "memory");
    if (hf && EH == 2) hint();
    if (c < 4) q[hf] = ld_relaxed128(gp + QO + 32768 + 128 * hf);
  }
  gp += 32768;
}
__device__ __forceinline__ void q_stats(uint32_t base, int w) {
  REGION_IDS;
  float s0 = 0.f, s1 = 0.f, q0 = 0.f, q1 = 0.f;
  const uint32_t a = OFF_Q + 1024 * w + 128 * (lane & 7) + (((lane >> 3) ^ (lane & 7)) << 4);
  const uint32_t ra = mapa(base + OFF_ST + 128 * (bid & 1) + 64 * (lane & 1) + 16 * w + 8 * (lane >> 2), lane >> 1 & 1), rb = mapa(BAR(B_ST1), lane >> 1 & 1);
  if (w == 3 && elect()) mbar_expect_tx(BAR(B_ST1), 256);
#pragma unroll 1
  for (int k = 0; k < 5; k++) {
    mbar_wait(BAR(B_Q + k));
    const uint32_t o = opaque(base + 4096 * k);
    const uint4 x = lds128(o + a), y = lds128(o + (a ^ 64));
    const uint32_t e[8] = {x.x, x.y, x.z, x.w, y.x, y.y, y.z, y.w};
#pragma unroll
    for (int i = 0; i < 8; i++) { const float lo = bf_lo(e[i]), hi = bf_hi(e[i]); s0 += lo; s1 += hi; q0 = fmaf(lo, lo, q0); q1 = fmaf(hi, hi, q1); }
  }
  s0 += s1; q0 += q1;
  arrive1(BAR(B_STD));
  s0 += __shfl_xor_sync(~0u, s0, 8); q0 += __shfl_xor_sync(~0u, q0, 8);
  s0 += __shfl_xor_sync(~0u, s0, 16); q0 += __shfl_xor_sync(~0u, q0, 16);
  if (lane < 8) asm volatile("st.async.shared::cluster.mbarrier::complete_tx::bytes.v2.b32 [%0], {%1,%2}, [%3];" ::"r"(ra), "r"(__float_as_uint(s0)), "r"(__float_as_uint(q0)), "r"(rb) : "memory");
}
__device__ __forceinline__ void short_conv(Scratch* G, uint32_t base, int s, int w, uint32_t par, uint32_t xh) {
  REGION_IDS;
  const uint32_t a = base + tab(T_KV, s) + 128 * (lane & 3) + ((w ^ (lane & 3)) << 4) + 4 * (lane & 16) + (lane & 12), keep = ~(lane & 1);
  uint4* dst = G->xr + (128 * s + 64 * (bid & 1) + 8 * w + 2 * (lane & 16) + (lane >> 1 & 6)) * 256 + 255 - 4 * (bid >> 1) - (lane & 3);
  mbar_wait(BAR(B_KV));
  mbar_wait(BAR(B_KV + s));
  const uint4 wv = lds128(base + OFF_TAP + 512 * s + 64 * w + 16 * (lane & 16) + 4 * (lane & 12));
  uint32_t kk[11], r[8];
#pragma unroll
  for (int k = 0; k < 11; k++) kk[k] = k < 3 ? lds32((a ^ (64 * (k & 1))) + KV_H + 512 * k) : lds32((a ^ (64 * (~k & 1))) + 512 * (k - 3));
  if (xh == 0 && elect()) red_hint(G->hint[s][4 * (bid & 1) + w]);
#pragma unroll
  for (int k = 0; k < 8; k++) r[k] = lds32((a ^ (64 * (k & 1))) + KV_V + 512 * k);
  arrive1(BAR(B_SC + s));
  const uint32_t w0 = __byte_perm(wv.x, wv.z, 0x5410), w1 = __byte_perm(wv.x, wv.z, 0x7632),
                 w2 = __byte_perm(wv.y, wv.w, 0x5410), w3 = __byte_perm(wv.y, wv.w, 0x7632);
#pragma unroll
  for (int k = 0; k < 8; k++) r[k] = bmul2(bfma2(kk[k + 3], w0, bfma2(kk[k + 2], w1, bfma2(kk[k + 1], w2, bmul2(kk[k], w3)))), r[k]);
  const uint32_t bit = ~par >> 7 & lane & 1;
  if (xh == 1 && elect()) red_hint(G->hint[s][4 * (bid & 1) + w]);
  st_relaxed128(dst, (__byte_perm(r[7], r[6], 0x5410) & keep) | bit, __byte_perm(r[5], r[4], 0x5410), __byte_perm(r[3], r[2], 0x5410), __byte_perm(r[1], r[0], 0x5410));
  st_relaxed128(dst + 256, (__byte_perm(r[7], r[6], 0x7632) & keep) | bit, __byte_perm(r[5], r[4], 0x7632), __byte_perm(r[3], r[2], 0x7632), __byte_perm(r[1], r[0], 0x7632));
  if (xh == 2 && elect()) red_hint(G->hint[s][4 * (bid & 1) + w]);
}
__device__ __forceinline__ void silu_vector(const bf16* c, int n, uint32_t base) {
  REGION_IDS;
  if (tid < n) {
    const uint32_t x = ldg32(c + 2 * tid);
    sts32(base + OFF_CV + 4 * tid, pack_bf16(silu_f(bf_lo(x)), silu_f(bf_hi(x))));
  }
  fence_async_smem();
}

template <int FIRST> __global__ void __cluster_dims__(2, 1, 1) __launch_bounds__(512, 1) k_fused(const __grid_constant__ Ptrs P, const __grid_constant__ Maps maps) {
  Scratch* const G = P.g;
  extern __shared__ __align__(1024) uint8_t smem_raw[];
  const uint32_t t_start = clock();
  const uint32_t base = __shfl_sync(~0u, smem_u32(smem_raw), 0);
  if (threadIdx.x == 416 && blockIdx.x + FIRST < 128) {
    const int c0 = 64 * (blockIdx.x & 1), c1 = 2 * (blockIdx.x & 126);
    mbar_init<1>(BAR(B_KV), 1);
    mbar_expect_tx(BAR(B_KV), 12288);
    tma3d(base + tab(T_KV, 0), &maps.km, c0, c1, 0, BAR(B_KV));
    tma3d(base + tab(T_KV, 0) + KV_V, &maps.v, c0, c1, 0, BAR(B_KV));
    tma3d(base + tab(T_KV, 0) + KV_H, &maps.kh, c0, c1 - 1, 5, BAR(B_KV));
    tma3d(base + OFF_TAP, &maps.tap, 0, blockIdx.x & 1, 0, BAR(B_KV));
  }
  if ((base & 0xFFFFFFu) != DB) __trap();
  const int wid = __shfl_sync(~0u, threadIdx.x >> 5, 0), wg = wid >> 2, w = wid & 3;
  if (blockIdx.x + FIRST >= 128) {
    REGION_IDS;
    auto unit = [&](int n) { return 4 * (P.hl[n >> 2] >> 8 * (n & 3) & 255) + (bid & 3); };
    auto fetch = [&](int n, int b) {
      if (unit(n) < 120 && elect()) {
        mbar_expect_tx(BAR(n), 40960);
#pragma unroll 1
        for (int k = 0; k < 5; k++) tma3d(base + 40960 * b + 8192 * k, &maps.wm, mod_col(unit(n) >> 1), 320 * (bid & 1) + 64 * k, 0, BAR(n));
      }
    };
    if (wid == 0) {
      mbar_init<4>(BAR(0), 1);
#pragma unroll 1
      for (int n = 0; n < 4; n++) { wait_clock(t_start + (P.hstart & 0xFFFF) + n * (P.hstart >> 16)); fetch(n, n); }
      mbar_init<28>(BAR(4), 1);
    }
    const uint32_t par = ~ld_relaxed32(G->hint[7][0]) >> 7 & 1;
    silu_vector(P.c + 320 * (bid & 1), 160, base);
    __syncthreads();
#pragma unroll 1
    for (int n = wg; unit(n) < 120; n += 4) {
      mbar_wait(BAR(n));
      mod_gemv<20>(G, 40960 * (n % 5), unit(n) >> 1, bid & 1, w, lane, par);
      named_bar(1 + wg, 128);
      if (w == 0) {
        wait_clock(t_start + P.hpause);
        if (n == 0) fetch(4, 4);
        fetch(n + 5, n % 5);
      }
    }
    return;
  }
  mbar_init<3>(BAR(wid < 15 ? 4 * wid + 1 : B_SC + 1), wid < 8 ? 1 : 4);
  mbar_init<1>(BAR(!wid ? B_SC + 4 : wid < 15 ? 4 * wid : B_SC), wid && wid < 8 ? 1 : 4);
  if (wid == 0) mbar_init<2>(BAR(B_SC + 5), 4);
  asm volatile("fence.mbarrier_init.release.cluster; bar.sync 0, 512;" ::: "memory");
  asm volatile("barrier.cluster.arrive.relaxed.aligned;" ::: "memory");
#define LAUNCHES const uint32_t launches = ld_relaxed32(G->hint[7][blockIdx.x >> 4])
#define EPOCH ((__shfl_sync(~0u, launches, 0) >> 7) + 1)
  if (wg < 2) {
    asm volatile("setmaxnreg.inc.sync.aligned.u32 224;");
    LAUNCHES;
    uint32_t par = launches;
    {
      float acc[128];
      uint32_t A[64];
#pragma unroll
      for (int i = 0; i < 64; i++) asm volatile("" : "=r"(A[i]));
      int c = wg;
#pragma unroll 1
      for (uint64_t prog = P.prog[wg]; prog; prog >>= 8) {
        REGION_IDS;
        const int s = prog & 7;
        if (s < 5) short_conv(G, base, s, w, par, P.xh);
        if (prog == P.prog[wg]) cluster_wait();
        if (prog & 16) {
          mbar_wait(BAR(B_QTD));
          mbar_wait(BAR(B_WM));
          mod_gemv<5>(G, OFF_WM, TA + (bid >> 3), bid & 7, w, lane, ~par >> 7 & 1);
          arrive1(BAR(B_G));
        }
        if (prog & 8) q_stats(base, w);
        if (prog & 32) {
          const int L = 16 * w + (lane >> 2) + 2 * (lane & 3) - 7;
          const uint32_t fo = base + ((L & 1) ? F_O + 2 * (L + 1) : F_E + 2 * L);
          mbar_wait(BAR(B_FRDY + c));
          cload<0, 0>(A, fo + tab(T_F, c));
          cload<15, 1>(A, fo + tab(T_F, c));
          arrive1(BAR(B_FL + c));
        }
        if (!(prog & 64)) continue;
        uint32_t xo;
#pragma unroll 1
        for (int it = 0; it < SPIN_LIMIT; it++) {
          xo = tab(T_X, opaque(c));
          mbar_wait(BAR(B_XR + c), it & 1);
          const uint32_t tag = lds32(base + xo + 32 * i0);
          wg_fence();
          csteps<0, 0>(acc, A, mkdesc(DB + xo, 16, 128, 0));
          csteps<15, 6>(acc, A, mkdesc(DB + xo, 16, 128, 0));
          wg_commit();
          if (bar_all(1 + wg, (tag ^ par >> 7) & 1)) break;
          wg_wait<0>();
          if (w == 0 && elect()) { mbar_expect_tx(BAR(B_XR + c), 4096); bulk_load(base + xo, G->xr + (128 * c + bid) * 256, 4096, BAR(B_XR + c)); }
        }
        wg_fence();
        csteps<5, 1>(acc, A, mkdesc(DB + tab(T_X, opaque(c)), 16, 128, 0));
        wg_commit();
        mbar_wait(BAR(opaque(B_SC + (c == 2 ? 3 : c))));
        wg_wait<0>();
        fence_regs(acc);
        const uint32_t pb = base + tab(T_P, c) + 4096 * w;
#pragma unroll
        for (int k = 0; k < 8; k++) {
          uint32_t p[4];
#pragma unroll
          for (int e = 0; e < 4; e++) { const int i = 4 * k + e; p[e] = i < 31 ? pack_bf16(acc[4 * i] + acc[4 * i + 6], acc[4 * i + 1] + acc[4 * i + 7]) : pack_bf16(acc[124], acc[125]); }
          if (k == 0 && (lane & 3) < w) p[0] = 0;
          stmatrix_x4_t(k == 0 ? pb + 16 * ((255 - lane + 2 * w) & 255) : pb + 16 * (255 - lane + 2 * w) - 512 * k, p[0], p[1], p[2], p[3]);
        }
        arrive1(BAR(B_PFULL + c));
        c += 2;
      }
    }
    par = ~par >> 7 & 1;
    const uint32_t ao = ((blockIdx.x ^ wg) & 1) * UNIT;
    uint32_t ck;
    { REGION_IDS; ck = base + ao + lane * 128 + (((2 * w) ^ (lane & 7)) << 4); }
    const uint32_t abd = DB + ao;
    auto tags = [&](int as, bool first) { return (lds32(ck + as) ^ par) | (lds32(ck + as + (first ? 4096 : 256)) ^ par); };
    int role;
    { int h, j, r; ffn_role(h, j, r); role = (2 * r + (h ^ wg)) * 8 + 4 * h + j; }
    auto a_tile = [&](int as, int n, bool first) {
#pragma unroll 1
      for (int it = 0; __any_sync(~0u, tags(as, first) & 1) && it < SPIN_LIMIT; it++) {
        if (elect()) {
          mbar_expect_tx(BAR(B_RETRY + wid), UNIT);
          if (first) tma2d(base + ao + as, &maps.xs, 8 * role & ~63, 64 * n, BAR(B_RETRY + wid));
          else bulk_load(base + as, G->hh + ((role & ~3) + ((role + n) & 3)) * 1536 + (n >> 2) * 512, UNIT, BAR(B_RETRY + wid));
        }
        mbar_wait(BAR(B_RETRY + wid), par >> 1);
        par ^= 2;
      }
    };
    float acc[128], acb[64];
    int ws = 0;
    float d[8];
    uint32_t *ud0, *ud1;
    unsigned* uh;
    {
      REGION_IDS;
      const int r = role >> 4, row = (r & 14) + (lane >> 2 & 1);
      ud0 = &G->uv[role & 7][32 * row + 4 * ((2 * w ^ row) & 7) + (lane & 3)];
      ud1 = ud0 + 512 * w_block(r & 1, 2);
      ud0 += 512 * w_block(r & 1, wg);
      uh = G->hint[8][role & 7];
      asm volatile("" : "+l"(ud0), "+l"(ud1), "+l"(uh));
    }
    auto step = [&](int n, int uv) {
      const int as = a_at(n);
      const uint64_t da = mkdesc(abd + as, 16, 1024, 1), db = mkdesc(DB + OFF_R + ws, 4096, 1024, 1);
      mbar_wait(BAR(B_FULL + 2 * n));
      a_tile(as, n, true);
      if (uv == 1) { mbar_wait(BAR(B_UVB)); mbar_wait(BAR(B_CO)); }
      wg_fence();
#pragma unroll
      for (int k = 0; k < 4; k++) {
        wg_ss64_11(acc + 96, da + 128 * k, db + 768 + 128 * (k & 1) + 1024 * (k >> 1), k ? 1 : n);
        if (k == GA - 1) { wg_commit(); wg_wait<1>(); if (elect()) mbar_arrive(BAR(B_EMPTY + 2 * n - 1)); if (uv == 2) fence_regs(d); }
      }
      if (uv == 1) {
#pragma unroll
        for (int k = 0; k < 5; k++) {
          wg_ss8_10(d, mkdesc(DB + OFF_UV + 2048 * wg + 6144 * k, 16, 1024, 1), mkdesc(DB + OFF_CO + 64 * k, 32, 128, 0), k);
        }
        if (!wg) {
#pragma unroll
          for (int k = 0; k < 5; k++) wg_ss8_10(d + 4, mkdesc(DB + OFF_UV + 4096 + 6144 * k, 16, 1024, 1), mkdesc(DB + OFF_CO + 64 * k, 32, 128, 0), k);
        }
      }
#pragma unroll
      for (int k = 0; k < 4; k++) wg_ss192_11(acc, da + 128 * k, db + 128 * (k & 1) + 1024 * (k >> 1), k ? 1 : n);
      wg_commit();
      ws = ws == 4 * WSLOT ? 0 : ws + 2 * WSLOT;
      if (uv == 2) {
        split(P.ulo, 30);
        REGION_IDS;
        const uint32_t tag = !(lane & 3);
        if (elect()) red_hint(uh);
        uint32_t x[4];
#pragma unroll
        for (int k = 0; k < 4; k++) asm volatile("movmatrix.sync.aligned.m8n8.trans.b16 %0, %1;" : "=r"(x[k]) : "r"(pack_bf16(d[2 * k], d[2 * k + 1])));
        const uint32_t y1 = __shfl_up_sync(~0u, x[1], 8), y3 = __shfl_up_sync(~0u, x[3], 8);
        if (lane < 16) {
          st_relaxed32((uint32_t*)((uint64_t)ud0 ^ 2 * (lane & 8)), set_tag(lane < 8 ? x[0] : y1, tag, par));
          if (!wg) st_relaxed32((uint32_t*)((uint64_t)ud1 ^ 2 * (lane & 8)), set_tag(lane < 8 ? x[2] : y3, tag, par));
        }
      }
    };
#pragma unroll 1
    for (int n = 0; n < UVS; n++) step(n, 0);
    step(UVS, 1);
    step(UVS + 1, 2);
#pragma unroll 1
    for (int n = UVS + 2; n < 10; n++) step(n, 0);
    float o[80];
    uint32_t fr[3][16], bo;
    {
      REGION_IDS;
      float r0, r1, s0, s1;
      const int id = role, j = role;
      uint4* const hdst = G->hh + id * 1536 + 128 * w + (lane ^ lane >> 3);
      const uint32_t keep = ~(~lane & 1), bit = par & ~keep;
      bo = 1024 + ((j & 1) << 23);
      auto own = [&](int i) { wg_rs160_1(o, fr[i >> 2] + 4 * (i & 3), mkdesc(DB + w2_at(i / 4) + (i & 3) * 2048, UNIT, bo, 1), i); };
      auto hint = [&](int v) { asm volatile("{.reg .pred p; setp.eq.u32 p, %1, 0; @p red.relaxed.gpu.global.add.u32 [%0], 1;}" ::"l"(&G->hhf[id * 8 + v]), "r"(lane) : "memory"); };
      auto put = [&](int v, int k) {
        uint32_t* x = fr[v] + 2 * k;
        const uint32_t t0 = (x[k / 2] & keep) | bit, t1 = (x[5 + k / 2] & keep) | bit;
        x[k / 2] = t0; x[5 + k / 2] = t1;
        st_relaxed128(hdst + 512 * v + 8 * k, x[0], x[2], x[4], x[6]);
        st_relaxed128(hdst + 512 * v + 8 * k + 64, x[1], x[3], x[5], x[7]);
      };
      auto move = [&](uint32_t* x, int n) {
#pragma unroll
        for (int k = 0; k < n; k++) asm volatile("mul.rn.f32 %0, %0, %1;" : "+r"(x[k]) : "f"(P.one));
      };
      auto act = [&](int i) {
        const int v = i >> 3, k = 7 - (i & 7);
        const float *g = v < 2 ? acc + 32 * v + 4 * k : acb + 4 * k, *up = g + (v < 2 ? 64 : 32);
        fr[v][2 * k] = pack_bf16(silu2(g[0], r0, s0) * up[0], silu2(g[1], r0, s0) * up[1]);
        fr[v][2 * k + 1] = pack_bf16(silu2(g[2], r1, s1) * up[2], silu2(g[3], r1, s1) * up[3]);
        if (!(k & 3)) { put(v, k); if (!k && !(HL >> v & 1)) hint(v); if (i == 15) { move(fr[0], 16); } }
        else asm volatile("" : "+r"(fr[v][2 * k]), "+r"(fr[v][2 * k + 1]));
      };
#pragma unroll
      for (int v = 0; v < 10; v++) {
        mbar_wait(BAR(B_FULL + 20 + v));
        if (v == XP) {
          mbar_wait(BAR(B_EXT));
          wg_fence();
          wg_ss192_01(acc, mkdesc(DB + OFF_AX + 1024 * opaque(wg), 0, 128, 0), mkdesc(DB + OFF_BX, 2048, 1024, 1), 1);
          wg_ss64_01(acc + 96, mkdesc(DB + OFF_AX + 1024 * opaque(wg), 0, 128, 0), mkdesc(DB + OFF_BX + 6144, 2048, 1024, 1), 1);
          wg_commit();
          r0 = 0.5f * __uint_as_float(lds32(base + OFF_RT + 256 * wg + 64 * w + (lane & 28)));
          r1 = 0.5f * __uint_as_float(lds32(base + OFF_RT + 256 * wg + 64 * w + 32 + (lane & 28)));
          s0 = 2.f * r0 * r0;
          s1 = 2.f * r1 * r1;
        }
        wg_fence();
#pragma unroll
        for (int k = 0; k < 4; k++) {
          wg_ss128_11(acb, mkdesc(opaque(abd) + a_at(second(v)) + k * 2048, 16, 1024, 1), mkdesc(DB + OFF_R + WSLOT * ((v + 2) % 6) + k * 2048, UNIT, 1024, 1), v + k);
          if (k == GB - 1) { wg_commit(); wg_wait<1>(); if (v == XP) fence_regs(acc); if (elect()) mbar_arrive(BAR(B_EMPTY + 19 + v)); }
        }
        if (v == 9) wg_ss128_01(acb, mkdesc(DB + OFF_AX + 1024 * opaque(wg), 0, 128, 0), mkdesc(DB + OFF_BX + UNIT, 2048, 1024, 1), 1);
        wg_commit();
        split(P.ulo, v);
        if (v == XP + NP / 2 && (HL & 1)) hint(0);
        if (v == XP + NP && (HL & 2)) hint(1);
#pragma unroll
        for (int i = 0; i < 16; i++) if (v >= XP && i * NP / 16 == v - XP) act(i);
      }
#pragma unroll
      for (int v = 0; v < 3; v++) {
        mbar_wait(BAR(B_FULL + 30 + v));
        wg_fence();
#pragma unroll
        for (int i = 0; i < 4; i++) {
          own(4 * v + i);
          if (i == GB - 1) { wg_commit(); wg_wait<1>(); if (v == 0) fence_regs(acb); if (elect()) mbar_arrive(BAR(B_EMPTY + 29 + v)); }
        }
        wg_commit();
        split(P.ulo, 10 + v);
        if (v == 0 && XP + NP == 10 && (HL & 2)) hint(1);
        if (v == 2 && (HL & 4)) hint(2);
#pragma unroll
        for (int i = 0; i < 4; i++) if (v < 2) act(16 + 4 * v + i);
      }
      ck = base + 2048 * w + 516 * (lane >> 3) + 144 * (lane >> 2 & 1) + 32 * (lane & 3);
    }
    uint32_t x1[40], gb[20];
    if (!wg) {
      REGION_IDS;
      mbar_wait(BAR(B_GB));
#pragma unroll
      for (int k = 0; k < 5; k++) {
        const uint4 g = lds128(base + OFF_GB + 80 * (lane & 3) + 16 * k);
        gb[4 * k] = g.x; gb[4 * k + 1] = g.y; gb[4 * k + 2] = g.z; gb[4 * k + 3] = g.w;
      }
    }
#pragma unroll 1
    for (int u = 33; u < (wg ? 42 : SPL); u++) {
      const int x = P.hid[wg][u - 33], as = x & ~15;
      const uint64_t wd = mkdesc(0, 0, bo, 1) | P.w2t[u - 30].x;
      mbar_wait(BAR(wg || u < 38 ? B_FULL + u : B_LAST + u - 38));
      a_tile(as, x & 15, false);
      if (wg || u < 38) {
        wg_fence();
#pragma unroll
        for (int kk = 0; kk < 4; kk++) {
          wg_ss160_01(o, mkdesc(DB + as + kk / 2 * 512 + (kk & 1) * 32, 16, 1024, 2), wd + kk * 128, 1);
          if (kk == GB - 1) { wg_commit(); wg_wait<1>(); if (elect()) mbar_arrive(BAR(B_EMPTY + u - 1)); }
        }
        wg_commit();
        if (u == 41 && elect()) mbar_arrive(BAR(B_LAG));
      }
      if (u == 38 - 1 && !wg) {
        REGION_IDS;
        const uint32_t xa = base + (lane >> 4) * 1024 + (lane & 7) * 128 + (((2 * w + ((lane >> 3) & 1)) ^ (lane & 7)) << 4);
        mbar_wait(BAR(B_FULL + 42));
        wg_wait<0>();
        if (elect()) mbar_arrive(BAR(B_EMPTY + 38 - 1));
#pragma unroll
        for (int k = 0; k < 10; k++) ldmatrix_x4_t(x1 + 4 * k, xa + x1_at(k / 2) + (k & 1) * 2048);
      }
    }
    REGION_IDS;
    const int h = role >> 2 & 1, j = role & 3;
    const uint32_t xb = base + OFF_XCH + 5120 * w;
    if (wg) {
      const uint32_t rdst = mapa(xb + 16 * lane, h ^ 1), rbar = mapa(BAR(B_FULL + 1), h ^ 1);
      mbar_wait(BAR(B_XFREE));
      wg_wait<0>();
      fence_regs(o);
#pragma unroll
      for (int k = 0; k < 10; k++)
        asm volatile("st.async.shared::cluster.mbarrier::complete_tx::bytes.v4.b32 [%0], {%1,%2,%3,%4}, [%5];" ::"r"(rdst + 512 * k), "r"(pack_bf16(o[8 * k], o[8 * k + 1])),
                     "r"(pack_bf16(o[8 * k + 2], o[8 * k + 3])), "r"(pack_bf16(o[8 * k + 4], o[8 * k + 5])), "r"(pack_bf16(o[8 * k + 6], o[8 * k + 7])), "r"(rbar + 16 * (k / 4)) : "memory");
    } else {
      mbar_wait(BAR(B_LAG));
      wg_fence();
#pragma unroll
      for (int i = 152; i < 4 * SPL; i++) wg_ss160_01(o, mkdesc(DB + hid_at(i / 4 - 33, 0) + (i & 2) * 256 + (i & 1) * 32, 16, 1024, 2), mkdesc(DB + w2_at(i / 4 - 30) + (i & 3) * 2048, UNIT, bo, 1), 1);
      wg_commit();
#pragma unroll 1
      for (int u = SPL; u < 42; u++) {
        const int x = P.hid[0][u - 33];
        mbar_wait(BAR(B_LAST + u - 38));
        a_tile(x & ~15, x & 15, false);
      }
      wg_fence();
#pragma unroll
      for (int i = 4 * SPL; i < 168; i++) wg_ss160_01(o, mkdesc(DB + hid_at(i / 4 - 33, 0) + (i & 2) * 256 + (i & 1) * 32, 16, 1024, 2), mkdesc(DB + w2_at(i / 4 - 30) + (i & 3) * 2048, UNIT, bo, 1), 1);
      wg_commit();
      const int row = (8 * role & ~63) + 16 * w;
      auto merge = [&](int e0, int e1) {
#pragma unroll
        for (int e = e0; e < e1; e++) {
          if (e % 4 == 0) mbar_wait_cluster(BAR(B_FULL + 1 + e / 2));
          const uint4 p = lds128(xb + 16 * lane + 512 * e);
          x1[4 * e] = bfma2(gb[2 * e], p.x, x1[4 * e]); x1[4 * e + 1] = bfma2(gb[2 * e], p.y, x1[4 * e + 1]);
          x1[4 * e + 2] = bfma2(gb[2 * e + 1], p.z, x1[4 * e + 2]); x1[4 * e + 3] = bfma2(gb[2 * e + 1], p.w, x1[4 * e + 3]);
        }
        __syncwarp();
      };
      merge(0, MG);
      wg_wait<0>();
      fence_regs(o);
#pragma unroll
      for (int k = 0; k < 10; k++) {
        if (k >= MG && k % 4 == 0) merge(k, k < 8 ? k + 4 : 10);
        uint32_t y[4];
#pragma unroll
        for (int e = 0; e < 4; e++) y[e] = bfma2(gb[2 * k + e / 2], pack_bf16(o[8 * k + 2 * e], o[8 * k + 2 * e + 1]), x1[4 * k + e]);
        stmatrix_x4(k < 8 ? xb + 2048 * (k >> 2) + (lane & 15) * 128 + (((2 * (k & 3) + (lane >> 4)) ^ (lane & 7) ^ 4 * (j & 1)) << 4)
                          : xb + 4096 + (lane & 15) * 64 + (((2 * (k & 1) + (lane >> 4)) ^ (lane >> 1 & 3)) << 4), y[0], y[1], y[2], y[3]);
        if ((SG >> k & 1) || k == 9) {
          fence_async_smem();
          __syncwarp();
#pragma unroll
          for (int b = 0; b < 3; b++) {
            const int e = b < 2 ? 4 * b + 3 : 9;
            if (e <= k && !(SG & ((1 << k) - 1) & ~((1 << e) - 1)) && lane == 0) tma2d_store(b < 2 ? &maps.outa : &maps.outb, b < 2 ? 128 * j + 64 * b : 512 + 32 * j, row, xb + 2048 * b);
          }
        }
      }
      if (lane == 0) { bulk_commit(); bulk_wait_read(); }
    }
  } else if (wg == 2) {
    asm volatile("setmaxnreg.dec.sync.aligned.u32 40;");
    mbar_init<15>(BAR(B_FULL + 15 * w), 1);
    mbar_init<11>(BAR(B_EMPTY - 1 + 11 * w), 8);
    mbar_init<1>(BAR(B_LAST + w), 1);
    asm volatile("fence.mbarrier_init.release.cluster;" ::: "memory");
    LAUNCHES;
    silu_vector(P.c + 80 * (blockIdx.x & 7) - 512, 296, base - 1024);
    const uint32_t epoch = EPOCH;
    if (w == 2) rank_pair(G, base, epoch, true);
    cluster_wait();
    {
      REGION_IDS;
      const uint32_t tag = opaque(~lane & 1);
      auto q_t = [&]() {
        const int tr = 4 * (lane & 1) + (lane >> 1 & 3);
        uint32_t a = base + OFF_Q + 128 * ((lane & 24) + tr) + ((w ^ tr) << 4);
        uint4* dst = G->qt + (64 * (bid & 1) + 8 * w + (lane >> 2)) * 256 + 4 * (bid >> 1) + (lane & 3);
#pragma unroll 1
        for (int c = 0; c < 5; c++) {
          mbar_wait(BAR(B_Q + c));
#pragma unroll
          for (int k = 0; k < 2; k++) {
            uint32_t x[4];
            ldmatrix_x4_t(x, a ^ (64 * k));
            st_relaxed128(dst + 8192 * k, set_tag(x[0], tag, epoch), x[1], x[2], x[3]);
          }
          a += 4096;
          dst += 32768;
        }
        arrive1(BAR(B_QTD));
      };
      q_t();
      if (w == 3) {
        mbar_wait_cluster(BAR(B_ST1));
        if (lane < 8) red_hint(G->hint[5][lane]);
        const uint2 x = lds64(base + OFF_ST + 8 * (lane & 15)), y = lds64(base + OFF_ST + 128 + 8 * (lane & 15));
        float m, sd;
        ln_final(__uint_as_float(x.x) + __uint_as_float(y.x), __uint_as_float(x.y) + __uint_as_float(y.y), m, sd);
        sd = rbf(rcpf(sd));
        const uint32_t mr = pack_bf16(sd, -rbf(m) * sd), tg = lane & 7 ? 0 : lane & 8 ? 1 : 0x8000;
        const uint32_t o = __byte_perm(__shfl_sync(~0u, mr, 2 * lane & 14), __shfl_sync(~0u, mr, (2 * lane & 14) + 1), (lane & 8) ? 0x7632 : 0x5410);
        if (lane < 16) st_relaxed32(&G->st1[lane >> 3][8 * bid + (lane & 7)], (o & ~tg) | ((epoch & 1) * tg));
      }
      if (w == 2) rank_pair(G, base, epoch, false);
      if (w == 1) mod_fetch(G, base, epoch, M8, 0, 1);
    }
    {
      REGION_IDS;
      const uint32_t tag = opaque(~lane & 1), sa = opaque(base + 16 * i0);
      uint4 q[2];
      mbar_wait(BAR(B_PFULL));
#pragma unroll 1
      for (uint32_t a = sa + tab(T_P, 0); a < sa + tab(T_P, 0) + 4096; a += 2048) {
        uint4 y = lds128(a), z = lds128(a + 4096), u = lds128(a + 8192);
        const uint4 v = lds128(a + 12288);
        add4(y, z); add4(u, v); add4(y, u);
        sts128(a, y.x, y.y, y.z, y.w);
      }
      uint4* gp = G->xs + 256 * bid + (sa - base >> 4);
      q[0] = ld_relaxed128(gp - D_ * 256);
      q[1] = ld_relaxed128(gp - D_ * 256 + 128);
      mbar_wait(BAR(B_MR));
      e_round<true>(G, base, sa, gp, q, 0, w, tag, epoch);
#pragma unroll 1
      for (int c = 1; c < 5; c++) e_round<false>(G, base, sa, gp, q, c, w, tag, epoch);
    }
    int h, j, r;
    ffn_role(h, j, r);
    arrive1(BAR(B_ED));
    {
      REGION_IDS;
      float s0 = 0.f, q0 = 0.f, s1 = 0.f, q1 = 0.f;
#pragma unroll 1
      for (int c = 2; c < 5; c++) {
        const uint32_t buf = base + OFF_SX + 4096 * (c - 2), b = BAR(B_SX + c);
        uint32_t x[8];
#pragma unroll 1
        for (int it = 0; it < SPIN_LIMIT; it++) {
          mbar_wait(b, it & 1);
#pragma unroll
          for (int i = 0; i < 8; i++) x[i] = lds32(buf + 1024 * w + 4 * lane + 128 * i);
          if (bar_all(3, (lane & 7) || min(min(min(x[0], x[1]), min(x[2], x[3])), min(min(x[4], x[5]), min(x[6], x[7]))))) break;
          if (w == 0 && elect()) { mbar_expect_tx(b, 4096); tma2d(buf, &maps.x1s, 128 * r + 64 * h, D_ * (epoch & 1) + 128 * c + 32 * j, b); }
        }
#pragma unroll
        for (int i = 0; i < 8; i++) { const float lo = bf_lo(x[i]), hi = bf_hi(x[i]); s0 += lo; q0 = fmaf(lo, lo, q0); s1 += hi; q1 = fmaf(hi, hi, q1); }
      }
      sts128(base + OFF_MR + 1024 * w + 16 * lane, __float_as_uint(s0), __float_as_uint(q0), __float_as_uint(s1), __float_as_uint(q1));
      arrive1(BAR(B_S2));
    }
    {
      REGION_IDS;
      const uint32_t* sp = &G->st2[2 * r + (h ^ (w >> 1))][0][2 * (i0 & 63)];
      uint2 x[4];
      int it;
#pragma unroll 1
      for (it = 0; it < SPIN_LIMIT; it++) {
        mbar_wait(BAR(B_BX), it & 1);
        uint32_t y = 0;
#pragma unroll
        for (int k = 0; k < 3; k++) y |= lds32(base + OFF_BX + 32 * i0 + 4096 * k) ^ epoch;
        if (bar_all(3, !(y & 1))) break;
        if (w == 0 && elect()) { mbar_expect_tx(BAR(B_BX), 12288); bulk_load(base + OFF_BX, G->uv[4 * h + j], 12288, BAR(B_BX)); }
      }
      it = 0;
#pragma unroll 1
      do {
#pragma unroll
        for (int k = 0; k < 4; k++) x[k] = ld_relaxed64(sp + 128 * k);
      } while (__any_sync(~0u, ((x[0].x ^ epoch) | (x[1].x ^ epoch) | (x[2].x ^ epoch) | (x[3].x ^ epoch)) & 1) && ++it < SPIN_LIMIT);
      float m, sd;
      ln_final((__uint_as_float(x[0].x) + __uint_as_float(x[1].x)) + (__uint_as_float(x[2].x) + __uint_as_float(x[3].x)),
               (__uint_as_float(x[0].y) + __uint_as_float(x[1].y)) + (__uint_as_float(x[2].y) + __uint_as_float(x[3].y)), m, sd);
      const uint32_t e = pack_bf16(-m, sd);
      sts128(base + OFF_AX + 16 * i0, e, e, e, e);
      sts32(base + OFF_RT + 4 * i0, __float_as_uint(rcpf(sd)));
      fence_async_smem();
      arrive1(BAR(B_EXT));
      {
        uint2 g0, g1;
        int it = 0;
#pragma unroll 1
        do {
          g0 = ld_relaxed64(&G->modv[1][128 * j + i0]);
          g1 = ld_relaxed64(&G->modv[1][512 + 32 * j + lane]);
        } while (__any_sync(~0u, ((g0.x ^ epoch) | (g0.y ^ epoch) | (g1.x ^ epoch) | (g1.y ^ epoch)) & 1) && ++it < SPIN_LIMIT);
        const uint32_t a = base + OFF_GB + 40 * (lane & 6) + 2 * (lane & 1) + (lane >> 3) * 4;
        asm volatile("st.shared.u16 [%0], %1; st.shared.u16 [%2], %3;" ::"r"(a + 16 * (w ^ (j & 1))), "h"((uint16_t)(mod_sum(g0) >> 16)), "r"(a + 64), "h"((uint16_t)(mod_sum(g1) >> 16)) : "memory");
        arrive1(BAR(B_GB));
      }
#pragma unroll 1
      for (int m = w < 3 ? w : 5; m < 9; m += w < 3 ? 3 : 1) {
        const int x = P.hid[0][m], id = 16 * r + 4 * h + ((j + x) & 3), q = x >> 2 & 3;
        const uint4* src = G->hh + id * 1536 + 512 * q;
        it = 0;
#pragma unroll 1
        while (w < 3 && __any_sync(~0u, ld_relaxed32(&G->hhf[8 * id + 64 * (lane & 1) + q]) != 4 * epoch) && ++it < SPIN_LIMIT);
        mbar_wait(BAR(w < 3 ? P.hid[2][m] : P.hid[3][m]));
        if (elect()) {
          if (w < 3) bulk_load(base + (P.hid[1][m] & ~15), src + 8 * 1536 * (h ^ 1), UNIT, BAR(B_FULL + 33 + m));
          else mbar_expect_tx(BAR(B_LAST + m - 5), UNIT);
          if (w == 3 || m < 5) bulk_load(base + (x & ~15), src + 8 * 1536 * h, UNIT, BAR(w < 3 ? B_FULL + 33 + m : B_LAST + m - 5));
        }
      }
    }
  } else {
    asm volatile("setmaxnreg.dec.sync.aligned.u32 24;");
    if (w >= 2) {
      LAUNCHES;
      uint32_t epoch;
      {
        REGION_IDS;
        uint32_t dv;
        asm volatile("ld.global.nc.u16 %0, [%1];" : "=r"(dv) : "l"(P.ssmd + 128 * (lane & 7) % D_ + bid));
        if (lane < 5) sts128(base + tab(T_F, lane) + (w & 1) * (F_O - F_E) + F_E - 16, 0, 0, 0, 0);
        epoch = EPOCH;
        __syncwarp();
#pragma unroll 1
        for (int c = 0; c < 5; c++) {
          const float d = i0 == 64 ? bf_lo(dv) : 0.f;
          dv = __shfl_down_sync(~0u, dv, 1);
          const uint32_t a = base + tab(T_F, c) + 16 * (i0 - 64);
          mbar_wait(BAR(B_FRAW + c));
#pragma unroll
          for (int k = 0; k < 4; k++) {
            uint4 x = lds128(a + F_E + 1024 * k);
            const uint32_t pv = lds32(a + F_E - 4 + 1024 * k);
            if (k == 0) { x.x = pack_bf16(bf_lo(x.x) + d, bf_hi(x.x)); sts32(a + F_E, x.x); }
            sts128(a + F_O + 1024 * k, __byte_perm(pv, x.x, 0x5432), __byte_perm(x.x, x.y, 0x5432), __byte_perm(x.y, x.z, 0x5432), __byte_perm(x.z, x.w, 0x5432));
          }
          __syncwarp();
          if (elect()) mbar_arrive2(BAR(B_FRDY + c));
          if (c == 0 && w == 3) {
#pragma unroll 1
            for (int k = 0; k < 13; k++) prefetch_map(&maps.w1a + k);
          }
        }
      }
      REGION_IDS;
      int h, j, r;
      ffn_role(h, j, r);
      cluster_wait();
      if (w == 2) {
        const unsigned* fp = G->xsh[lane < 10 ? lane >> 1 : 0][(r & 6) + (lane & 1)];
        uint32_t rdy = 0;
        mbar_wait(BAR(B_SC + 4));
#pragma unroll 1
        for (int e = 0; e < 14; e++) {
          const uint32_t x = P.adep[e], n = x >> 21 & 15, s = base + (x >> 25 << 13), b = BAR(B_FULL + (x >> 16 & 31));
          mbar_wait(BAR(opaque(x & 255)));
          mbar_wait(BAR(opaque(x >> 8 & 255)));
          const uint32_t f = BAR(B_FULL + 7 + 2 * (e < 7 ? e : e - 7));
          if (elect()) mbar_arrive_remote(mapa(f, h ^ 1));
#pragma unroll 1
          for (int it = 0; !(rdy >> n & 1) && it < SPIN_LIMIT; it++) rdy = __ballot_sync(~0u, ld_relaxed32(fp) == 64 * epoch);
          mbar_wait(f, e >= 7);
          if (elect()) asm volatile("cp.async.bulk.tensor.2d.shared::cluster.global.mbarrier::complete_tx::bytes.multicast::cluster [%0], [%1, {%3,%4}], [%2], %5;"
                                    ::"r"(s + UNIT * h), "l"(&maps.xs), "r"(b), "r"(128 * r + 64 * h), "r"(64 * n), "h"((uint16_t)3) : "memory");
        }
#pragma unroll 1
        for (int v = 0; v < 12; v++) {
          const int q = v * 11 >> 5, e = v - 3 * q, k32 = 24 * h + (q ? 6 * ((j + 1 + e) & 3) + 2 * q - 2 : 6 * j + 2 * e);
          const uint2 x = P.w2t[v];
          mbar_wait(BAR(x.y));
          if (elect()) {
            mbar_expect_tx(BAR(B_FULL + 30 + v), W2TILE + (v >= 8 ? UNIT : q ? 2 * UNIT : 0));
#pragma unroll
            for (int k = 0; k < 3; k++) tma5d(base - DB + 16 * (x.x & 0xFFFF) + UNIT * k, &maps.w2a + (q > 0), k < 2 ? 128 * j + 64 * k : 512 + 32 * (j & 2), k32, BAR(B_FULL + 30 + v));
          }
        }
      } else {
        float s0 = 0.f, q0 = 0.f, s1 = 0.f, q1 = 0.f;
        uint32_t nl = 0, np = 0, ph = 0;
#pragma unroll 1
        for (uint32_t seq = 0x94; seq > 1; seq >>= 1) {
          const uint32_t c = seq & 1 ? np : nl, buf = base + OFF_SX + 4096 * (c < 4 ? c & 1 : 2), b = BAR(opaque(B_SX + c));
          int it = 0;
          if (seq & 1) {
            mbar_wait(b, ph >> c & 1);
            ph ^= 1 << c;
            const uint32_t a = buf + 32 * lane;
            if (__all_sync(~0u, min(min(lds32(a), lds32(a + 1024)), min(lds32(a + 2048), lds32(a + 3072)))) || ph > SPIN_LIMIT) {
#pragma unroll 1
              for (uint32_t o = buf + 4 * lane; o < buf + 4096; o += 1024) {
                uint32_t x[8];
#pragma unroll
                for (int i = 0; i < 8; i++) x[i] = lds32(o + 128 * i);
#pragma unroll
                for (int i = 0; i < 8; i++) { const float lo = bf_lo(x[i]), hi = bf_hi(x[i]); s0 += lo; q0 = fmaf(lo, lo, q0); s1 += hi; q1 = fmaf(hi, hi, q1); }
              }
              np++;
              continue;
            }
            ph += 4;
            seq = 2 * seq + 1;
          } else {
#pragma unroll 1
            while (__any_sync(~0u, ld_relaxed32(G->xsh[c][(r & 6) + (j >> 1)]) != 64 * epoch) && ++it < SPIN_LIMIT);
            if (++nl == 5) mbar_wait(BAR(B_PEMPTY + 4));
          }
          if (elect()) { mbar_expect_tx(b, 4096); tma2d(buf, &maps.x1s, 128 * r + 64 * h, D_ * (epoch & 1) + 128 * c + 32 * j, b); }
        }
        mbar_wait(BAR(B_S2));
#pragma unroll
        for (int k = 0; k < 4; k++) {
          const uint4 x = lds128(base + OFF_MR + 1024 * k + 16 * lane);
          s0 += __uint_as_float(x.x); q0 += __uint_as_float(x.y); s1 += __uint_as_float(x.z); q1 += __uint_as_float(x.w);
        }
        asm volatile("{.reg .b128 t, x; .reg .b64 a, b; mov.b64 a, {%1,%2}; mov.b64 b, {%3,%4}; mov.b128 x, {a,b}; atom.relaxed.gpu.global.exch.b128 t, [%0], x;}"
                     ::"l"(&G->st2[2 * r + h][j][4 * lane]), "r"((__float_as_uint(s0) & ~1u) | (epoch & 1)), "f"(q0), "r"((__float_as_uint(s1) & ~1u) | (epoch & 1)), "f"(q1) : "memory");
        mbar_wait(BAR(B_EMPTY + 2 * UVS + 1));
        sts128(base + OFF_CO + 16 * lane, 0, 0, 0, 0);
        fence_async_smem();
        __syncwarp();
        if (elect()) {
#pragma unroll 1
          for (int k = 0; k < 40; k++) asm volatile("cp.async.bulk.global.shared::cta.bulk_group [%0], [%1], 512;" ::"l"(G->x1[~epoch & 1] + 1280 * blockIdx.x + 32 * k), "r"(base + OFF_CO) : "memory");
          bulk_commit();
          bulk_wait_read();
        }
      }
    } else if (w == 0) {
      LAUNCHES;
      uint32_t epoch;
      {
        REGION_IDS;
        const unsigned* hp = G->hint[0][4 * (bid >> 6) + (bid >> 3 & 3)];
        uint32_t v = ld_relaxed32(hp + 256 * min(lane, 5));
        if (lane < 3) sts128(base + tab(T_X, lane) + 4096, 0, 0, 0, 0);
        if (lane && lane <= B_WM) mbar_expect_tx(BAR(lane), lane < B_FRAW ? 9728 : lane == B_WM ? 10240 : 4096);
        epoch = EPOCH;
        fence_async_smem();
        const uint32_t rdy = __ballot_sync(~0u, v == epoch << 6) & 31;
        uint32_t nx = 0, mr = 1;
#pragma unroll 1
        for (int it = 0; (nx < 5 || mr) && it < SPIN_LIMIT; it++) {
          const bool second = nx == 5 || (lane && mr && nx >= P.mq);
          if (!(rdy >> nx & 1)) v = ld_relaxed32(hp + 256 * (second ? 5 : nx));
          const uint32_t ok = __ballot_sync(~0u, v == epoch << (second ? 7 : 6)) | (rdy >> nx & 1);
          if (nx < 5 && (ok & 1)) {
            if (nx >= 3) mbar_wait(BAR(B_PFULL - 3 + nx));
            if (elect()) { mbar_expect_tx(BAR(B_XR + nx), 4096); bulk_load(base + tab(T_X, nx), G->xr + (128 * nx + bid) * 256, 4096, BAR(B_XR + nx)); }
          }
          if (mr && (nx == 5 || nx >= P.mq) && (ok & 2) && !(rdy >> nx & 1)) {
            if (elect()) { mbar_expect_tx(BAR(B_MR), 8192); bulk_load(base + OFF_MR, G->st1, 8192, BAR(B_MR)); mbar_arrive(BAR(B_QTOK)); }
            mr = 0;
          }
          if (nx < 5) nx += ok & 1;
        }
        mod_fetch(G, base, epoch, M8, 2, 5);
      }
      REGION_IDS;
      int h, j, r;
      ffn_role(h, j, r);
      cluster_wait();
      if (elect()) mbar_expect_tx(BAR(B_UVB), 30720);
#pragma unroll 1
      for (int k = 0; k < 5; k++) {
        mbar_wait(BAR(opaque(B_EMPTY + nib(P.uvd, k))));
        if (elect()) tma3d(base + OFF_UV + 6144 * k, &maps.w1u + (r & 1), 0, 40 * (r & 14) + 16 * k, 3 * (4 * h + j), BAR(B_UVB));
      }
      mbar_wait(BAR(B_G));
      {
        const uint2* mp = &G->modv[lane & 4 ? 0 : 2][40 * (r & 14) + (lane & 24) + 2 * (lane & 3)];
        uint4 v[3];
        int it = 0;
#pragma unroll 1
        do {
          v[0] = ld_relaxed128(mp); v[1] = ld_relaxed128(mp + 32); v[2] = ld_relaxed128(mp + 64 - (lane & 16));
        } while (__any_sync(~0u, ((v[0].x ^ epoch) | (v[0].y ^ epoch) | (v[0].z ^ epoch) | (v[0].w ^ epoch) | (v[1].x ^ epoch) | (v[1].y ^ epoch) | (v[1].z ^ epoch) | (v[1].w ^ epoch) |
                                  (v[2].x ^ epoch) | (v[2].y ^ epoch) | (v[2].z ^ epoch) | (v[2].w ^ epoch)) & 1) && ++it < SPIN_LIMIT);
#pragma unroll
        for (int i = 0; i < 3; i++)
          sts32(base + OFF_CO + 128 * i + 4 * lane, badd2(pack_bf16(__uint_as_float(v[i].x) + __uint_as_float(v[i].y), __uint_as_float(v[i].z) + __uint_as_float(v[i].w)), lane & 4 ? 0 : 0x3F803F80u));
      }
      fence_async_smem();
      arrive1(BAR(B_CO));
      ffn_role(h, j, r);
      mbar_wait(BAR(B_ED));
      int it = 0;
#pragma unroll 1
      while (__any_sync(~0u, ld_relaxed32(G->hint[8][4 * h + j]) != 128 * epoch) && ++it < SPIN_LIMIT);
      if (elect()) { mbar_expect_tx(BAR(B_BX), 12288); bulk_load(base + OFF_BX, G->uv[4 * h + j], 12288, BAR(B_BX)); }
      asm volatile("fence.acq_rel.gpu;" ::: "memory");
      if (lane < 8) red_hint(G->hint[7][lane]);
      unsigned x;
      it = 0;
#pragma unroll 1
      do { asm volatile("ld.acquire.gpu.global.u32 %0, [%1];" : "=r"(x) : "l"(G->hint[7][bid >> 4]) : "memory"); } while (__any_sync(~0u, x != 128 * epoch) && ++it < SPIN_LIMIT);
      fence_async_all();
      const int ch = D_ * (epoch & 1);
      mbar_wait(BAR(P.xdep));
      if (elect()) {
        mbar_expect_tx(BAR(B_FULL + 42), 20480);
#pragma unroll
        for (int k = 0; k < 4; k++) tma2d(base + x1_at(k), &maps.x1b, 128 * r + 64 * h, ch + 128 * j + 32 * (k ^ (j & 1)), BAR(B_FULL + 42));
        tma2d(base + x1_at(4), &maps.x1b, 128 * r + 64 * h, ch + 512 + 32 * j, BAR(B_FULL + 42));
        mbar_expect_tx(BAR(B_FULL + 1), 8192); mbar_expect_tx(BAR(B_FULL + 3), 8192); mbar_expect_tx(BAR(B_FULL + 5), 4096);
      }
      mbar_wait(BAR(B_EMPTY + 37));
      if (elect()) mbar_arrive_remote(mapa(BAR(B_XFREE), h ^ 1));
    } else {
      LAUNCHES;
      {
        REGION_IDS;
        loads<0>(P, maps, base);
      }
      cluster_wait();
      int h, j, r;
      ffn_role(h, j, r);
      mbar_wait(BAR(B_QTD));
      mbar_wait(BAR(B_STD));
      mbar_wait(BAR(B_SC));
      mbar_wait(BAR(B_SC + 2));
      mbar_wait(BAR(B_FL));
#pragma unroll 1
      for (int u = 0; u < 30; u++) {
        if (u == P.mpos) mod_fetch(G, base, EPOCH, M8, 1, 2);
        if (u < 6) wait_clock(t_start + P.wt0 + u * P.wpace);
        const uint32_t x = P.wdep[u], b = x >> 8 & 1;
        uint32_t s = base + OFF_R + WSLOT * (x >> 9 & 7), f = BAR(B_FULL + (b ? u : u & ~1)), n = x & 0xC000, y = x >> 16, z = 3 * (4 * h + j) + 2 * b;
        const CUtensorMap* m = &maps.w1a + 5 * b;
        asm volatile("{.reg .pred p, q; .reg .b32 i, t; .reg .b64 m; mov.u32 i, 0; add.u32 t, %0, 8192; add.u64 m, %1, 128; elect.sync _|q, 0xffffffff;"
                     "W: mbarrier.try_wait.parity.shared::cta.b64 p, [%6], 0; @p bra.uni D; add.u32 i, i, 1; setp.lt.u32 p, i, %7; @p bra.uni W; D:"
                     "setp.ne.and.u32 p, %3, 0, q; @p mbarrier.arrive.expect_tx.shared::cta.b64 _, [%2], %3;"
                     "@q cp.async.bulk.tensor.3d.shared::cluster.global.mbarrier::complete_tx::bytes [%0], [%1, {0,%4,%5}], [%2];"
                     "@q cp.async.bulk.tensor.3d.shared::cluster.global.mbarrier::complete_tx::bytes [t], [m, {0,%4,%5}], [%2];}"
                     ::"r"(s), "l"(m), "r"(f), "r"(n), "r"(y), "r"(z), "r"(BAR(opaque(x & 255))), "n"(SPIN_LIMIT) : "memory");
      }
    }
  }
}

typedef CUresult (*EncFn)(CUtensorMap*, CUtensorMapDataType, cuuint32_t, void*, const cuuint64_t*, const cuuint64_t*, const cuuint32_t*,
                          const cuuint32_t*, CUtensorMapInterleave, CUtensorMapSwizzle, CUtensorMapL2promotion, CUtensorMapFloatOOBfill);
static int enc_err = 0;
static void enc(EncFn fn, CUtensorMap* m, const void* p, int rank, const cuuint64_t* gd, const cuuint64_t* gs, const cuuint32_t* bd, CUtensorMapSwizzle sw) {
  cuuint32_t es[5] = {1, 1, 1, 1, 1};
  enc_err = 2 * enc_err + (fn(m, CU_TENSOR_MAP_DATA_TYPE_BFLOAT16, rank, (void*)p, gd, gs, bd, es, CU_TENSOR_MAP_INTERLEAVE_NONE, sw,
                              CU_TENSOR_MAP_L2_PROMOTION_L2_128B, CU_TENSOR_MAP_FLOAT_OOB_FILL_NONE) != CUDA_SUCCESS);
}

extern "C" void kernel_launch(void* const* d_in, const int* in_sizes, int n_in, void* d_out, int out_size) {
  const bf16 *q = (const bf16*)d_in[0], *k = (const bf16*)d_in[1], *v = (const bf16*)d_in[2], *shift = (const bf16*)d_in[3],
             *ssmk = (const bf16*)d_in[4], *ssmd = (const bf16*)d_in[5], *w1 = (const bf16*)d_in[7], *w3 = (const bf16*)d_in[8],
             *w2 = (const bf16*)d_in[9], *c = (const bf16*)d_in[10], *wmod = (const bf16*)d_in[11];
  EncFn fn = nullptr;
  cudaDriverEntryPointQueryResult qr;
  cudaGetDriverEntryPoint("cuTensorMapEncodeTiled", (void**)&fn, cudaEnableDefault, &qr);
  Scratch* pg;
  cudaGetSymbolAddress((void**)&pg, g_s);
  Maps maps;
  enc_err = 0;
  const CUtensorMapSwizzle S128 = CU_TENSOR_MAP_SWIZZLE_128B;
  { cuuint64_t gd[3] = {D_, S_ / 8, 8}, gs[2] = {D_ * 16, D_ * 2}; cuuint32_t b[3] = {64, 4, 8};
    enc(fn, &maps.km, k, 3, gd, gs, b, S128);
    enc(fn, &maps.v, v, 3, gd, gs, b, S128);
    enc(fn, &maps.q, q, 3, gd, gs, b, S128);
    b[2] = 3;
    enc(fn, &maps.kh, k, 3, gd, gs, b, S128); }
  { cuuint64_t gd[3] = {256, 8, D_}, gs[2] = {512, 4096}; cuuint32_t b[3] = {256, 8, 1};
    enc(fn, &maps.fm, ssmk, 3, gd, gs, b, CU_TENSOR_MAP_SWIZZLE_NONE); }
  { cuuint64_t gd[3] = {256, 2, 5}, gs[2] = {512, 1024}; cuuint32_t b[3] = {256, 1, 5};
    enc(fn, &maps.tap, shift, 3, gd, gs, b, CU_TENSOR_MAP_SWIZZLE_NONE); }
  { cuuint64_t gd[3] = {6 * D_, D_, 1}, gs[2] = {6 * D_ * 2, 6 * D_ * 2 * D_}; cuuint32_t b[3] = {64, 64, 1};
    enc(fn, &maps.wm, wmod, 3, gd, gs, b, S128);
    b[1] = 80;
    enc(fn, &maps.wmp, wmod, 3, gd, gs, b, S128); }
  { cuuint64_t gd[3] = {64, D_, F_ / 64}, gs[2] = {F_ * 2, 128}; cuuint32_t b[3] = {64, 16, 3};
    enc(fn, &maps.w1u, w1, 3, gd, gs, b, S128);
    enc(fn, &maps.w3u, w3, 3, gd, gs, b, S128);
    b[1] = 32; b[2] = 2;
    enc(fn, &maps.w1a, w1, 3, gd, gs, b, S128);
    enc(fn, &maps.w3a, w3, 3, gd, gs, b, S128);
    b[1] = 64; b[2] = 1;
    enc(fn, &maps.w1b, w1, 3, gd, gs, b, S128);
    enc(fn, &maps.w3b, w3, 3, gd, gs, b, S128); }
  { cuuint64_t gd[2] = {S_, D_}, gs[1] = {S_ * 2}; cuuint32_t b1[2] = {64, 64}, b2[2] = {64, 32};
    enc(fn, &maps.xs, pg->xs, 2, gd, gs, b1, S128);
    gd[1] = 2 * D_;
    enc(fn, &maps.x1b, pg->x1, 2, gd, gs, b2, S128);
    enc(fn, &maps.x1s, pg->x1, 2, gd, gs, b2, CU_TENSOR_MAP_SWIZZLE_NONE); }
  { cuuint64_t gd[5] = {D_, 2, 4, 4, 48}, gs[4] = {D_ * 2, D_ * 4, D_ * 16, D_ * 64}; cuuint32_t b[5] = {64, 2, 4, 4, 2};
    enc(fn, &maps.w2a, w2, 5, gd, gs, b, S128);
    gs[1] = D_ * 16; gs[2] = D_ * 4;
    enc(fn, &maps.w2b, w2, 5, gd, gs, b, S128); }
  { cuuint64_t gd[2] = {D_, S_}, gs[1] = {D_ * 2}; cuuint32_t b1[2] = {64, 16}, b2[2] = {32, 16};
    enc(fn, &maps.outa, d_out, 2, gd, gs, b1, S128);
    enc(fn, &maps.outb, d_out, 2, gd, gs, b2, CU_TENSOR_MAP_SWIZZLE_64B); }
  if (enc_err) return;
  cudaFuncSetAttribute(k_fused<0>, cudaFuncAttributeMaxDynamicSharedMemorySize, SMEM_BYTES);
  cudaFuncSetAttribute(k_fused<128>, cudaFuncAttributeMaxDynamicSharedMemorySize, SMEM_BYTES);
  cudaLaunchConfig_t cfg = {132, 512, SMEM_BYTES};
  cudaLaunchAttribute at = {cudaLaunchAttributeClusterDimension};
  at.val.clusterDim.x = 2; at.val.clusterDim.y = at.val.clusterDim.z = 1;
  cfg.attrs = &at; cfg.numAttrs = 1;
  int nc = 0;
  cudaOccupancyMaxActiveClusters(&nc, k_fused<0>, &cfg);
  Ptrs P = {c, ssmd, pg, {0x676360, 0x746209}, {}, 32, 3, 0, B_EMPTY + 32, 0 | 0 << 16, 0, {}, 0x33511, 0, 11400, 900, 1.f};
  const char* ho = "abcdefghijklmnopqrstuvwxyz{|}~";
  memset(P.hl, 255, sizeof(P.hl));
  for (int k = 0, n = 0; k < 30; k++) {
    const int i = ho[k] - 'a';
    if (i >= 20 || !(M8 >> i / 4 & 1)) ((uint8_t*)P.hl)[n++] = i;
  }
  for (int u = 0; u < 30; u++) P.wdep[u] = (u < 4 ? B_FL + 1 + u / 3 : u < 6 ? B_G : B_EMPTY + (u < 26 ? (u - 6) | 1 : u - 6)) | (u >= 20) << 8 | u % 6 << 9 | (u < 20 ? 3 * (~u & 1) : 1 + (u >= 26)) << 14 | (u < 20 ? 32 * u : 64 * (second(u - 20) % 10)) << 16;
  const int adep[14] = {B_PEMPTY, B_PEMPTY, B_PFULL + 4, B_PEMPTY + 1, B_PEMPTY + 2, B_EMPTY + 5, B_EMPTY + 7, B_PEMPTY + 3, B_EMPTY + 2 * UVS + 1, B_EMPTY + 2 * UVS + 1, B_EMPTY + 20, B_EMPTY + 21, B_EMPTY + 22, B_EMPTY + 23};
  const char *ad = "--*--d----uvwx", *wd = "255679:<=>?@", *hd = "789;;>?@A";
  for (int n = 0; n < 14; n++) P.adep[n] = adep[n] | (ad[n] == '-' ? adep[n] : ad[n] == '*' ? B_PFULL + 3 : B_EMPTY + ad[n] - 'a') << 8 | (n < 10 ? 2 * n : n + 16) << 16 | n % 10 << 21 | a_at(n) / UNIT << 25;
  const char* ld = "abcd";
  for (int v = 0; v < 12; v++) P.w2t[v] = make_uint2(w2_desc(v), B_EMPTY + 20 + wd[v] - '0');
  for (int m = 0; m < 9; m++) { P.hid[0][m] = hid_at(m, 0) | m / 3 * 4 | (m % 3 + 1); P.hid[1][m] = hid_at(m, 1) | m / 3 * 4 | (m % 3 + 1); P.hid[2][m] = B_EMPTY + 20 + hd[m] - '0'; P.hid[3][m] = m < 5 ? 0 : ld[m - 5] < 'a' ? B_EMPTY + 20 + ld[m - 5] - '0' : B_FULL + 38 + ld[m - 5] - 'a'; }
  if (nc < 66) k_fused<128><<<4, 512, SMEM_BYTES, cudaStreamPerThread>>>(P, maps);
  k_fused<0><<<nc < 66 ? 128 : 132, 512, SMEM_BYTES, cudaStreamPerThread>>>(P, maps);
}
```

```cpp
#include <cuda_runtime.h>
#include <cuda.h>
#include <cuda_bf16.h>
#include <stdint.h>
#include <stdlib.h>
#include <string.h>

typedef __nv_bfloat16 bf16;
constexpr int S_ = 2048, D_ = 640, F_ = 1536;

struct Scratch {
  uint32_t st1[2][1024];
  uint32_t st2[32][4][128];
  uint32_t modc[128][5][32];
  uint2 modv[3][D_];
  uint32_t uv[8][3072];
  unsigned hint[9][8][32];
  unsigned xsh[5][8][32], hhf[256 * 8], key[256];
  uint4 xr[D_ * 256];
  uint4 qt[D_ * 256];
  uint4 xs[D_ * 256];
  uint4 x1[2][D_ * 256];
  uint4 hh[32 * 8 * 1536];
};
__device__ __align__(1024) Scratch g_s;

__device__ __forceinline__ uint32_t smem_u32(const void* p) { return (uint32_t)__cvta_generic_to_shared(p); }
__device__ __forceinline__ void mbar_expect_tx(uint32_t b, uint32_t n) { asm volatile("mbarrier.arrive.expect_tx.shared::cta.b64 _, [%0], %1;" ::"r"(b), "r"(n) : "memory"); }
__device__ __forceinline__ void mbar_arrive(uint32_t b) { asm volatile("mbarrier.arrive.shared::cta.b64 _, [%0];" ::"r"(b) : "memory"); }
__device__ __forceinline__ void mbar_arrive2(uint32_t b) { asm volatile("mbarrier.arrive.shared::cta.b64 _, [%0], 2;" ::"r"(b) : "memory"); }
__device__ __forceinline__ uint32_t mapa(uint32_t a, uint32_t cta) { uint32_t r; asm volatile("mapa.shared::cluster.u32 %0, %1, %2;" : "=r"(r) : "r"(a), "r"(cta)); return r; }
__device__ __forceinline__ void mbar_arrive_remote(uint32_t rb) { asm volatile("mbarrier.arrive.shared::cluster.b64 _, [%0];" ::"r"(rb) : "memory"); }
constexpr int SPIN_LIMIT = 1 << 16;
template <int N> __device__ __forceinline__ void mbar_init(uint32_t b, uint32_t count) {
#pragma unroll
  for (int i = 0; i < N; i++) asm volatile("mbarrier.init.shared::cta.b64 [%0], %1;" ::"r"(b + 8 * i), "r"(count) : "memory");
}
__device__ __forceinline__ bool elect() { uint32_t p; asm volatile("{.reg .pred q; elect.sync _|q, 0xffffffff; selp.u32 %0, 1, 0, q;}" : "=r"(p)); return p; }
__device__ __forceinline__ void arrive1(uint32_t b) { __syncwarp(); if (elect()) mbar_arrive(b); }
__device__ __forceinline__ bool mbar_test(uint32_t b) {
  uint32_t ok;
  asm volatile("{.reg .pred p; mbarrier.test_wait.parity.shared::cta.b64 p, [%1], 0; selp.u32 %0,1,0,p;}" : "=r"(ok) : "r"(b) : "memory");
  return ok;
}
#define WAIT_LOOP(sem) "{.reg .pred p; mov.u32 %0, 0; W: mbarrier.try_wait.parity" sem ".shared::cta.b64 p, [%1], %2; @p bra.uni D; add.u32 %0, %0, 1; setp.lt.u32 p, %0, %3; @p bra.uni W; D:}"
__device__ __forceinline__ void mbar_wait(uint32_t b, uint32_t ph = 0) {
  int it;
  asm volatile(WAIT_LOOP("") : "=&r"(it) : "r"(b), "r"(ph), "n"(SPIN_LIMIT) : "memory");
}
__device__ __forceinline__ void mbar_wait_cluster(uint32_t b, uint32_t ph = 0) {
  int it;
  asm volatile(WAIT_LOOP(".acquire.cluster") : "=&r"(it) : "r"(b), "r"(ph), "n"(SPIN_LIMIT) : "memory");
}
__device__ __forceinline__ void wait_clock(uint32_t t) {
  asm volatile("{.reg .pred p; .reg .s32 d; W: mov.u32 d, %%clock; sub.s32 d, d, %0; setp.lt.s32 p, d, 0; @p bra.uni W;}" ::"r"(t) : "memory");
}
__device__ __forceinline__ void tma2d(uint32_t dst, const CUtensorMap* m, int c0, int c1, uint32_t bar) {
  asm volatile("cp.async.bulk.tensor.2d.shared::cluster.global.mbarrier::complete_tx::bytes [%0], [%1, {%3,%4}], [%2];" ::"r"(dst), "l"(m), "r"(bar), "r"(c0), "r"(c1) : "memory");
}
__device__ __forceinline__ void tma3d(uint32_t dst, const CUtensorMap* m, int c0, int c1, int c2, uint32_t bar) {
  asm volatile("cp.async.bulk.tensor.3d.shared::cluster.global.mbarrier::complete_tx::bytes [%0], [%1, {%3,%4,%5}], [%2];" ::"r"(dst), "l"(m), "r"(bar), "r"(c0), "r"(c1), "r"(c2) : "memory");
}
__device__ __forceinline__ void tma5d(uint32_t dst, const CUtensorMap* m, int c0, int c4, uint32_t bar) {
  asm volatile("cp.async.bulk.tensor.5d.shared::cluster.global.mbarrier::complete_tx::bytes [%0], [%1, {%4,%3,%3,%3,%5}], [%2];" ::"r"(dst), "l"(m), "r"(bar), "r"(0), "r"(c0), "r"(c4) : "memory");
}
__device__ __forceinline__ void tma2d_store(const CUtensorMap* m, int c0, int c1, uint32_t src) {
  asm volatile("cp.async.bulk.tensor.2d.global.shared::cta.bulk_group [%0, {%2,%3}], [%1];" ::"l"(m), "r"(src), "r"(c0), "r"(c1) : "memory");
}
__device__ __forceinline__ void bulk_load(uint32_t dst, const void* src, uint32_t bytes, uint32_t bar) {
  asm volatile("cp.async.bulk.shared::cluster.global.mbarrier::complete_tx::bytes [%0], [%1], %2, [%3];" ::"r"(dst), "l"(src), "r"(bytes), "r"(bar) : "memory");
}
__device__ __forceinline__ void prefetch_map(const CUtensorMap* m) { asm volatile("prefetch.tensormap [%0];" ::"l"(m) : "memory"); }
__device__ __forceinline__ void bulk_commit() { asm volatile("cp.async.bulk.commit_group;" ::: "memory"); }
__device__ __forceinline__ void bulk_wait_read() { asm volatile("cp.async.bulk.wait_group.read 0;" ::: "memory"); }
__device__ __forceinline__ void fence_async_smem() { asm volatile("fence.proxy.async.shared::cta;" ::: "memory"); }
__device__ __forceinline__ void fence_async_all() { asm volatile("fence.proxy.async.global;" ::: "memory"); }
__device__ __forceinline__ void named_bar(int id, int n) { asm volatile("bar.sync %0, %1;" ::"r"(id), "r"(n) : "memory"); }
__device__ __forceinline__ bool bar_all(int id, bool v) {
  uint32_t r;
  asm volatile("{.reg .pred p, q; setp.ne.u32 p, %2, 0; bar.red.and.pred q, %1, 128, p; selp.u32 %0, 1, 0, q;}" : "=r"(r) : "r"(id), "r"((uint32_t)v) : "memory");
  return __all_sync(~0u, r);
}
__device__ __forceinline__ void cluster_wait() { asm volatile("barrier.cluster.wait.aligned;" ::: "memory"); }
__device__ __forceinline__ void wg_fence() { asm volatile("wgmma.fence.sync.aligned;" ::: "memory"); }
__device__ __forceinline__ void wg_commit() { asm volatile("wgmma.commit_group.sync.aligned;" ::: "memory"); }
template <int N> __device__ __forceinline__ void wg_wait() { asm volatile("wgmma.wait_group.sync.aligned %0;" ::"n"(N) : "memory"); }
template <int N> __device__ __forceinline__ void fence_regs(float (&a)[N]) {
#pragma unroll
  for (int i = 0; i < N; i++) asm volatile("" : "+f"(a[i])::"memory");
}
__device__ __forceinline__ uint64_t mkdesc(uint32_t addr, uint32_t lbo, uint32_t sbo, uint32_t swz) {
  uint32_t lo = (addr >> 4) | ((lbo >> 4) << 16), hi = (sbo >> 4) | (swz << 30);
  return ((uint64_t)hi << 32) | lo;
}
__device__ __forceinline__ void stmatrix_x4(uint32_t a, uint32_t r0, uint32_t r1, uint32_t r2, uint32_t r3) {
  asm volatile("stmatrix.sync.aligned.m8n8.x4.shared.b16 [%0], {%1,%2,%3,%4};" ::"r"(a), "r"(r0), "r"(r1), "r"(r2), "r"(r3) : "memory");
}
__device__ __forceinline__ void stmatrix_x4_t(uint32_t a, uint32_t r0, uint32_t r1, uint32_t r2, uint32_t r3) {
  asm volatile("stmatrix.sync.aligned.m8n8.x4.trans.shared.b16 [%0], {%1,%2,%3,%4};" ::"r"(a), "r"(r0), "r"(r1), "r"(r2), "r"(r3) : "memory");
}
__device__ __forceinline__ void ldmatrix_x4_t(uint32_t* r, uint32_t a) {
  asm volatile("ldmatrix.sync.aligned.m8n8.x4.trans.shared.b16 {%0,%1,%2,%3}, [%4];" : "=r"(r[0]), "=r"(r[1]), "=r"(r[2]), "=r"(r[3]) : "r"(a) : "memory");
}
__device__ __forceinline__ uint32_t lds32(uint32_t a) { uint32_t v; asm volatile("ld.shared.b32 %0, [%1];" : "=r"(v) : "r"(a) : "memory"); return v; }
__device__ __forceinline__ uint2 lds64(uint32_t a) { uint2 v; asm volatile("ld.shared.v2.b32 {%0,%1}, [%2];" : "=r"(v.x), "=r"(v.y) : "r"(a) : "memory"); return v; }
__device__ __forceinline__ uint4 lds128(uint32_t a) { uint4 v; asm volatile("ld.shared.v4.b32 {%0,%1,%2,%3}, [%4];" : "=r"(v.x), "=r"(v.y), "=r"(v.z), "=r"(v.w) : "r"(a) : "memory"); return v; }
__device__ __forceinline__ void sts32(uint32_t a, uint32_t v) { asm volatile("st.shared.b32 [%0], %1;" ::"r"(a), "r"(v) : "memory"); }
__device__ __forceinline__ void sts64(uint32_t a, uint32_t x, uint32_t y) { asm volatile("st.shared.v2.b32 [%0], {%1,%2};" ::"r"(a), "r"(x), "r"(y) : "memory"); }
__device__ __forceinline__ void sts128(uint32_t a, uint32_t x, uint32_t y, uint32_t z, uint32_t w) { asm volatile("st.shared.v4.b32 [%0], {%1,%2,%3,%4};" ::"r"(a), "r"(x), "r"(y), "r"(z), "r"(w) : "memory"); }
__device__ __forceinline__ uint4 ld_relaxed128(const void* p) { uint4 v; asm volatile("ld.relaxed.gpu.global.v4.u32 {%0,%1,%2,%3}, [%4];" : "=r"(v.x), "=r"(v.y), "=r"(v.z), "=r"(v.w) : "l"(p) : "memory"); return v; }
__device__ __forceinline__ uint2 ld_relaxed64(const void* p) { uint2 v; asm volatile("ld.relaxed.gpu.global.v2.u32 {%0,%1}, [%2];" : "=r"(v.x), "=r"(v.y) : "l"(p) : "memory"); return v; }
__device__ __forceinline__ uint32_t ld_relaxed32(const void* p) { uint32_t v; asm volatile("ld.relaxed.gpu.global.u32 %0, [%1];" : "=r"(v) : "l"(p) : "memory"); return v; }
__device__ __forceinline__ void st_relaxed128(void* p, uint32_t x, uint32_t y, uint32_t z, uint32_t w) { asm volatile("st.relaxed.gpu.global.v4.u32 [%0], {%1,%2,%3,%4};" ::"l"(p), "r"(x), "r"(y), "r"(z), "r"(w) : "memory"); }
__device__ __forceinline__ void st_relaxed32(void* p, uint32_t x) { asm volatile("st.relaxed.gpu.global.u32 [%0], %1;" ::"l"(p), "r"(x) : "memory"); }
__device__ __forceinline__ void red_hint(unsigned* p) { asm volatile("red.relaxed.gpu.global.add.u32 [%0], 1;" ::"l"(p) : "memory"); }
__device__ __forceinline__ void publish(uint32_t* p, uint32_t x) { asm volatile("{.reg .b32 t; atom.relaxed.gpu.global.exch.b32 t, [%0], %1;}" ::"l"(p), "r"(x) : "memory"); }
__device__ __forceinline__ uint32_t ldg32(const void* p) { uint32_t v; asm volatile("ld.global.nc.L1::no_allocate.b32 %0, [%1];" : "=r"(v) : "l"(p)); return v; }
__device__ __forceinline__ uint32_t pack_bf16(float lo, float hi) { uint32_t r; asm("cvt.rn.bf16x2.f32 %0, %1, %2;" : "=r"(r) : "f"(hi), "f"(lo)); return r; }
__device__ __forceinline__ float bf_lo(uint32_t v) { return __uint_as_float(v << 16); }
__device__ __forceinline__ float bf_hi(uint32_t v) { return __uint_as_float(v & 0xFFFF0000u); }
__device__ __forceinline__ uint32_t bmul2(uint32_t a, uint32_t b) { uint32_t r; asm("mul.rn.bf16x2 %0, %1, %2;" : "=r"(r) : "r"(a), "r"(b)); return r; }
__device__ __forceinline__ uint32_t badd2(uint32_t a, uint32_t b) { uint32_t r; asm("add.rn.bf16x2 %0, %1, %2;" : "=r"(r) : "r"(a), "r"(b)); return r; }
__device__ __forceinline__ uint32_t bfma2(uint32_t a, uint32_t b, uint32_t c) { uint32_t r; asm("fma.rn.bf16x2 %0, %1, %2, %3;" : "=r"(r) : "r"(a), "r"(b), "r"(c)); return r; }
__device__ __forceinline__ uint32_t set_tag(uint32_t x, uint32_t mask, uint32_t e) { uint32_t r; asm("lop3.b32 %0, %1, %2, %3, 0xB8;" : "=r"(r) : "r"(x), "r"(mask), "r"(e)); return r; }
__device__ __forceinline__ uint32_t opaque(uint32_t x) { asm volatile("" : "+r"(x)); return x; }
__device__ __forceinline__ float rbf(float x) { return __bfloat162float(__float2bfloat16(x)); }
__device__ __forceinline__ float silu_f(float x) {
  float e, r;
  asm("ex2.approx.ftz.f32 %0, %1;" : "=f"(e) : "f"(x * -1.4426950408889634f));
  asm("rcp.approx.ftz.f32 %0, %1;" : "=f"(r) : "f"(1.f + e));
  return x * r;
}
__device__ __forceinline__ float silu2(float g, float a, float b) {
  float t;
  asm("tanh.approx.f32 %0, %1;" : "=f"(t) : "f"(g * a));
  return fmaf(g * b, t, g * b);
}
__device__ __forceinline__ void pin(int off, uint32_t x) { asm volatile("{.reg .pred p; setp.lt.s32 p, %0, 0; @p st.shared.b32 [%0], %1;}" ::"r"(off), "r"(x) : "memory"); }
__device__ __forceinline__ void pin4(int off, const uint32_t* x) { asm volatile("{.reg .pred p; setp.lt.s32 p, %0, 0; @p st.shared.v4.b32 [%0], {%1,%2,%3,%4};}" ::"r"(off), "r"(x[0]), "r"(x[1]), "r"(x[2]), "r"(x[3]) : "memory"); }
__device__ __forceinline__ void split(int x, int n) { asm volatile("{.reg .pred p; setp.eq.s32 p, %0, %1; @p trap;}" ::"r"(x), "r"(~n) : "memory"); }
__device__ __forceinline__ void ln_final(float s, float q, float& m, float& sd) {
  m = s * (1.f / D_);
  asm("sqrt.approx.f32 %0, %1;" : "=f"(sd) : "f"(rbf(rbf(fmaxf(fmaf(-m, m, q * (1.f / D_)), 0.f)) + 1e-5f)));
  sd = rbf(sd);
}
__device__ __forceinline__ float rcpf(float x) { float r; asm("rcp.approx.f32 %0, %1;" : "=f"(r) : "f"(x)); return r; }

__device__ __forceinline__ void wg_rs16_0(float* d, const uint32_t* a, uint64_t db, int sc) {
  asm volatile("{.reg .pred p; setp.ne.b32 p, %13, 0; wgmma.mma_async.sync.aligned.m64n16k16.f32.bf16.bf16 {%0,%1,%2,%3,%4,%5,%6,%7}, {%8,%9,%10,%11}, %12, p, 1, 1, 0;}"
    : "+f"(d[0]),"+f"(d[1]),"+f"(d[2]),"+f"(d[3]),"+f"(d[4]),"+f"(d[5]),"+f"(d[6]),"+f"(d[7]) : "r"(a[0]),"r"(a[1]),"r"(a[2]),"r"(a[3]),"l"(db),"r"(sc));
}
__device__ __forceinline__ void wg_rs32_0(float* d, const uint32_t* a, uint64_t db, int sc) {
  asm volatile("{.reg .pred p; setp.ne.b32 p, %21, 0; wgmma.mma_async.sync.aligned.m64n32k16.f32.bf16.bf16 {%0,%1,%2,%3,%4,%5,%6,%7,%8,%9,%10,%11,%12,%13,%14,%15}, {%16,%17,%18,%19}, %20, p, 1, 1, 0;}"
    : "+f"(d[0]),"+f"(d[1]),"+f"(d[2]),"+f"(d[3]),"+f"(d[4]),"+f"(d[5]),"+f"(d[6]),"+f"(d[7]),"+f"(d[8]),"+f"(d[9]),"+f"(d[10]),"+f"(d[11]),"+f"(d[12]),"+f"(d[13]),"+f"(d[14]),"+f"(d[15]) : "r"(a[0]),"r"(a[1]),"r"(a[2]),"r"(a[3]),"l"(db),"r"(sc));
}
__device__ __forceinline__ void wg_rs48_0(float* d, const uint32_t* a, uint64_t db, int sc) {
  asm volatile("{.reg .pred p; setp.ne.b32 p, %29, 0; wgmma.mma_async.sync.aligned.m64n48k16.f32.bf16.bf16 {%0,%1,%2,%3,%4,%5,%6,%7,%8,%9,%10,%11,%12,%13,%14,%15,%16,%17,%18,%19,%20,%21,%22,%23}, {%24,%25,%26,%27}, %28, p, 1, 1, 0;}"
    : "+f"(d[0]),"+f"(d[1]),"+f"(d[2]),"+f"(d[3]),"+f"(d[4]),"+f"(d[5]),"+f"(d[6]),"+f"(d[7]),"+f"(d[8]),"+f"(d[9]),"+f"(d[10]),"+f"(d[11]),"+f"(d[12]),"+f"(d[13]),"+f"(d[14]),"+f"(d[15]),"+f"(d[16]),"+f"(d[17]),"+f"(d[18]),"+f"(d[19]),"+f"(d[20]),"+f"(d[21]),"+f"(d[22]),"+f"(d[23]) : "r"(a[0]),"r"(a[1]),"r"(a[2]),"r"(a[3]),"l"(db),"r"(sc));
}
__device__ __forceinline__ void wg_rs64_0(float* d, const uint32_t* a, uint64_t db, int sc) {
  asm volatile("{.reg .pred p; setp.ne.b32 p, %37, 0; wgmma.mma_async.sync.aligned.m64n64k16.f32.bf16.bf16 {%0,%1,%2,%3,%4,%5,%6,%7,%8,%9,%10,%11,%12,%13,%14,%15,%16,%17,%18,%19,%20,%21,%22,%23,%24,%25,%26,%27,%28,%29,%30,%31}, {%32,%33,%34,%35}, %36, p, 1, 1, 0;}"
    : "+f"(d[0]),"+f"(d[1]),"+f"(d[2]),"+f"(d[3]),"+f"(d[4]),"+f"(d[5]),"+f"(d[6]),"+f"(d[7]),"+f"(d[8]),"+f"(d[9]),"+f"(d[10]),"+f"(d[11]),"+f"(d[12]),"+f"(d[13]),"+f"(d[14]),"+f"(d[15]),"+f"(d[16]),"+f"(d[17]),"+f"(d[18]),"+f"(d[19]),"+f"(d[20]),"+f"(d[21]),"+f"(d[22]),"+f"(d[23]),"+f"(d[24]),"+f"(d[25]),"+f"(d[26]),"+f"(d[27]),"+f"(d[28]),"+f"(d[29]),"+f"(d[30]),"+f"(d[31]) : "r"(a[0]),"r"(a[1]),"r"(a[2]),"r"(a[3]),"l"(db),"r"(sc));
}
__device__ __forceinline__ void wg_rs80_0(float* d, const uint32_t* a, uint64_t db, int sc) {
  asm volatile("{.reg .pred p; setp.ne.b32 p, %45, 0; wgmma.mma_async.sync.aligned.m64n80k16.f32.bf16.bf16 {%0,%1,%2,%3,%4,%5,%6,%7,%8,%9,%10,%11,%12,%13,%14,%15,%16,%17,%18,%19,%20,%21,%22,%23,%24,%25,%26,%27,%28,%29,%30,%31,%32,%33,%34,%35,%36,%37,%38,%39}, {%40,%41,%42,%43}, %44, p, 1, 1, 0;}"
    : "+f"(d[0]),"+f"(d[1]),"+f"(d[2]),"+f"(d[3]),"+f"(d[4]),"+f"(d[5]),"+f"(d[6]),"+f"(d[7]),"+f"(d[8]),"+f"(d[9]),"+f"(d[10]),"+f"(d[11]),"+f"(d[12]),"+f"(d[13]),"+f"(d[14]),"+f"(d[15]),"+f"(d[16]),"+f"(d[17]),"+f"(d[18]),"+f"(d[19]),"+f"(d[20]),"+f"(d[21]),"+f"(d[22]),"+f"(d[23]),"+f"(d[24]),"+f"(d[25]),"+f"(d[26]),"+f"(d[27]),"+f"(d[28]),"+f"(d[29]),"+f"(d[30]),"+f"(d[31]),"+f"(d[32]),"+f"(d[33]),"+f"(d[34]),"+f"(d[35]),"+f"(d[36]),"+f"(d[37]),"+f"(d[38]),"+f"(d[39]) : "r"(a[0]),"r"(a[1]),"r"(a[2]),"r"(a[3]),"l"(db),"r"(sc));
}
__device__ __forceinline__ void wg_rs96_0(float* d, const uint32_t* a, uint64_t db, int sc) {
  asm volatile("{.reg .pred p; setp.ne.b32 p, %53, 0; wgmma.mma_async.sync.aligned.m64n96k16.f32.bf16.bf16 {%0,%1,%2,%3,%4,%5,%6,%7,%8,%9,%10,%11,%12,%13,%14,%15,%16,%17,%18,%19,%20,%21,%22,%23,%24,%25,%26,%27,%28,%29,%30,%31,%32,%33,%34,%35,%36,%37,%38,%39,%40,%41,%42,%43,%44,%45,%46,%47}, {%48,%49,%50,%51}, %52, p, 1, 1, 0;}"
    : "+f"(d[0]),"+f"(d[1]),"+f"(d[2]),"+f"(d[3]),"+f"(d[4]),"+f"(d[5]),"+f"(d[6]),"+f"(d[7]),"+f"(d[8]),"+f"(d[9]),"+f"(d[10]),"+f"(d[11]),"+f"(d[12]),"+f"(d[13]),"+f"(d[14]),"+f"(d[15]),"+f"(d[16]),"+f"(d[17]),"+f"(d[18]),"+f"(d[19]),"+f"(d[20]),"+f"(d[21]),"+f"(d[22]),"+f"(d[23]),"+f"(d[24]),"+f"(d[25]),"+f"(d[26]),"+f"(d[27]),"+f"(d[28]),"+f"(d[29]),"+f"(d[30]),"+f"(d[31]),"+f"(d[32]),"+f"(d[33]),"+f"(d[34]),"+f"(d[35]),"+f"(d[36]),"+f"(d[37]),"+f"(d[38]),"+f"(d[39]),"+f"(d[40]),"+f"(d[41]),"+f"(d[42]),"+f"(d[43]),"+f"(d[44]),"+f"(d[45]),"+f"(d[46]),"+f"(d[47]) : "r"(a[0]),"r"(a[1]),"r"(a[2]),"r"(a[3]),"l"(db),"r"(sc));
}
__device__ __forceinline__ void wg_rs112_0(float* d, const uint32_t* a, uint64_t db, int sc) {
  asm volatile("{.reg .pred p; setp.ne.b32 p, %61, 0; wgmma.mma_async.sync.aligned.m64n112k16.f32.bf16.bf16 {%0,%1,%2,%3,%4,%5,%6,%7,%8,%9,%10,%11,%12,%13,%14,%15,%16,%17,%18,%19,%20,%21,%22,%23,%24,%25,%26,%27,%28,%29,%30,%31,%32,%33,%34,%35,%36,%37,%38,%39,%40,%41,%42,%43,%44,%45,%46,%47,%48,%49,%50,%51,%52,%53,%54,%55}, {%56,%57,%58,%59}, %60, p, 1, 1, 0;}"
    : "+f"(d[0]),"+f"(d[1]),"+f"(d[2]),"+f"(d[3]),"+f"(d[4]),"+f"(d[5]),"+f"(d[6]),"+f"(d[7]),"+f"(d[8]),"+f"(d[9]),"+f"(d[10]),"+f"(d[11]),"+f"(d[12]),"+f"(d[13]),"+f"(d[14]),"+f"(d[15]),"+f"(d[16]),"+f"(d[17]),"+f"(d[18]),"+f"(d[19]),"+f"(d[20]),"+f"(d[21]),"+f"(d[22]),"+f"(d[23]),"+f"(d[24]),"+f"(d[25]),"+f"(d[26]),"+f"(d[27]),"+f"(d[28]),"+f"(d[29]),"+f"(d[30]),"+f"(d[31]),"+f"(d[32]),"+f"(d[33]),"+f"(d[34]),"+f"(d[35]),"+f"(d[36]),"+f"(d[37]),"+f"(d[38]),"+f"(d[39]),"+f"(d[40]),"+f"(d[41]),"+f"(d[42]),"+f"(d[43]),"+f"(d[44]),"+f"(d[45]),"+f"(d[46]),"+f"(d[47]),"+f"(d[48]),"+f"(d[49]),"+f"(d[50]),"+f"(d[51]),"+f"(d[52]),"+f"(d[53]),"+f"(d[54]),"+f"(d[55]) : "r"(a[0]),"r"(a[1]),"r"(a[2]),"r"(a[3]),"l"(db),"r"(sc));
}
__device__ __forceinline__ void wg_rs128_0(float* d, const uint32_t* a, uint64_t db, int sc) {
  asm volatile("{.reg .pred p; setp.ne.b32 p, %69, 0; wgmma.mma_async.sync.aligned.m64n128k16.f32.bf16.bf16 {%0,%1,%2,%3,%4,%5,%6,%7,%8,%9,%10,%11,%12,%13,%14,%15,%16,%17,%18,%19,%20,%21,%22,%23,%24,%25,%26,%27,%28,%29,%30,%31,%32,%33,%34,%35,%36,%37,%38,%39,%40,%41,%42,%43,%44,%45,%46,%47,%48,%49,%50,%51,%52,%53,%54,%55,%56,%57,%58,%59,%60,%61,%62,%63}, {%64,%65,%66,%67}, %68, p, 1, 1, 0;}"
    : "+f"(d[0]),"+f"(d[1]),"+f"(d[2]),"+f"(d[3]),"+f"(d[4]),"+f"(d[5]),"+f"(d[6]),"+f"(d[7]),"+f"(d[8]),"+f"(d[9]),"+f"(d[10]),"+f"(d[11]),"+f"(d[12]),"+f"(d[13]),"+f"(d[14]),"+f"(d[15]),"+f"(d[16]),"+f"(d[17]),"+f"(d[18]),"+f"(d[19]),"+f"(d[20]),"+f"(d[21]),"+f"(d[22]),"+f"(d[23]),"+f"(d[24]),"+f"(d[25]),"+f"(d[26]),"+f"(d[27]),"+f"(d[28]),"+f"(d[29]),"+f"(d[30]),"+f"(d[31]),"+f"(d[32]),"+f"(d[33]),"+f"(d[34]),"+f"(d[35]),"+f"(d[36]),"+f"(d[37]),"+f"(d[38]),"+f"(d[39]),"+f"(d[40]),"+f"(d[41]),"+f"(d[42]),"+f"(d[43]),"+f"(d[44]),"+f"(d[45]),"+f"(d[46]),"+f"(d[47]),"+f"(d[48]),"+f"(d[49]),"+f"(d[50]),"+f"(d[51]),"+f"(d[52]),"+f"(d[53]),"+f"(d[54]),"+f"(d[55]),"+f"(d[56]),"+f"(d[57]),"+f"(d[58]),"+f"(d[59]),"+f"(d[60]),"+f"(d[61]),"+f"(d[62]),"+f"(d[63]) : "r"(a[0]),"r"(a[1]),"r"(a[2]),"r"(a[3]),"l"(db),"r"(sc));
}
__device__ __forceinline__ void wg_rs144_0(float* d, const uint32_t* a, uint64_t db, int sc) {
  asm volatile("{.reg .pred p; setp.ne.b32 p, %77, 0; wgmma.mma_async.sync.aligned.m64n144k16.f32.bf16.bf16 {%0,%1,%2,%3,%4,%5,%6,%7,%8,%9,%10,%11,%12,%13,%14,%15,%16,%17,%18,%19,%20,%21,%22,%23,%24,%25,%26,%27,%28,%29,%30,%31,%32,%33,%34,%35,%36,%37,%38,%39,%40,%41,%42,%43,%44,%45,%46,%47,%48,%49,%50,%51,%52,%53,%54,%55,%56,%57,%58,%59,%60,%61,%62,%63,%64,%65,%66,%67,%68,%69,%70,%71}, {%72,%73,%74,%75}, %76, p, 1, 1, 0;}"
    : "+f"(d[0]),"+f"(d[1]),"+f"(d[2]),"+f"(d[3]),"+f"(d[4]),"+f"(d[5]),"+f"(d[6]),"+f"(d[7]),"+f"(d[8]),"+f"(d[9]),"+f"(d[10]),"+f"(d[11]),"+f"(d[12]),"+f"(d[13]),"+f"(d[14]),"+f"(d[15]),"+f"(d[16]),"+f"(d[17]),"+f"(d[18]),"+f"(d[19]),"+f"(d[20]),"+f"(d[21]),"+f"(d[22]),"+f"(d[23]),"+f"(d[24]),"+f"(d[25]),"+f"(d[26]),"+f"(d[27]),"+f"(d[28]),"+f"(d[29]),"+f"(d[30]),"+f"(d[31]),"+f"(d[32]),"+f"(d[33]),"+f"(d[34]),"+f"(d[35]),"+f"(d[36]),"+f"(d[37]),"+f"(d[38]),"+f"(d[39]),"+f"(d[40]),"+f"(d[41]),"+f"(d[42]),"+f"(d[43]),"+f"(d[44]),"+f"(d[45]),"+f"(d[46]),"+f"(d[47]),"+f"(d[48]),"+f"(d[49]),"+f"(d[50]),"+f"(d[51]),"+f"(d[52]),"+f"(d[53]),"+f"(d[54]),"+f"(d[55]),"+f"(d[56]),"+f"(d[57]),"+f"(d[58]),"+f"(d[59]),"+f"(d[60]),"+f"(d[61]),"+f"(d[62]),"+f"(d[63]),"+f"(d[64]),"+f"(d[65]),"+f"(d[66]),"+f"(d[67]),"+f"(d[68]),"+f"(d[69]),"+f"(d[70]),"+f"(d[71]) : "r"(a[0]),"r"(a[1]),"r"(a[2]),"r"(a[3]),"l"(db),"r"(sc));
}
__device__ __forceinline__ void wg_rs160_0(float* d, const uint32_t* a, uint64_t db, int sc) {
  asm volatile("{.reg .pred p; setp.ne.b32 p, %85, 0; wgmma.mma_async.sync.aligned.m64n160k16.f32.bf16.bf16 {%0,%1,%2,%3,%4,%5,%6,%7,%8,%9,%10,%11,%12,%13,%14,%15,%16,%17,%18,%19,%20,%21,%22,%23,%24,%25,%26,%27,%28,%29,%30,%31,%32,%33,%34,%35,%36,%37,%38,%39,%40,%41,%42,%43,%44,%45,%46,%47,%48,%49,%50,%51,%52,%53,%54,%55,%56,%57,%58,%59,%60,%61,%62,%63,%64,%65,%66,%67,%68,%69,%70,%71,%72,%73,%74,%75,%76,%77,%78,%79}, {%80,%81,%82,%83}, %84, p, 1, 1, 0;}"
    : "+f"(d[0]),"+f"(d[1]),"+f"(d[2]),"+f"(d[3]),"+f"(d[4]),"+f"(d[5]),"+f"(d[6]),"+f"(d[7]),"+f"(d[8]),"+f"(d[9]),"+f"(d[10]),"+f"(d[11]),"+f"(d[12]),"+f"(d[13]),"+f"(d[14]),"+f"(d[15]),"+f"(d[16]),"+f"(d[17]),"+f"(d[18]),"+f"(d[19]),"+f"(d[20]),"+f"(d[21]),"+f"(d[22]),"+f"(d[23]),"+f"(d[24]),"+f"(d[25]),"+f"(d[26]),"+f"(d[27]),"+f"(d[28]),"+f"(d[29]),"+f"(d[30]),"+f"(d[31]),"+f"(d[32]),"+f"(d[33]),"+f"(d[34]),"+f"(d[35]),"+f"(d[36]),"+f"(d[37]),"+f"(d[38]),"+f"(d[39]),"+f"(d[40]),"+f"(d[41]),"+f"(d[42]),"+f"(d[43]),"+f"(d[44]),"+f"(d[45]),"+f"(d[46]),"+f"(d[47]),"+f"(d[48]),"+f"(d[49]),"+f"(d[50]),"+f"(d[51]),"+f"(d[52]),"+f"(d[53]),"+f"(d[54]),"+f"(d[55]),"+f"(d[56]),"+f"(d[57]),"+f"(d[58]),"+f"(d[59]),"+f"(d[60]),"+f"(d[61]),"+f"(d[62]),"+f"(d[63]),"+f"(d[64]),"+f"(d[65]),"+f"(d[66]),"+f"(d[67]),"+f"(d[68]),"+f"(d[69]),"+f"(d[70]),"+f"(d[71]),"+f"(d[72]),"+f"(d[73]),"+f"(d[74]),"+f"(d[75]),"+f"(d[76]),"+f"(d[77]),"+f"(d[78]),"+f"(d[79]) : "r"(a[0]),"r"(a[1]),"r"(a[2]),"r"(a[3]),"l"(db),"r"(sc));
}
__device__ __forceinline__ void wg_rs176_0(float* d, const uint32_t* a, uint64_t db, int sc) {
  asm volatile("{.reg .pred p; setp.ne.b32 p, %93, 0; wgmma.mma_async.sync.aligned.m64n176k16.f32.bf16.bf16 {%0,%1,%2,%3,%4,%5,%6,%7,%8,%9,%10,%11,%12,%13,%14,%15,%16,%17,%18,%19,%20,%21,%22,%23,%24,%25,%26,%27,%28,%29,%30,%31,%32,%33,%34,%35,%36,%37,%38,%39,%40,%41,%42,%43,%44,%45,%46,%47,%48,%49,%50,%51,%52,%53,%54,%55,%56,%57,%58,%59,%60,%61,%62,%63,%64,%65,%66,%67,%68,%69,%70,%71,%72,%73,%74,%75,%76,%77,%78,%79,%80,%81,%82,%83,%84,%85,%86,%87}, {%88,%89,%90,%91}, %92, p, 1, 1, 0;}"
    : "+f"(d[0]),"+f"(d[1]),"+f"(d[2]),"+f"(d[3]),"+f"(d[4]),"+f"(d[5]),"+f"(d[6]),"+f"(d[7]),"+f"(d[8]),"+f"(d[9]),"+f"(d[10]),"+f"(d[11]),"+f"(d[12]),"+f"(d[13]),"+f"(d[14]),"+f"(d[15]),"+f"(d[16]),"+f"(d[17]),"+f"(d[18]),"+f"(d[19]),"+f"(d[20]),"+f"(d[21]),"+f"(d[22]),"+f"(d[23]),"+f"(d[24]),"+f"(d[25]),"+f"(d[26]),"+f"(d[27]),"+f"(d[28]),"+f"(d[29]),"+f"(d[30]),"+f"(d[31]),"+f"(d[32]),"+f"(d[33]),"+f"(d[34]),"+f"(d[35]),"+f"(d[36]),"+f"(d[37]),"+f"(d[38]),"+f"(d[39]),"+f"(d[40]),"+f"(d[41]),"+f"(d[42]),"+f"(d[43]),"+f"(d[44]),"+f"(d[45]),"+f"(d[46]),"+f"(d[47]),"+f"(d[48]),"+f"(d[49]),"+f"(d[50]),"+f"(d[51]),"+f"(d[52]),"+f"(d[53]),"+f"(d[54]),"+f"(d[55]),"+f"(d[56]),"+f"(d[57]),"+f"(d[58]),"+f"(d[59]),"+f"(d[60]),"+f"(d[61]),"+f"(d[62]),"+f"(d[63]),"+f"(d[64]),"+f"(d[65]),"+f"(d[66]),"+f"(d[67]),"+f"(d[68]),"+f"(d[69]),"+f"(d[70]),"+f"(d[71]),"+f"(d[72]),"+f"(d[73]),"+f"(d[74]),"+f"(d[75]),"+f"(d[76]),"+f"(d[77]),"+f"(d[78]),"+f"(d[79]),"+f"(d[80]),"+f"(d[81]),"+f"(d[82]),"+f"(d[83]),"+f"(d[84]),"+f"(d[85]),"+f"(d[86]),"+f"(d[87]) : "r"(a[0]),"r"(a[1]),"r"(a[2]),"r"(a[3]),"l"(db),"r"(sc));
}
__device__ __forceinline__ void wg_rs192_0(float* d, const uint32_t* a, uint64_t db, int sc) {
  asm volatile("{.reg .pred p; setp.ne.b32 p, %101, 0; wgmma.mma_async.sync.aligned.m64n192k16.f32.bf16.bf16 {%0,%1,%2,%3,%4,%5,%6,%7,%8,%9,%10,%11,%12,%13,%14,%15,%16,%17,%18,%19,%20,%21,%22,%23,%24,%25,%26,%27,%28,%29,%30,%31,%32,%33,%34,%35,%36,%37,%38,%39,%40,%41,%42,%43,%44,%45,%46,%47,%48,%49,%50,%51,%52,%53,%54,%55,%56,%57,%58,%59,%60,%61,%62,%63,%64,%65,%66,%67,%68,%69,%70,%71,%72,%73,%74,%75,%76,%77,%78,%79,%80,%81,%82,%83,%84,%85,%86,%87,%88,%89,%90,%91,%92,%93,%94,%95}, {%96,%97,%98,%99}, %100, p, 1, 1, 0;}"
    : "+f"(d[0]),"+f"(d[1]),"+f"(d[2]),"+f"(d[3]),"+f"(d[4]),"+f"(d[5]),"+f"(d[6]),"+f"(d[7]),"+f"(d[8]),"+f"(d[9]),"+f"(d[10]),"+f"(d[11]),"+f"(d[12]),"+f"(d[13]),"+f"(d[14]),"+f"(d[15]),"+f"(d[16]),"+f"(d[17]),"+f"(d[18]),"+f"(d[19]),"+f"(d[20]),"+f"(d[21]),"+f"(d[22]),"+f"(d[23]),"+f"(d[24]),"+f"(d[25]),"+f"(d[26]),"+f"(d[27]),"+f"(d[28]),"+f"(d[29]),"+f"(d[30]),"+f"(d[31]),"+f"(d[32]),"+f"(d[33]),"+f"(d[34]),"+f"(d[35]),"+f"(d[36]),"+f"(d[37]),"+f"(d[38]),"+f"(d[39]),"+f"(d[40]),"+f"(d[41]),"+f"(d[42]),"+f"(d[43]),"+f"(d[44]),"+f"(d[45]),"+f"(d[46]),"+f"(d[47]),"+f"(d[48]),"+f"(d[49]),"+f"(d[50]),"+f"(d[51]),"+f"(d[52]),"+f"(d[53]),"+f"(d[54]),"+f"(d[55]),"+f"(d[56]),"+f"(d[57]),"+f"(d[58]),"+f"(d[59]),"+f"(d[60]),"+f"(d[61]),"+f"(d[62]),"+f"(d[63]),"+f"(d[64]),"+f"(d[65]),"+f"(d[66]),"+f"(d[67]),"+f"(d[68]),"+f"(d[69]),"+f"(d[70]),"+f"(d[71]),"+f"(d[72]),"+f"(d[73]),"+f"(d[74]),"+f"(d[75]),"+f"(d[76]),"+f"(d[77]),"+f"(d[78]),"+f"(d[79]),"+f"(d[80]),"+f"(d[81]),"+f"(d[82]),"+f"(d[83]),"+f"(d[84]),"+f"(d[85]),"+f"(d[86]),"+f"(d[87]),"+f"(d[88]),"+f"(d[89]),"+f"(d[90]),"+f"(d[91]),"+f"(d[92]),"+f"(d[93]),"+f"(d[94]),"+f"(d[95]) : "r"(a[0]),"r"(a[1]),"r"(a[2]),"r"(a[3]),"l"(db),"r"(sc));
}
__device__ __forceinline__ void wg_ss192_11(float* d, uint64_t da, uint64_t db, int sc) {
  asm volatile("{.reg .pred p; setp.ne.b32 p, %98, 0; wgmma.mma_async.sync.aligned.m64n192k16.f32.bf16.bf16 {%0,%1,%2,%3,%4,%5,%6,%7,%8,%9,%10,%11,%12,%13,%14,%15,%16,%17,%18,%19,%20,%21,%22,%23,%24,%25,%26,%27,%28,%29,%30,%31,%32,%33,%34,%35,%36,%37,%38,%39,%40,%41,%42,%43,%44,%45,%46,%47,%48,%49,%50,%51,%52,%53,%54,%55,%56,%57,%58,%59,%60,%61,%62,%63,%64,%65,%66,%67,%68,%69,%70,%71,%72,%73,%74,%75,%76,%77,%78,%79,%80,%81,%82,%83,%84,%85,%86,%87,%88,%89,%90,%91,%92,%93,%94,%95}, %96, %97, p, 1, 1, 1, 1;}"
    : "+f"(d[0]),"+f"(d[1]),"+f"(d[2]),"+f"(d[3]),"+f"(d[4]),"+f"(d[5]),"+f"(d[6]),"+f"(d[7]),"+f"(d[8]),"+f"(d[9]),"+f"(d[10]),"+f"(d[11]),"+f"(d[12]),"+f"(d[13]),"+f"(d[14]),"+f"(d[15]),"+f"(d[16]),"+f"(d[17]),"+f"(d[18]),"+f"(d[19]),"+f"(d[20]),"+f"(d[21]),"+f"(d[22]),"+f"(d[23]),"+f"(d[24]),"+f"(d[25]),"+f"(d[26]),"+f"(d[27]),"+f"(d[28]),"+f"(d[29]),"+f"(d[30]),"+f"(d[31]),"+f"(d[32]),"+f"(d[33]),"+f"(d[34]),"+f"(d[35]),"+f"(d[36]),"+f"(d[37]),"+f"(d[38]),"+f"(d[39]),"+f"(d[40]),"+f"(d[41]),"+f"(d[42]),"+f"(d[43]),"+f"(d[44]),"+f"(d[45]),"+f"(d[46]),"+f"(d[47]),"+f"(d[48]),"+f"(d[49]),"+f"(d[50]),"+f"(d[51]),"+f"(d[52]),"+f"(d[53]),"+f"(d[54]),"+f"(d[55]),"+f"(d[56]),"+f"(d[57]),"+f"(d[58]),"+f"(d[59]),"+f"(d[60]),"+f"(d[61]),"+f"(d[62]),"+f"(d[63]),"+f"(d[64]),"+f"(d[65]),"+f"(d[66]),"+f"(d[67]),"+f"(d[68]),"+f"(d[69]),"+f"(d[70]),"+f"(d[71]),"+f"(d[72]),"+f"(d[73]),"+f"(d[74]),"+f"(d[75]),"+f"(d[76]),"+f"(d[77]),"+f"(d[78]),"+f"(d[79]),"+f"(d[80]),"+f"(d[81]),"+f"(d[82]),"+f"(d[83]),"+f"(d[84]),"+f"(d[85]),"+f"(d[86]),"+f"(d[87]),"+f"(d[88]),"+f"(d[89]),"+f"(d[90]),"+f"(d[91]),"+f"(d[92]),"+f"(d[93]),"+f"(d[94]),"+f"(d[95]) : "l"(da),"l"(db),"r"(sc));
}
__device__ __forceinline__ void wg_ss192_01(float* d, uint64_t da, uint64_t db, int sc) {
  asm volatile("{.reg .pred p; setp.ne.b32 p, %98, 0; wgmma.mma_async.sync.aligned.m64n192k16.f32.bf16.bf16 {%0,%1,%2,%3,%4,%5,%6,%7,%8,%9,%10,%11,%12,%13,%14,%15,%16,%17,%18,%19,%20,%21,%22,%23,%24,%25,%26,%27,%28,%29,%30,%31,%32,%33,%34,%35,%36,%37,%38,%39,%40,%41,%42,%43,%44,%45,%46,%47,%48,%49,%50,%51,%52,%53,%54,%55,%56,%57,%58,%59,%60,%61,%62,%63,%64,%65,%66,%67,%68,%69,%70,%71,%72,%73,%74,%75,%76,%77,%78,%79,%80,%81,%82,%83,%84,%85,%86,%87,%88,%89,%90,%91,%92,%93,%94,%95}, %96, %97, p, 1, 1, 0, 1;}"
    : "+f"(d[0]),"+f"(d[1]),"+f"(d[2]),"+f"(d[3]),"+f"(d[4]),"+f"(d[5]),"+f"(d[6]),"+f"(d[7]),"+f"(d[8]),"+f"(d[9]),"+f"(d[10]),"+f"(d[11]),"+f"(d[12]),"+f"(d[13]),"+f"(d[14]),"+f"(d[15]),"+f"(d[16]),"+f"(d[17]),"+f"(d[18]),"+f"(d[19]),"+f"(d[20]),"+f"(d[21]),"+f"(d[22]),"+f"(d[23]),"+f"(d[24]),"+f"(d[25]),"+f"(d[26]),"+f"(d[27]),"+f"(d[28]),"+f"(d[29]),"+f"(d[30]),"+f"(d[31]),"+f"(d[32]),"+f"(d[33]),"+f"(d[34]),"+f"(d[35]),"+f"(d[36]),"+f"(d[37]),"+f"(d[38]),"+f"(d[39]),"+f"(d[40]),"+f"(d[41]),"+f"(d[42]),"+f"(d[43]),"+f"(d[44]),"+f"(d[45]),"+f"(d[46]),"+f"(d[47]),"+f"(d[48]),"+f"(d[49]),"+f"(d[50]),"+f"(d[51]),"+f"(d[52]),"+f"(d[53]),"+f"(d[54]),"+f"(d[55]),"+f"(d[56]),"+f"(d[57]),"+f"(d[58]),"+f"(d[59]),"+f"(d[60]),"+f"(d[61]),"+f"(d[62]),"+f"(d[63]),"+f"(d[64]),"+f"(d[65]),"+f"(d[66]),"+f"(d[67]),"+f"(d[68]),"+f"(d[69]),"+f"(d[70]),"+f"(d[71]),"+f"(d[72]),"+f"(d[73]),"+f"(d[74]),"+f"(d[75]),"+f"(d[76]),"+f"(d[77]),"+f"(d[78]),"+f"(d[79]),"+f"(d[80]),"+f"(d[81]),"+f"(d[82]),"+f"(d[83]),"+f"(d[84]),"+f"(d[85]),"+f"(d[86]),"+f"(d[87]),"+f"(d[88]),"+f"(d[89]),"+f"(d[90]),"+f"(d[91]),"+f"(d[92]),"+f"(d[93]),"+f"(d[94]),"+f"(d[95]) : "l"(da),"l"(db),"r"(sc));
}
__device__ __forceinline__ void wg_ss64_11(float* d, uint64_t da, uint64_t db, int sc) {
  asm volatile("{.reg .pred p; setp.ne.b32 p, %34, 0; wgmma.mma_async.sync.aligned.m64n64k16.f32.bf16.bf16 {%0,%1,%2,%3,%4,%5,%6,%7,%8,%9,%10,%11,%12,%13,%14,%15,%16,%17,%18,%19,%20,%21,%22,%23,%24,%25,%26,%27,%28,%29,%30,%31}, %32, %33, p, 1, 1, 1, 1;}"
    : "+f"(d[0]),"+f"(d[1]),"+f"(d[2]),"+f"(d[3]),"+f"(d[4]),"+f"(d[5]),"+f"(d[6]),"+f"(d[7]),"+f"(d[8]),"+f"(d[9]),"+f"(d[10]),"+f"(d[11]),"+f"(d[12]),"+f"(d[13]),"+f"(d[14]),"+f"(d[15]),"+f"(d[16]),"+f"(d[17]),"+f"(d[18]),"+f"(d[19]),"+f"(d[20]),"+f"(d[21]),"+f"(d[22]),"+f"(d[23]),"+f"(d[24]),"+f"(d[25]),"+f"(d[26]),"+f"(d[27]),"+f"(d[28]),"+f"(d[29]),"+f"(d[30]),"+f"(d[31]) : "l"(da),"l"(db),"r"(sc));
}
__device__ __forceinline__ void wg_ss64_01(float* d, uint64_t da, uint64_t db, int sc) {
  asm volatile("{.reg .pred p; setp.ne.b32 p, %34, 0; wgmma.mma_async.sync.aligned.m64n64k16.f32.bf16.bf16 {%0,%1,%2,%3,%4,%5,%6,%7,%8,%9,%10,%11,%12,%13,%14,%15,%16,%17,%18,%19,%20,%21,%22,%23,%24,%25,%26,%27,%28,%29,%30,%31}, %32, %33, p, 1, 1, 0, 1;}"
    : "+f"(d[0]),"+f"(d[1]),"+f"(d[2]),"+f"(d[3]),"+f"(d[4]),"+f"(d[5]),"+f"(d[6]),"+f"(d[7]),"+f"(d[8]),"+f"(d[9]),"+f"(d[10]),"+f"(d[11]),"+f"(d[12]),"+f"(d[13]),"+f"(d[14]),"+f"(d[15]),"+f"(d[16]),"+f"(d[17]),"+f"(d[18]),"+f"(d[19]),"+f"(d[20]),"+f"(d[21]),"+f"(d[22]),"+f"(d[23]),"+f"(d[24]),"+f"(d[25]),"+f"(d[26]),"+f"(d[27]),"+f"(d[28]),"+f"(d[29]),"+f"(d[30]),"+f"(d[31]) : "l"(da),"l"(db),"r"(sc));
}
__device__ __forceinline__ void wg_ss128_11(float* d, uint64_t da, uint64_t db, int sc) {
  asm volatile("{.reg .pred p; setp.ne.b32 p, %66, 0; wgmma.mma_async.sync.aligned.m64n128k16.f32.bf16.bf16 {%0,%1,%2,%3,%4,%5,%6,%7,%8,%9,%10,%11,%12,%13,%14,%15,%16,%17,%18,%19,%20,%21,%22,%23,%24,%25,%26,%27,%28,%29,%30,%31,%32,%33,%34,%35,%36,%37,%38,%39,%40,%41,%42,%43,%44,%45,%46,%47,%48,%49,%50,%51,%52,%53,%54,%55,%56,%57,%58,%59,%60,%61,%62,%63}, %64, %65, p, 1, 1, 1, 1;}"
    : "+f"(d[0]),"+f"(d[1]),"+f"(d[2]),"+f"(d[3]),"+f"(d[4]),"+f"(d[5]),"+f"(d[6]),"+f"(d[7]),"+f"(d[8]),"+f"(d[9]),"+f"(d[10]),"+f"(d[11]),"+f"(d[12]),"+f"(d[13]),"+f"(d[14]),"+f"(d[15]),"+f"(d[16]),"+f"(d[17]),"+f"(d[18]),"+f"(d[19]),"+f"(d[20]),"+f"(d[21]),"+f"(d[22]),"+f"(d[23]),"+f"(d[24]),"+f"(d[25]),"+f"(d[26]),"+f"(d[27]),"+f"(d[28]),"+f"(d[29]),"+f"(d[30]),"+f"(d[31]),"+f"(d[32]),"+f"(d[33]),"+f"(d[34]),"+f"(d[35]),"+f"(d[36]),"+f"(d[37]),"+f"(d[38]),"+f"(d[39]),"+f"(d[40]),"+f"(d[41]),"+f"(d[42]),"+f"(d[43]),"+f"(d[44]),"+f"(d[45]),"+f"(d[46]),"+f"(d[47]),"+f"(d[48]),"+f"(d[49]),"+f"(d[50]),"+f"(d[51]),"+f"(d[52]),"+f"(d[53]),"+f"(d[54]),"+f"(d[55]),"+f"(d[56]),"+f"(d[57]),"+f"(d[58]),"+f"(d[59]),"+f"(d[60]),"+f"(d[61]),"+f"(d[62]),"+f"(d[63]) : "l"(da),"l"(db),"r"(sc));
}
__device__ __forceinline__ void wg_ss128_01(float* d, uint64_t da, uint64_t db, int sc) {
  asm volatile("{.reg .pred p; setp.ne.b32 p, %66, 0; wgmma.mma_async.sync.aligned.m64n128k16.f32.bf16.bf16 {%0,%1,%2,%3,%4,%5,%6,%7,%8,%9,%10,%11,%12,%13,%14,%15,%16,%17,%18,%19,%20,%21,%22,%23,%24,%25,%26,%27,%28,%29,%30,%31,%32,%33,%34,%35,%36,%37,%38,%39,%40,%41,%42,%43,%44,%45,%46,%47,%48,%49,%50,%51,%52,%53,%54,%55,%56,%57,%58,%59,%60,%61,%62,%63}, %64, %65, p, 1, 1, 0, 1;}"
    : "+f"(d[0]),"+f"(d[1]),"+f"(d[2]),"+f"(d[3]),"+f"(d[4]),"+f"(d[5]),"+f"(d[6]),"+f"(d[7]),"+f"(d[8]),"+f"(d[9]),"+f"(d[10]),"+f"(d[11]),"+f"(d[12]),"+f"(d[13]),"+f"(d[14]),"+f"(d[15]),"+f"(d[16]),"+f"(d[17]),"+f"(d[18]),"+f"(d[19]),"+f"(d[20]),"+f"(d[21]),"+f"(d[22]),"+f"(d[23]),"+f"(d[24]),"+f"(d[25]),"+f"(d[26]),"+f"(d[27]),"+f"(d[28]),"+f"(d[29]),"+f"(d[30]),"+f"(d[31]),"+f"(d[32]),"+f"(d[33]),"+f"(d[34]),"+f"(d[35]),"+f"(d[36]),"+f"(d[37]),"+f"(d[38]),"+f"(d[39]),"+f"(d[40]),"+f"(d[41]),"+f"(d[42]),"+f"(d[43]),"+f"(d[44]),"+f"(d[45]),"+f"(d[46]),"+f"(d[47]),"+f"(d[48]),"+f"(d[49]),"+f"(d[50]),"+f"(d[51]),"+f"(d[52]),"+f"(d[53]),"+f"(d[54]),"+f"(d[55]),"+f"(d[56]),"+f"(d[57]),"+f"(d[58]),"+f"(d[59]),"+f"(d[60]),"+f"(d[61]),"+f"(d[62]),"+f"(d[63]) : "l"(da),"l"(db),"r"(sc));
}
__device__ __forceinline__ void wg_ss96_01(float* d, uint64_t da, uint64_t db, int sc) {
  asm volatile("{.reg .pred p; setp.ne.b32 p, %50, 0; wgmma.mma_async.sync.aligned.m64n96k16.f32.bf16.bf16 {%0,%1,%2,%3,%4,%5,%6,%7,%8,%9,%10,%11,%12,%13,%14,%15,%16,%17,%18,%19,%20,%21,%22,%23,%24,%25,%26,%27,%28,%29,%30,%31,%32,%33,%34,%35,%36,%37,%38,%39,%40,%41,%42,%43,%44,%45,%46,%47}, %48, %49, p, 1, 1, 0, 1;}"
    : "+f"(d[0]),"+f"(d[1]),"+f"(d[2]),"+f"(d[3]),"+f"(d[4]),"+f"(d[5]),"+f"(d[6]),"+f"(d[7]),"+f"(d[8]),"+f"(d[9]),"+f"(d[10]),"+f"(d[11]),"+f"(d[12]),"+f"(d[13]),"+f"(d[14]),"+f"(d[15]),"+f"(d[16]),"+f"(d[17]),"+f"(d[18]),"+f"(d[19]),"+f"(d[20]),"+f"(d[21]),"+f"(d[22]),"+f"(d[23]),"+f"(d[24]),"+f"(d[25]),"+f"(d[26]),"+f"(d[27]),"+f"(d[28]),"+f"(d[29]),"+f"(d[30]),"+f"(d[31]),"+f"(d[32]),"+f"(d[33]),"+f"(d[34]),"+f"(d[35]),"+f"(d[36]),"+f"(d[37]),"+f"(d[38]),"+f"(d[39]),"+f"(d[40]),"+f"(d[41]),"+f"(d[42]),"+f"(d[43]),"+f"(d[44]),"+f"(d[45]),"+f"(d[46]),"+f"(d[47]) : "l"(da),"l"(db),"r"(sc));
}
__device__ __forceinline__ void wg_rs64_1(float* d, const uint32_t* a, uint64_t db, int sc) {
  asm volatile("{.reg .pred p; setp.ne.b32 p, %37, 0; wgmma.mma_async.sync.aligned.m64n64k16.f32.bf16.bf16 {%0,%1,%2,%3,%4,%5,%6,%7,%8,%9,%10,%11,%12,%13,%14,%15,%16,%17,%18,%19,%20,%21,%22,%23,%24,%25,%26,%27,%28,%29,%30,%31}, {%32,%33,%34,%35}, %36, p, 1, 1, 1;}"
    : "+f"(d[0]),"+f"(d[1]),"+f"(d[2]),"+f"(d[3]),"+f"(d[4]),"+f"(d[5]),"+f"(d[6]),"+f"(d[7]),"+f"(d[8]),"+f"(d[9]),"+f"(d[10]),"+f"(d[11]),"+f"(d[12]),"+f"(d[13]),"+f"(d[14]),"+f"(d[15]),"+f"(d[16]),"+f"(d[17]),"+f"(d[18]),"+f"(d[19]),"+f"(d[20]),"+f"(d[21]),"+f"(d[22]),"+f"(d[23]),"+f"(d[24]),"+f"(d[25]),"+f"(d[26]),"+f"(d[27]),"+f"(d[28]),"+f"(d[29]),"+f"(d[30]),"+f"(d[31]) : "r"(a[0]),"r"(a[1]),"r"(a[2]),"r"(a[3]),"l"(db),"r"(sc));
}
__device__ __forceinline__ void wg_rs96_1(float* d, const uint32_t* a, uint64_t db, int sc) {
  asm volatile("{.reg .pred p; setp.ne.b32 p, %53, 0; wgmma.mma_async.sync.aligned.m64n96k16.f32.bf16.bf16 {%0,%1,%2,%3,%4,%5,%6,%7,%8,%9,%10,%11,%12,%13,%14,%15,%16,%17,%18,%19,%20,%21,%22,%23,%24,%25,%26,%27,%28,%29,%30,%31,%32,%33,%34,%35,%36,%37,%38,%39,%40,%41,%42,%43,%44,%45,%46,%47}, {%48,%49,%50,%51}, %52, p, 1, 1, 1;}"
    : "+f"(d[0]),"+f"(d[1]),"+f"(d[2]),"+f"(d[3]),"+f"(d[4]),"+f"(d[5]),"+f"(d[6]),"+f"(d[7]),"+f"(d[8]),"+f"(d[9]),"+f"(d[10]),"+f"(d[11]),"+f"(d[12]),"+f"(d[13]),"+f"(d[14]),"+f"(d[15]),"+f"(d[16]),"+f"(d[17]),"+f"(d[18]),"+f"(d[19]),"+f"(d[20]),"+f"(d[21]),"+f"(d[22]),"+f"(d[23]),"+f"(d[24]),"+f"(d[25]),"+f"(d[26]),"+f"(d[27]),"+f"(d[28]),"+f"(d[29]),"+f"(d[30]),"+f"(d[31]),"+f"(d[32]),"+f"(d[33]),"+f"(d[34]),"+f"(d[35]),"+f"(d[36]),"+f"(d[37]),"+f"(d[38]),"+f"(d[39]),"+f"(d[40]),"+f"(d[41]),"+f"(d[42]),"+f"(d[43]),"+f"(d[44]),"+f"(d[45]),"+f"(d[46]),"+f"(d[47]) : "r"(a[0]),"r"(a[1]),"r"(a[2]),"r"(a[3]),"l"(db),"r"(sc));
}
__device__ __forceinline__ void wg_ss160_01(float* d, uint64_t da, uint64_t db, int sc) {
  asm volatile("{.reg .pred p; setp.ne.b32 p, %82, 0; wgmma.mma_async.sync.aligned.m64n160k16.f32.bf16.bf16 {%0,%1,%2,%3,%4,%5,%6,%7,%8,%9,%10,%11,%12,%13,%14,%15,%16,%17,%18,%19,%20,%21,%22,%23,%24,%25,%26,%27,%28,%29,%30,%31,%32,%33,%34,%35,%36,%37,%38,%39,%40,%41,%42,%43,%44,%45,%46,%47,%48,%49,%50,%51,%52,%53,%54,%55,%56,%57,%58,%59,%60,%61,%62,%63,%64,%65,%66,%67,%68,%69,%70,%71,%72,%73,%74,%75,%76,%77,%78,%79}, %80, %81, p, 1, 1, 0, 1;}"
    : "+f"(d[0]),"+f"(d[1]),"+f"(d[2]),"+f"(d[3]),"+f"(d[4]),"+f"(d[5]),"+f"(d[6]),"+f"(d[7]),"+f"(d[8]),"+f"(d[9]),"+f"(d[10]),"+f"(d[11]),"+f"(d[12]),"+f"(d[13]),"+f"(d[14]),"+f"(d[15]),"+f"(d[16]),"+f"(d[17]),"+f"(d[18]),"+f"(d[19]),"+f"(d[20]),"+f"(d[21]),"+f"(d[22]),"+f"(d[23]),"+f"(d[24]),"+f"(d[25]),"+f"(d[26]),"+f"(d[27]),"+f"(d[28]),"+f"(d[29]),"+f"(d[30]),"+f"(d[31]),"+f"(d[32]),"+f"(d[33]),"+f"(d[34]),"+f"(d[35]),"+f"(d[36]),"+f"(d[37]),"+f"(d[38]),"+f"(d[39]),"+f"(d[40]),"+f"(d[41]),"+f"(d[42]),"+f"(d[43]),"+f"(d[44]),"+f"(d[45]),"+f"(d[46]),"+f"(d[47]),"+f"(d[48]),"+f"(d[49]),"+f"(d[50]),"+f"(d[51]),"+f"(d[52]),"+f"(d[53]),"+f"(d[54]),"+f"(d[55]),"+f"(d[56]),"+f"(d[57]),"+f"(d[58]),"+f"(d[59]),"+f"(d[60]),"+f"(d[61]),"+f"(d[62]),"+f"(d[63]),"+f"(d[64]),"+f"(d[65]),"+f"(d[66]),"+f"(d[67]),"+f"(d[68]),"+f"(d[69]),"+f"(d[70]),"+f"(d[71]),"+f"(d[72]),"+f"(d[73]),"+f"(d[74]),"+f"(d[75]),"+f"(d[76]),"+f"(d[77]),"+f"(d[78]),"+f"(d[79]) : "l"(da),"l"(db),"r"(sc));
}
__device__ __forceinline__ void wg_rs160_1(float* d, const uint32_t* a, uint64_t db, int sc) {
  asm volatile("{.reg .pred p; setp.ne.b32 p, %85, 0; wgmma.mma_async.sync.aligned.m64n160k16.f32.bf16.bf16 {%0,%1,%2,%3,%4,%5,%6,%7,%8,%9,%10,%11,%12,%13,%14,%15,%16,%17,%18,%19,%20,%21,%22,%23,%24,%25,%26,%27,%28,%29,%30,%31,%32,%33,%34,%35,%36,%37,%38,%39,%40,%41,%42,%43,%44,%45,%46,%47,%48,%49,%50,%51,%52,%53,%54,%55,%56,%57,%58,%59,%60,%61,%62,%63,%64,%65,%66,%67,%68,%69,%70,%71,%72,%73,%74,%75,%76,%77,%78,%79}, {%80,%81,%82,%83}, %84, p, 1, 1, 1;}"
    : "+f"(d[0]),"+f"(d[1]),"+f"(d[2]),"+f"(d[3]),"+f"(d[4]),"+f"(d[5]),"+f"(d[6]),"+f"(d[7]),"+f"(d[8]),"+f"(d[9]),"+f"(d[10]),"+f"(d[11]),"+f"(d[12]),"+f"(d[13]),"+f"(d[14]),"+f"(d[15]),"+f"(d[16]),"+f"(d[17]),"+f"(d[18]),"+f"(d[19]),"+f"(d[20]),"+f"(d[21]),"+f"(d[22]),"+f"(d[23]),"+f"(d[24]),"+f"(d[25]),"+f"(d[26]),"+f"(d[27]),"+f"(d[28]),"+f"(d[29]),"+f"(d[30]),"+f"(d[31]),"+f"(d[32]),"+f"(d[33]),"+f"(d[34]),"+f"(d[35]),"+f"(d[36]),"+f"(d[37]),"+f"(d[38]),"+f"(d[39]),"+f"(d[40]),"+f"(d[41]),"+f"(d[42]),"+f"(d[43]),"+f"(d[44]),"+f"(d[45]),"+f"(d[46]),"+f"(d[47]),"+f"(d[48]),"+f"(d[49]),"+f"(d[50]),"+f"(d[51]),"+f"(d[52]),"+f"(d[53]),"+f"(d[54]),"+f"(d[55]),"+f"(d[56]),"+f"(d[57]),"+f"(d[58]),"+f"(d[59]),"+f"(d[60]),"+f"(d[61]),"+f"(d[62]),"+f"(d[63]),"+f"(d[64]),"+f"(d[65]),"+f"(d[66]),"+f"(d[67]),"+f"(d[68]),"+f"(d[69]),"+f"(d[70]),"+f"(d[71]),"+f"(d[72]),"+f"(d[73]),"+f"(d[74]),"+f"(d[75]),"+f"(d[76]),"+f"(d[77]),"+f"(d[78]),"+f"(d[79]) : "r"(a[0]),"r"(a[1]),"r"(a[2]),"r"(a[3]),"l"(db),"r"(sc));
}
__device__ __forceinline__ void wg_ss8_10(float* d, uint64_t da, uint64_t db, int sc) {
  asm volatile("{.reg .pred p; setp.ne.b32 p, %6, 0; wgmma.mma_async.sync.aligned.m64n8k16.f32.bf16.bf16 {%0,%1,%2,%3}, %4, %5, p, 1, 1, 1, 0;}"
    : "+f"(d[0]),"+f"(d[1]),"+f"(d[2]),"+f"(d[3]) : "l"(da),"l"(db),"r"(sc));
}
__device__ __forceinline__ void wg_ss8_if(float* d, uint64_t da, uint64_t db, int sc, int skip) {
  asm volatile("{.reg .pred p, q; setp.ne.b32 p, %6, 0; setp.eq.b32 q, %7, 0; @q wgmma.mma_async.sync.aligned.m64n8k16.f32.bf16.bf16 {%0,%1,%2,%3}, %4, %5, p, 1, 1, 1, 0;}"
    : "+f"(d[0]),"+f"(d[1]),"+f"(d[2]),"+f"(d[3]) : "l"(da),"l"(db),"r"(sc),"r"(skip));
}

constexpr uint32_t DB = 1024;
constexpr int UNIT = 8192, WSLOT = 16384, W2TILE = 24576, OFF_R = 12 * UNIT;
constexpr int OFF_PB = 26 * UNIT;
constexpr int OFF_CV = OFF_PB + 16384, OFF_ST = OFF_CV + 768, OFF_TS = OFF_ST + 256, OFF_MODR = OFF_TS + 512, OFF_ROLE = OFF_MODR + 80, OFF_BAR = OFF_ROLE + 16, SMEM_BYTES = OFF_BAR + 1400;
constexpr int OFF_BX = OFF_PB, OFF_AX = OFF_BX + 12288, OFF_RT = OFF_AX + 2048, OFF_GB = OFF_RT + 512, OFF_CO = OFF_CV;
constexpr int OFF_UV = 4 * UNIT, OFF_SX = 24 * UNIT, OFF_XCH = 12 * UNIT;
constexpr int OFF_Q = 99328, KV_V = 4096, KV_H = 8192, F_E = 128, F_O = 4288, OFF_WM = 20 * UNIT, OFF_TAP = 12672, OFF_MR = 25 * UNIT;
constexpr uint64_t pk5(int a, int b, int c, int d, int e) { return (uint64_t)(a / 128) | (uint64_t)(b / 128) << 12 | (uint64_t)(c / 128) << 24 | (uint64_t)(d / 128) << 36 | (uint64_t)(e / 128) << 48; }
constexpr uint64_t T_KV = pk5(119808, 16384, 130048, 65536, 49152), T_F = pk5(140288, 90368, 148736, 81920, OFF_PB), T_X = pk5(0, 4224, 8448, 0, 4224),
                   T_P = pk5(32768, 16384, 65536, 81920, OFF_PB);
__host__ __device__ __forceinline__ uint32_t tab(uint64_t t, int c) { return ((uint32_t)(t >> (12 * c)) & 0xFFF) << 7; }
enum { B_KV = 0, B_FRAW = 5, B_Q = 10, B_WM = 15, B_XR = 17, B_MR = B_XR + 5, B_QTOK, B_ST1, B_MODR, B_ROLE = B_MODR + 5, B_FL = 32, B_PFULL = B_FL + 5, B_PEMPTY = B_PFULL + 5, B_FRDY = B_PEMPTY + 5,
       B_G = B_FRDY + 5, B_EXT = B_G + 2, B_QTD, B_ED, B_S2 = B_ED + 2, B_GB, B_FULL = 60, B_RETRY = B_FULL + 43, B_XFREE = B_RETRY + 8, B_BX, B_UVB, B_CO, B_SX, B_EMPTY = 121, B_SC = 164, B_STD = B_SC + 5, B_LAG, B_LAST };
static_assert(B_ROLE < B_FL && B_GB < B_FULL && B_SX + 5 <= B_EMPTY - 1 && OFF_MR == OFF_SX + 8192 && SMEM_BYTES <= 232448, "barrier groups");
#define BAR(i) (base + OFF_BAR + 8 * (i))

struct Maps { CUtensorMap km, v, q, fm, wmp, kh, tap, wm, w1a, w3a, xs, w1u, w3u, w1b, w3b, x1s, x1b, w2a, w2b, outa, outb; };
struct Ptrs {
  const bf16 *c, *ssmd; Scratch* g; int ulo; float one; uint32_t hl[8], wdep[30], adep[14]; uint2 w2t[12]; int hid[4][9];
};

constexpr uint64_t C_prog0 = 0x676360, C_prog1 = 0x746209;
constexpr uint32_t C_mq = 3, C_xh = 0, C_xdep = B_EMPTY + 32, C_hstart = 0 | 0 << 16, C_hpause = 0, C_uvd = 0x33511, C_mpos = 0, C_wt0 = 11400, C_wpace = 900;
#define C_prog (wg ? C_prog1 : C_prog0)
#define K(x) C_##x
#define prog_of(wg) C_prog

#define REGION_IDS int tid, lane, bid; \
  asm volatile("mov.u32 %0, %%tid.x;" : "=r"(tid)); asm volatile("mov.u32 %0, %%laneid;" : "=r"(lane)); asm volatile("mov.u32 %0, %%ctaid.x;" : "=r"(bid)); \
  const int i0 = tid & 127; (void)i0; (void)lane; (void)bid

#define ffn_role(h, j, r) do { \
  mbar_wait(BAR(B_ROLE)); \
  r = __shfl_sync(~0u, lds32(base + OFF_ROLE), 0); \
  asm volatile("mov.u32 %0, %%ctaid.x;" : "=r"(h)); \
  h &= 1; j = r >> 4; r &= 15; } while (0)
__device__ __forceinline__ void rank_pair(Scratch* G, uint32_t base, uint32_t epoch, bool put) {
  REGION_IDS;
  uint32_t t;
  asm volatile("mov.u32 %0, %%smid;" : "=r"(t));
  t >>= 1;
  const uint32_t q = (t - 32) * 37 >> 8, g = t < 32 ? t & 7 : t < 60 ? t - 31 - 7 * q : t < 62 ? t - 54 : 0;
  const uint32_t key = epoch << 20 | (g & 3) << 18 | (g & 4) << 15 | (t & 127) << 6 | bid >> 1;
  if (put) {
    if (lane == (bid & 1) * 99) publish(&G->key[bid >> 1], key);
    return;
  }
  uint2 x;
  int it = 0;
#pragma unroll 1
  do x = ld_relaxed64(&G->key[2 * lane]); while (__any_sync(~0u, ((x.x ^ key) | (x.y ^ key)) >> 20) && ++it < SPIN_LIMIT);
  t = __shfl_sync(~0u, bid & 2 ? x.y : x.x, bid >> 2);
  sts32(base + OFF_ROLE, __popc(__ballot_sync(~0u, x.x < t)) + __popc(__ballot_sync(~0u, x.y < t)));
  arrive1(BAR(B_ROLE));
}
__device__ __forceinline__ int mod_ch(int p) { return p < 40 ? (p >> 3) * 128 + (p & 1) * 64 : 64 * (p < 50 ? p - 40 : p - 50); }
__device__ __forceinline__ int mod_col(int p) { return mod_ch(p) + 640 * (p < 40 ? 0x4210 >> (2 * (p & 6)) & 7 : p < 50 ? 3 : 5); }
__device__ __forceinline__ uint32_t mod_sum(uint2 v) { return pack_bf16(0.f, __uint_as_float(v.x) + __uint_as_float(v.y)); }
#define UVS 5
#define XP 2
#define GA 3
#define GB 1
#define HL 0
#define EH 0
#define MG 4
#define SG 0x88
#define SPL 41
#define NP 8
__device__ __forceinline__ int nib(uint32_t t, int i) { return (t >> (4 * i)) & 15; }
__device__ __forceinline__ int w_block(int up, int m) { return m < 2 ? 2 * up + m : 4 + up; }
__host__ __device__ constexpr int w2_at(int v) { return UNIT * (v == 1 ? 0 : 0x0811030C18ull >> (v - (v > 1)) % 5 * 8 & 255); }
__host__ __device__ constexpr int hid_at(int m, int g) { return UNIT * ((g ? 0x0200150710ull : 0x010B14060Full) >> m % 5 * 8 & 255); }
__host__ __device__ constexpr int x1_at(int k) { return k < 4 ? 22 * UNIT + 4096 * k : OFF_BX + UNIT; }
__host__ __device__ constexpr uint32_t w2_desc(int v) { return (DB + w2_at(v)) >> 4 | UNIT << 12; }
__host__ __device__ constexpr int a_at(int n) { return WSLOT * (0x54323251041032ull >> 4 * n & 15); }
__host__ __device__ constexpr int second(int v) { return 0xDCBA657498ull >> 4 * v & 15; }

#define WINS "4444444444443444444"
#define ORDER "k1v1f0q0q1q2q3q4k2v2f1k3v3f2k4v4f3w0f4"
constexpr int NL = sizeof(ORDER) / 2, TA = 16, M8 = 3 << TA / 8;
__host__ __device__ constexpr int load_bar(int e) { return e < 0 ? B_KV : ORDER[2 * e + 1] - '0' + (ORDER[2 * e] == 'q' ? B_Q : ORDER[2 * e] == 'f' ? B_FRAW : ORDER[2 * e] == 'w' ? B_WM : B_KV); }
__host__ __device__ constexpr int load_gate(int e, int w) {
  int i = e, sum = 0;
  while (i >= -1 && sum + (i < 0 ? 8 : ORDER[2 * i] == 'w' ? 10 : 4) <= 4 * w) { sum += i < 0 ? 8 : ORDER[2 * i] == 'w' ? 10 : 4; i--; }
  for (; i >= -1; i--) {
    bool ok = i < e;
    for (int k = e; k < NL; k++) ok = ok && load_bar(k) != load_bar(i);
    if (ok) return load_bar(i);
  }
  return -1;
}
template <int E> __device__ __forceinline__ void loads(const Ptrs& P, const Maps& maps, uint32_t base) {
  if constexpr (E < NL) {
    constexpr int r = ORDER[2 * E + 1] - '0';
    constexpr char x = ORDER[2 * E];
    const int c0 = 128 * r + 64 * (blockIdx.x & 1), c1 = 2 * (blockIdx.x & 126);
    constexpr int g = load_gate(E, WINS[E] - '0');
    if (g >= 0 && (E == 0 || g != load_gate(E - 1, WINS[E ? E - 1 : 0] - '0'))) mbar_wait(BAR(g < 0 ? 0 : g));
    if (elect()) {
      if (x == 'k') { tma3d(base + tab(T_KV, r), &maps.km, c0, c1, 0, BAR(B_KV + r)); tma3d(base + tab(T_KV, r) + KV_H, &maps.kh, c0, c1 - 1, 5, BAR(B_KV + r)); }
      if (x == 'v') tma3d(base + tab(T_KV, r) + KV_V, &maps.v, c0, c1, 0, BAR(B_KV + r));
      if (x == 'q') tma3d(base + OFF_Q + 4096 * r, &maps.q, c0, c1, 0, BAR(B_Q + r));
      if (x == 'f') tma3d(base + tab(T_F, r) + F_E, &maps.fm, 0, 0, 128 * r + blockIdx.x, BAR(B_FRAW + r));
      if (x == 'w') tma3d(base + OFF_WM, &maps.wmp, mod_col(TA + (blockIdx.x >> 3)), 80 * (blockIdx.x & 7), 0, BAR(B_WM));
    }
    loads<E + 1>(P, maps, base);
  }
}

template <int U> __device__ __forceinline__ void cstep(float* acc, const uint32_t* A, uint64_t db) {
  const uint32_t* a = A + 4 * U;
  const uint64_t d = db + 16 * U;
  if (U == 4) { wg_rs64_0(acc + 96, A, db + 192, 0); wg_rs48_0(acc + 96, A + 4, db + 208, 1); wg_rs32_0(acc + 96, A + 8, db + 224, 1); wg_rs16_0(acc + 96, A + 12, db + 240, 1); }
  if (U <= 4) wg_rs192_0(acc, a, d, U);
  if (U == 5) wg_rs176_0(acc, a, d, 1);
  if (U == 6) wg_rs160_0(acc, a, d, 1);
  if (U == 7) wg_rs144_0(acc, a, d, 1);
  if (U == 8) wg_rs128_0(acc, a, d, 1);
  if (U == 9) wg_rs112_0(acc, a, d, 1);
  if (U == 10) wg_rs96_0(acc, a, d, 1);
  if (U == 11) wg_rs80_0(acc, a, d, 1);
  if (U == 12) wg_rs64_0(acc, a, d, 1);
  if (U == 13) wg_rs48_0(acc, a, d, 1);
  if (U == 14) wg_rs32_0(acc, a, d, 1);
  if (U == 15) wg_rs16_0(acc, a, d, 1);
}
template <int U0, int U1> __device__ __forceinline__ void csteps(float* acc, const uint32_t* A, uint64_t db) {
  cstep<U0>(acc, A, db);
  if constexpr (U0 > U1) csteps<U0 - 1, U1>(acc, A, db);
}
template <int U0, int U1> __device__ __forceinline__ void cload(uint32_t* A, uint32_t fa) {
  asm volatile("{ld.shared.b32 %0, [%4+%5]; ld.shared.b32 %1, [%4+%5+128]; ld.shared.b32 %2, [%4+%5+16]; ld.shared.b32 %3, [%4+%5+144];}"
               : "=r"(A[4 * U0]), "=r"(A[4 * U0 + 1]), "=r"(A[4 * U0 + 2]), "=r"(A[4 * U0 + 3]) : "r"(fa), "n"(256 * U0) : "memory");
  if constexpr (U0 > U1) cload<U0 - 1, U1>(A, fa);
}

template <int NK> __device__ __forceinline__ void mod_gemv(Scratch* G, uint32_t wm, int p, int part, int w, int lane, uint32_t par) {
  float d[4] = {};
  fence_regs(d);
  wg_fence();
#pragma unroll 1
  for (int k = 0; k < NK; k += 5) {
#pragma unroll
    for (int i = 0; i < 5; i++) wg_ss8_10(d, mkdesc(DB + wm + 2048 * (k + i), 16, 1024, 1), mkdesc(DB + OFF_CV + 32 * (k + i), 16, 128, 0), 1);
  }
  wg_commit();
  const int ch = mod_ch(p) + 16 * w + (lane >> 2);
  uint32_t* dst = (p < 40 ? &G->modc[ch & 127][p >> 3][4 * (p & 6)] : (uint32_t*)&G->modv[p >= 50][ch]) + part;
  wg_wait<0>();
  fence_regs(d);
  if (!(lane & 3)) {
    publish(dst, (__float_as_uint(d[0]) & ~1u) | par);
    publish(dst + (p < 40 ? 1280 : 16), (__float_as_uint(d[2]) & ~1u) | par);
    if (NK == 20 && p < 40 && (p & 6) == 6) {
      dst = (uint32_t*)&G->modv[2][ch] + part;
      publish(dst, (__float_as_uint(d[0]) & ~1u) | par);
      publish(dst + 16, (__float_as_uint(d[2]) & ~1u) | par);
    }
  }
}
__device__ __forceinline__ void mod_fetch(Scratch* G, uint32_t base, uint32_t epoch, uint32_t m8, uint32_t c, uint32_t c1) {
  REGION_IDS;
  const uint32_t* mp = &G->modc[bid][0][lane];
  auto unused = [&]() { return (lane & 6) && !(m8 >> c & 1); };
#pragma unroll 1
  for (int it = 0; c < c1 && it < SPIN_LIMIT; it++) {
    uint32_t m = ld_relaxed32(mp + 32 * c);
    const uint32_t m1 = ld_relaxed32(mp + 32 * min(c + 1, c1 - 1));
#pragma unroll 1
    for (int k = 0; k < 2 && c < c1 && __all_sync(~0u, unused() || !((m ^ epoch) & 1)); k++) {
      float x = unused() ? 0.f : __uint_as_float(m);
      x += __shfl_xor_sync(~0u, x, 1); x += __shfl_xor_sync(~0u, x, 2); x += __shfl_xor_sync(~0u, x, 4);
      const uint32_t y = __byte_perm(badd2(pack_bf16(0.f, x), (lane & 8) * 0x07F00000u), 0, 0x3232), ga = __shfl_sync(~0u, y, 16);
      sts32(base + OFF_MODR + 16 * c + 4 * (lane >> 3), lane < 16 ? bmul2(y, ga) : y);
      arrive1(BAR(B_MODR + c));
      if (lane >= 30 && (m8 >> c & 1)) publish((uint32_t*)&G->modv[2][128 * c + bid] + (lane & 1), ((lane & 1 ? 0 : __float_as_uint(x)) & ~1u) | (epoch & 1));
      m = m1;
      c++;
    }
  }
}
__device__ __forceinline__ void add4(uint4& y, const uint4& z) { y.x = badd2(y.x, z.x); y.y = badd2(y.y, z.y); y.z = badd2(y.z, z.z); y.w = badd2(y.w, z.w); }
template <bool FIRST> __device__ __forceinline__ void e_round(Scratch* G, uint32_t base, uint32_t sa, uint4*& gp, uint4* q, int c, int w, uint32_t tag, uint32_t epoch) {
  constexpr int QO = -D_ * 256;
  mbar_wait(BAR(B_MODR + c));
  const uint4 co = lds128(base + OFF_MODR + 16 * c);
  mbar_wait(BAR(B_PFULL + c));
  const uint32_t pb = sa + tab(T_P, c);
  uint4 l[2][6];
  auto load = [&](int hf, int k) { l[hf][k] = lds128((k < 4 ? pb + 4096 * k : sa + OFF_MR + 4096 * (k - 4)) + 2048 * hf); };
#pragma unroll
  for (int hf = 0; hf < 2; hf++) {
    uint4 &y = l[hf][0], &z = l[hf][4], &m = l[hf][5];
    load(hf, 0);
    if (!FIRST) {
      load(hf, 1);
      add4(y, l[hf][1]);
      load(hf, 2); load(hf, 3);
      add4(l[hf][2], l[hf][3]);
      add4(y, l[hf][2]);
    }
    load(hf, 4); load(hf, 5);
    if (FIRST) {
#pragma unroll 1
      for (int it = 0; __any_sync(~0u, ((z.x >> 15 ^ epoch) | (m.x ^ epoch)) & tag) && it < SPIN_LIMIT; it++) {
        const uint4* sp = (const uint4*)G->st1 + (opaque(sa) - base >> 4) + 128 * hf;
        z = ld_relaxed128(sp);
        m = ld_relaxed128(sp + 256);
        sts128(sa + OFF_MR + 2048 * hf, z.x, z.y, z.z, z.w);
        sts128(sa + OFF_MR + 2048 * hf + 4096, m.x, m.y, m.z, m.w);
      }
      z.x &= 0xFFFF7FFFu;
      sts32(sa + OFF_MR + 2048 * hf, z.x);
    }
#pragma unroll 1
    for (int it = 0; __any_sync(~0u, (q[hf].x ^ epoch) & tag) && it < SPIN_LIMIT; it++) {
      q[hf] = ld_relaxed128(gp + QO + 128 * hf);
    }
    y.x = bfma2(bfma2(bfma2(q[hf].x, z.x, m.x), co.y, co.x), y.x, q[hf].x);
    auto hint = [&]() {
      __syncwarp();
      asm volatile("{.reg .pred p; elect.sync _|p, 0xffffffff; @p red.relaxed.gpu.global.add.u32 [%0], 1; @p mbarrier.arrive.shared::cta.b64 _, [%1];}"
                   ::"l"(G->xsh[c][2 * w + (blockIdx.x >> 6)]), "r"(BAR(B_PEMPTY + c)), "r"(y.x) : "memory");
    };
    if (hf && !EH) hint();
    y.y = bfma2(bfma2(bfma2(q[hf].y, z.y, m.y), co.y, co.x), y.y, q[hf].y);
    y.z = bfma2(bfma2(bfma2(q[hf].z, z.z, m.z), co.y, co.x), y.z, q[hf].z);
    y.w = bfma2(bfma2(bfma2(q[hf].w, z.w, m.w), co.y, co.x), y.w, q[hf].w);
    st_relaxed128(gp + 128 * hf, set_tag(bmul2(y.x, co.w), tag, epoch), bmul2(y.y, co.w), bmul2(y.z, co.w), bmul2(y.w, co.w));
    if (hf && EH == 1) hint();
    asm volatile("{.reg .pred p; .reg .b32 t; setp.ne.u32 p, %5, 0; max.u32 t, %1, 1; @!p st.relaxed.gpu.global.v4.u32 [%0+%6], {t,%2,%3,%4}; @p st.relaxed.gpu.global.v4.u32 [%0+%7], {t,%2,%3,%4};}"
                 ::"l"(gp + 128 * hf), "r"(y.x), "r"(y.y), "r"(y.z), "r"(y.w), "r"(epoch & 1), "n"(D_ * 4096), "n"(D_ * 8192) : "memory");
    if (hf && EH == 2) hint();
    if (c < 4) q[hf] = ld_relaxed128(gp + QO + 32768 + 128 * hf);
  }
  gp += 32768;
}
__device__ __forceinline__ void q_stats(uint32_t base, int w) {
  REGION_IDS;
  float s0 = 0.f, s1 = 0.f, q0 = 0.f, q1 = 0.f;
  const uint32_t a = OFF_Q + 1024 * w + 128 * (lane & 7) + (((lane >> 3) ^ (lane & 7)) << 4);
  const uint32_t ra = mapa(base + OFF_ST + 128 * (bid & 1) + 64 * (lane & 1) + 16 * w + 8 * (lane >> 2), lane >> 1 & 1), rb = mapa(BAR(B_ST1), lane >> 1 & 1);
  if (w == 3 && elect()) mbar_expect_tx(BAR(B_ST1), 256);
#pragma unroll 1
  for (int k = 0; k < 5; k++) {
    mbar_wait(BAR(B_Q + k));
    const uint32_t o = opaque(base + 4096 * k);
    const uint4 x = lds128(o + a), y = lds128(o + (a ^ 64));
    const uint32_t e[8] = {x.x, x.y, x.z, x.w, y.x, y.y, y.z, y.w};
#pragma unroll
    for (int i = 0; i < 8; i++) { const float lo = bf_lo(e[i]), hi = bf_hi(e[i]); s0 += lo; s1 += hi; q0 = fmaf(lo, lo, q0); q1 = fmaf(hi, hi, q1); }
  }
  s0 += s1; q0 += q1;
  arrive1(BAR(B_STD));
  s0 += __shfl_xor_sync(~0u, s0, 8); q0 += __shfl_xor_sync(~0u, q0, 8);
  s0 += __shfl_xor_sync(~0u, s0, 16); q0 += __shfl_xor_sync(~0u, q0, 16);
  if (lane < 8) asm volatile("st.async.shared::cluster.mbarrier::complete_tx::bytes.v2.b32 [%0], {%1,%2}, [%3];" ::"r"(ra), "r"(__float_as_uint(s0)), "r"(__float_as_uint(q0)), "r"(rb) : "memory");
}
__device__ __forceinline__ void short_conv(Scratch* G, uint32_t base, int s, int w, uint32_t par, uint32_t xh) {
  REGION_IDS;
  const uint32_t a = base + tab(T_KV, s) + 128 * (lane & 3) + ((w ^ (lane & 3)) << 4) + 4 * (lane & 16) + (lane & 12), keep = ~(lane & 1);
  uint4* dst = G->xr + (128 * s + 64 * (bid & 1) + 8 * w + 2 * (lane & 16) + (lane >> 1 & 6)) * 256 + 255 - 4 * (bid >> 1) - (lane & 3);
  mbar_wait(BAR(B_KV));
  mbar_wait(BAR(B_KV + s));
  const uint4 wv = lds128(base + OFF_TAP + 512 * s + 64 * w + 16 * (lane & 16) + 4 * (lane & 12));
  uint32_t kk[11], r[8];
#pragma unroll
  for (int k = 0; k < 11; k++) kk[k] = k < 3 ? lds32((a ^ (64 * (k & 1))) + KV_H + 512 * k) : lds32((a ^ (64 * (~k & 1))) + 512 * (k - 3));
  if (xh == 0 && elect()) red_hint(G->hint[s][4 * (bid & 1) + w]);
#pragma unroll
  for (int k = 0; k < 8; k++) r[k] = lds32((a ^ (64 * (k & 1))) + KV_V + 512 * k);
  arrive1(BAR(B_SC + s));
  const uint32_t w0 = __byte_perm(wv.x, wv.z, 0x5410), w1 = __byte_perm(wv.x, wv.z, 0x7632),
                 w2 = __byte_perm(wv.y, wv.w, 0x5410), w3 = __byte_perm(wv.y, wv.w, 0x7632);
#pragma unroll
  for (int k = 0; k < 8; k++) r[k] = bmul2(bfma2(kk[k + 3], w0, bfma2(kk[k + 2], w1, bfma2(kk[k + 1], w2, bmul2(kk[k], w3)))), r[k]);
  const uint32_t bit = ~par >> 7 & lane & 1;
  if (xh == 1 && elect()) red_hint(G->hint[s][4 * (bid & 1) + w]);
  st_relaxed128(dst, (__byte_perm(r[7], r[6], 0x5410) & keep) | bit, __byte_perm(r[5], r[4], 0x5410), __byte_perm(r[3], r[2], 0x5410), __byte_perm(r[1], r[0], 0x5410));
  st_relaxed128(dst + 256, (__byte_perm(r[7], r[6], 0x7632) & keep) | bit, __byte_perm(r[5], r[4], 0x7632), __byte_perm(r[3], r[2], 0x7632), __byte_perm(r[1], r[0], 0x7632));
  if (xh == 2 && elect()) red_hint(G->hint[s][4 * (bid & 1) + w]);
}
__device__ __forceinline__ void silu_vector(const bf16* c, int n, uint32_t base) {
  REGION_IDS;
  if (tid < n) {
    const uint32_t x = ldg32(c + 2 * tid);
    sts32(base + OFF_CV + 4 * tid, pack_bf16(silu_f(bf_lo(x)), silu_f(bf_hi(x))));
  }
  fence_async_smem();
}

template <int FIRST> __global__ void __cluster_dims__(2, 1, 1) __launch_bounds__(512, 1) k_fused(const __grid_constant__ Ptrs P, const __grid_constant__ Maps maps) {
  Scratch* const G = P.g;
  extern __shared__ __align__(1024) uint8_t smem_raw[];
  const uint32_t t_start = clock();
  const uint32_t base = __shfl_sync(~0u, smem_u32(smem_raw), 0);
  if (threadIdx.x == 416 && blockIdx.x + FIRST < 128) {
    const int c0 = 64 * (blockIdx.x & 1), c1 = 2 * (blockIdx.x & 126);
    mbar_init<1>(BAR(B_KV), 1);
    mbar_expect_tx(BAR(B_KV), 12288);
    tma3d(base + tab(T_KV, 0), &maps.km, c0, c1, 0, BAR(B_KV));
    tma3d(base + tab(T_KV, 0) + KV_V, &maps.v, c0, c1, 0, BAR(B_KV));
    tma3d(base + tab(T_KV, 0) + KV_H, &maps.kh, c0, c1 - 1, 5, BAR(B_KV));
    tma3d(base + OFF_TAP, &maps.tap, 0, blockIdx.x & 1, 0, BAR(B_KV));
  }
  if ((base & 0xFFFFFFu) != DB) __trap();
  const int wid = __shfl_sync(~0u, threadIdx.x >> 5, 0), wg = wid >> 2, w = wid & 3;
  if (blockIdx.x + FIRST >= 128) {
    REGION_IDS;
    auto unit = [&](int n) { return 4 * (P.hl[n >> 2] >> 8 * (n & 3) & 255) + (bid & 3); };
    auto fetch = [&](int n, int b) {
      if (unit(n) < 120 && elect()) {
        mbar_expect_tx(BAR(n), 40960);
#pragma unroll 1
        for (int k = 0; k < 5; k++) tma3d(base + 40960 * b + 8192 * k, &maps.wm, mod_col(unit(n) >> 1), 320 * (bid & 1) + 64 * k, 0, BAR(n));
      }
    };
    if (wid == 0) {
      mbar_init<4>(BAR(0), 1);
#pragma unroll 1
      for (int n = 0; n < 4; n++) { if (K(hstart)) wait_clock(t_start + (K(hstart) & 0xFFFF) + n * (K(hstart) >> 16)); fetch(n, n); }
      mbar_init<28>(BAR(4), 1);
    }
    const uint32_t par = ~ld_relaxed32(G->hint[7][0]) >> 7 & 1;
    silu_vector(P.c + 320 * (bid & 1), 160, base);
    __syncthreads();
#pragma unroll 1
    for (int n = wg; unit(n) < 120; n += 4) {
      mbar_wait(BAR(n));
      mod_gemv<20>(G, 40960 * (n % 5), unit(n) >> 1, bid & 1, w, lane, par);
      named_bar(1 + wg, 128);
      if (w == 0) {
        if (K(hpause)) wait_clock(t_start + K(hpause));
        if (n == 0) fetch(4, 4);
        fetch(n + 5, n % 5);
      }
    }
    return;
  }
  mbar_init<3>(BAR(wid < 15 ? 4 * wid + 1 : B_SC + 1), wid < 8 ? 1 : 4);
  mbar_init<1>(BAR(!wid ? B_SC + 4 : wid < 15 ? 4 * wid : B_SC), wid && wid < 8 ? 1 : 4);
  if (wid == 0) mbar_init<2>(BAR(B_SC + 5), 4);
  asm volatile("fence.mbarrier_init.release.cluster; bar.sync 0, 512;" ::: "memory");
  asm volatile("barrier.cluster.arrive.relaxed.aligned;" ::: "memory");
#define LAUNCHES const uint32_t launches = ld_relaxed32(G->hint[7][blockIdx.x >> 4])
#define EPOCH ((__shfl_sync(~0u, launches, 0) >> 7) + 1)
  if (wg < 2) {
    asm volatile("setmaxnreg.inc.sync.aligned.u32 224;");
    LAUNCHES;
    uint32_t par = launches;
    {
      float acc[128];
      uint32_t A[64];
#pragma unroll
      for (int i = 0; i < 64; i++) asm volatile("" : "=r"(A[i]));
      int c = wg;
#pragma unroll 1
      for (uint64_t prog = prog_of(wg); prog; prog >>= 8) {
        REGION_IDS;
        const int s = prog & 7;
        if (s < 5) short_conv(G, base, s, w, par, K(xh));
        if (prog == prog_of(wg)) cluster_wait();
        if (prog & 16) {
          mbar_wait(BAR(B_QTD));
          mbar_wait(BAR(B_WM));
          mod_gemv<5>(G, OFF_WM, TA + (bid >> 3), bid & 7, w, lane, ~par >> 7 & 1);
          arrive1(BAR(B_G));
        }
        if (prog & 8) q_stats(base, w);
        if (prog & 32) {
          const int L = 16 * w + (lane >> 2) + 2 * (lane & 3) - 7;
          const uint32_t fo = base + ((L & 1) ? F_O + 2 * (L + 1) : F_E + 2 * L);
          mbar_wait(BAR(B_FRDY + c));
          cload<0, 0>(A, fo + tab(T_F, c));
          cload<15, 1>(A, fo + tab(T_F, c));
          arrive1(BAR(B_FL + c));
        }
        if (!(prog & 64)) continue;
        uint32_t xo;
#pragma unroll 1
        for (int it = 0; it < SPIN_LIMIT; it++) {
          xo = tab(T_X, opaque(c));
          mbar_wait(BAR(B_XR + c), it & 1);
          const uint32_t tag = lds32(base + xo + 32 * i0);
          wg_fence();
          csteps<0, 0>(acc, A, mkdesc(DB + xo, 16, 128, 0));
          csteps<15, 6>(acc, A, mkdesc(DB + xo, 16, 128, 0));
          wg_commit();
          if (bar_all(1 + wg, (tag ^ par >> 7) & 1)) break;
          wg_wait<0>();
          if (w == 0 && elect()) { mbar_expect_tx(BAR(B_XR + c), 4096); bulk_load(base + xo, G->xr + (128 * c + bid) * 256, 4096, BAR(B_XR + c)); }
        }
        wg_fence();
        csteps<5, 1>(acc, A, mkdesc(DB + tab(T_X, opaque(c)), 16, 128, 0));
        wg_commit();
        mbar_wait(BAR(opaque(B_SC + (c == 2 ? 3 : c))));
        wg_wait<0>();
        fence_regs(acc);
        const uint32_t pb = base + tab(T_P, c) + 4096 * w;
#pragma unroll
        for (int k = 0; k < 8; k++) {
          uint32_t p[4];
#pragma unroll
          for (int e = 0; e < 4; e++) { const int i = 4 * k + e; p[e] = i < 31 ? pack_bf16(acc[4 * i] + acc[4 * i + 6], acc[4 * i + 1] + acc[4 * i + 7]) : pack_bf16(acc[124], acc[125]); }
          if (k == 0 && (lane & 3) < w) p[0] = 0;
          stmatrix_x4_t(k == 0 ? pb + 16 * ((255 - lane + 2 * w) & 255) : pb + 16 * (255 - lane + 2 * w) - 512 * k, p[0], p[1], p[2], p[3]);
        }
        arrive1(BAR(B_PFULL + c));
        c += 2;
      }
    }
    par = ~par >> 7 & 1;
    const uint32_t ao = ((blockIdx.x ^ wg) & 1) * UNIT;
    uint32_t ck;
    { REGION_IDS; ck = base + ao + lane * 128 + (((2 * w) ^ (lane & 7)) << 4); }
    const uint32_t abd = DB + ao;
    auto tags = [&](int as, bool first) { return (lds32(ck + as) ^ par) | (lds32(ck + as + (first ? 4096 : 256)) ^ par); };
    int role;
    { int h, j, r; ffn_role(h, j, r); role = (2 * r + (h ^ wg)) * 8 + 4 * h + j; }
    auto a_tile = [&](int as, int n, bool first) {
#pragma unroll 1
      for (int it = 0; __any_sync(~0u, tags(as, first) & 1) && it < SPIN_LIMIT; it++) {
        if (elect()) {
          mbar_expect_tx(BAR(B_RETRY + wid), UNIT);
          if (first) tma2d(base + ao + as, &maps.xs, 8 * role & ~63, 64 * n, BAR(B_RETRY + wid));
          else bulk_load(base + as, G->hh + ((role & ~3) + ((role + n) & 3)) * 1536 + (n >> 2) * 512, UNIT, BAR(B_RETRY + wid));
        }
        mbar_wait(BAR(B_RETRY + wid), par >> 1);
        par ^= 2;
      }
    };
    float acc[128], acb[64];
    int ws = 0;
    float d[8];
    uint32_t *ud0, *ud1;
    unsigned* uh;
    {
      REGION_IDS;
      const int r = role >> 4, row = (r & 14) + (lane >> 2 & 1);
      ud0 = &G->uv[role & 7][32 * row + 4 * ((2 * w ^ row) & 7) + (lane & 3)];
      ud1 = ud0 + 512 * w_block(r & 1, 2);
      ud0 += 512 * w_block(r & 1, wg);
      uh = G->hint[8][role & 7];
      asm volatile("" : "+l"(ud0), "+l"(ud1), "+l"(uh));
    }
    auto step = [&](int n, int uv) {
      const int as = a_at(n);
      const uint64_t da = mkdesc(abd + as, 16, 1024, 1), db = mkdesc(DB + OFF_R + ws, 4096, 1024, 1);
      mbar_wait(BAR(B_FULL + 2 * n));
      a_tile(as, n, true);
      if (uv == 1) { mbar_wait(BAR(B_UVB)); mbar_wait(BAR(B_CO)); }
      wg_fence();
#pragma unroll
      for (int k = 0; k < 4; k++) {
        wg_ss64_11(acc + 96, da + 128 * k, db + 768 + 128 * (k & 1) + 1024 * (k >> 1), k ? 1 : n);
        if (k == GA - 1) { wg_commit(); wg_wait<1>(); if (elect()) mbar_arrive(BAR(B_EMPTY + 2 * n - 1)); if (uv == 2) fence_regs(d); }
      }
      if (uv == 1) {
#pragma unroll
        for (int k = 0; k < 5; k++) {
          wg_ss8_10(d, mkdesc(DB + OFF_UV + 2048 * wg + 6144 * k, 16, 1024, 1), mkdesc(DB + OFF_CO + 64 * k, 32, 128, 0), k);
        }
        if (!wg) {
#pragma unroll
          for (int k = 0; k < 5; k++) wg_ss8_10(d + 4, mkdesc(DB + OFF_UV + 4096 + 6144 * k, 16, 1024, 1), mkdesc(DB + OFF_CO + 64 * k, 32, 128, 0), k);
        }
      }
#pragma unroll
      for (int k = 0; k < 4; k++) wg_ss192_11(acc, da + 128 * k, db + 128 * (k & 1) + 1024 * (k >> 1), k ? 1 : n);
      wg_commit();
      ws = ws == 4 * WSLOT ? 0 : ws + 2 * WSLOT;
      if (uv == 2) {
        split(P.ulo, 30);
        REGION_IDS;
        const uint32_t tag = !(lane & 3);
        if (elect()) red_hint(uh);
        uint32_t x[4];
#pragma unroll
        for (int k = 0; k < 4; k++) asm volatile("movmatrix.sync.aligned.m8n8.trans.b16 %0, %1;" : "=r"(x[k]) : "r"(pack_bf16(d[2 * k], d[2 * k + 1])));
        const uint32_t y1 = __shfl_up_sync(~0u, x[1], 8), y3 = __shfl_up_sync(~0u, x[3], 8);
        if (lane < 16) {
          st_relaxed32((uint32_t*)((uint64_t)ud0 ^ 2 * (lane & 8)), set_tag(lane < 8 ? x[0] : y1, tag, par));
          if (!wg) st_relaxed32((uint32_t*)((uint64_t)ud1 ^ 2 * (lane & 8)), set_tag(lane < 8 ? x[2] : y3, tag, par));
        }
      }
    };
#pragma unroll 1
    for (int n = 0; n < UVS; n++) step(n, 0);
    step(UVS, 1);
    step(UVS + 1, 2);
#pragma unroll 1
    for (int n = UVS + 2; n < 10; n++) step(n, 0);
    float o[80];
    uint32_t fr[3][16], bo;
    {
      REGION_IDS;
      float r0, r1, s0, s1;
      const int id = role, j = role;
      uint4* const hdst = G->hh + id * 1536 + 128 * w + (lane ^ lane >> 3);
      const uint32_t keep = ~(~lane & 1), bit = par & ~keep;
      bo = 1024 + ((j & 1) << 23);
      auto own = [&](int i) { wg_rs160_1(o, fr[i >> 2] + 4 * (i & 3), mkdesc(DB + w2_at(i / 4) + (i & 3) * 2048, UNIT, bo, 1), i); };
      auto hint = [&](int v) { asm volatile("{.reg .pred p; setp.eq.u32 p, %1, 0; @p red.relaxed.gpu.global.add.u32 [%0], 1;}" ::"l"(&G->hhf[id * 8 + v]), "r"(lane) : "memory"); };
      auto put = [&](int v, int k) {
        uint32_t* x = fr[v] + 2 * k;
        const uint32_t t0 = (x[k / 2] & keep) | bit, t1 = (x[5 + k / 2] & keep) | bit;
        x[k / 2] = t0; x[5 + k / 2] = t1;
        st_relaxed128(hdst + 512 * v + 8 * k, x[0], x[2], x[4], x[6]);
        st_relaxed128(hdst + 512 * v + 8 * k + 64, x[1], x[3], x[5], x[7]);
      };
      auto move = [&](uint32_t* x, int n) {
#pragma unroll
        for (int k = 0; k < n; k++) asm volatile("mul.rn.f32 %0, %0, %1;" : "+r"(x[k]) : "f"(P.one));
      };
      auto act = [&](int i) {
        const int v = i >> 3, k = 7 - (i & 7);
        const float *g = v < 2 ? acc + 32 * v + 4 * k : acb + 4 * k, *up = g + (v < 2 ? 64 : 32);
        fr[v][2 * k] = pack_bf16(silu2(g[0], r0, s0) * up[0], silu2(g[1], r0, s0) * up[1]);
        fr[v][2 * k + 1] = pack_bf16(silu2(g[2], r1, s1) * up[2], silu2(g[3], r1, s1) * up[3]);
        if (!(k & 3)) { put(v, k); if (!k && !(HL >> v & 1)) hint(v); if (i == 15) { move(fr[0], 16); } }
        else asm volatile("" : "+r"(fr[v][2 * k]), "+r"(fr[v][2 * k + 1]));
      };
#pragma unroll
      for (int v = 0; v < 10; v++) {
        mbar_wait(BAR(B_FULL + 20 + v));
        if (v == XP) {
          mbar_wait(BAR(B_EXT));
          wg_fence();
          wg_ss192_01(acc, mkdesc(DB + OFF_AX + 1024 * opaque(wg), 0, 128, 0), mkdesc(DB + OFF_BX, 2048, 1024, 1), 1);
          wg_ss64_01(acc + 96, mkdesc(DB + OFF_AX + 1024 * opaque(wg), 0, 128, 0), mkdesc(DB + OFF_BX + 6144, 2048, 1024, 1), 1);
          wg_commit();
          r0 = 0.5f * __uint_as_float(lds32(base + OFF_RT + 256 * wg + 64 * w + (lane & 28)));
          r1 = 0.5f * __uint_as_float(lds32(base + OFF_RT + 256 * wg + 64 * w + 32 + (lane & 28)));
          s0 = 2.f * r0 * r0;
          s1 = 2.f * r1 * r1;
        }
        wg_fence();
#pragma unroll
        for (int k = 0; k < 4; k++) {
          wg_ss128_11(acb, mkdesc(opaque(abd) + a_at(second(v)) + k * 2048, 16, 1024, 1), mkdesc(DB + OFF_R + WSLOT * ((v + 2) % 6) + k * 2048, UNIT, 1024, 1), v + k);
          if (k == GB - 1) { wg_commit(); wg_wait<1>(); if (v == XP) fence_regs(acc); if (elect()) mbar_arrive(BAR(B_EMPTY + 19 + v)); }
        }
        if (v == 9) wg_ss128_01(acb, mkdesc(DB + OFF_AX + 1024 * opaque(wg), 0, 128, 0), mkdesc(DB + OFF_BX + UNIT, 2048, 1024, 1), 1);
        wg_commit();
        split(P.ulo, v);
        if (v == XP + NP / 2 && (HL & 1)) hint(0);
        if (v == XP + NP && (HL & 2)) hint(1);
#pragma unroll
        for (int i = 0; i < 16; i++) if (v >= XP && i * NP / 16 == v - XP) act(i);
      }
#pragma unroll
      for (int v = 0; v < 3; v++) {
        mbar_wait(BAR(B_FULL + 30 + v));
        wg_fence();
#pragma unroll
        for (int i = 0; i < 4; i++) {
          own(4 * v + i);
          if (i == GB - 1) { wg_commit(); wg_wait<1>(); if (v == 0) fence_regs(acb); if (elect()) mbar_arrive(BAR(B_EMPTY + 29 + v)); }
        }
        wg_commit();
        split(P.ulo, 10 + v);
        if (v == 0 && XP + NP == 10 && (HL & 2)) hint(1);
        if (v == 2 && (HL & 4)) hint(2);
#pragma unroll
        for (int i = 0; i < 4; i++) if (v < 2) act(16 + 4 * v + i);
      }
      ck = base + 2048 * w + 516 * (lane >> 3) + 144 * (lane >> 2 & 1) + 32 * (lane & 3);
    }
    uint32_t x1[40], gb[20];
    if (!wg) {
      REGION_IDS;
      mbar_wait(BAR(B_GB));
#pragma unroll
      for (int k = 0; k < 5; k++) {
        const uint4 g = lds128(base + OFF_GB + 80 * (lane & 3) + 16 * k);
        gb[4 * k] = g.x; gb[4 * k + 1] = g.y; gb[4 * k + 2] = g.z; gb[4 * k + 3] = g.w;
      }
    }
#pragma unroll 1
    for (int u = 33; u < (wg ? 42 : SPL); u++) {
      const int x = P.hid[wg][u - 33], as = x & ~15;
      const uint64_t wd = mkdesc(0, 0, bo, 1) | P.w2t[u - 30].x;
      mbar_wait(BAR(wg || u < 38 ? B_FULL + u : B_LAST + u - 38));
      a_tile(as, x & 15, false);
      if (wg || u < 38) {
        wg_fence();
#pragma unroll
        for (int kk = 0; kk < 4; kk++) {
          wg_ss160_01(o, mkdesc(DB + as + kk / 2 * 512 + (kk & 1) * 32, 16, 1024, 2), wd + kk * 128, 1);
          if (kk == GB - 1) { wg_commit(); wg_wait<1>(); if (elect()) mbar_arrive(BAR(B_EMPTY + u - 1)); }
        }
        wg_commit();
        if (u == 41 && elect()) mbar_arrive(BAR(B_LAG));
      }
      if (u == 38 - 1 && !wg) {
        REGION_IDS;
        const uint32_t xa = base + (lane >> 4) * 1024 + (lane & 7) * 128 + (((2 * w + ((lane >> 3) & 1)) ^ (lane & 7)) << 4);
        mbar_wait(BAR(B_FULL + 42));
        wg_wait<0>();
        if (elect()) mbar_arrive(BAR(B_EMPTY + 38 - 1));
#pragma unroll
        for (int k = 0; k < 10; k++) ldmatrix_x4_t(x1 + 4 * k, xa + x1_at(k / 2) + (k & 1) * 2048);
      }
    }
    REGION_IDS;
    const int h = role >> 2 & 1, j = role & 3;
    const uint32_t xb = base + OFF_XCH + 5120 * w;
    if (wg) {
      const uint32_t rdst = mapa(xb + 16 * lane, h ^ 1), rbar = mapa(BAR(B_FULL + 1), h ^ 1);
      mbar_wait(BAR(B_XFREE));
      wg_wait<0>();
      fence_regs(o);
#pragma unroll
      for (int k = 0; k < 10; k++)
        asm volatile("st.async.shared::cluster.mbarrier::complete_tx::bytes.v4.b32 [%0], {%1,%2,%3,%4}, [%5];" ::"r"(rdst + 512 * k), "r"(pack_bf16(o[8 * k], o[8 * k + 1])),
                     "r"(pack_bf16(o[8 * k + 2], o[8 * k + 3])), "r"(pack_bf16(o[8 * k + 4], o[8 * k + 5])), "r"(pack_bf16(o[8 * k + 6], o[8 * k + 7])), "r"(rbar + 16 * (k / 4)) : "memory");
    } else {
      mbar_wait(BAR(B_LAG));
      wg_fence();
#pragma unroll
      for (int i = 152; i < 4 * SPL; i++) wg_ss160_01(o, mkdesc(DB + hid_at(i / 4 - 33, 0) + (i & 2) * 256 + (i & 1) * 32, 16, 1024, 2), mkdesc(DB + w2_at(i / 4 - 30) + (i & 3) * 2048, UNIT, bo, 1), 1);
      wg_commit();
#pragma unroll 1
      for (int u = SPL; u < 42; u++) {
        const int x = P.hid[0][u - 33];
        mbar_wait(BAR(B_LAST + u - 38));
        a_tile(x & ~15, x & 15, false);
      }
      wg_fence();
#pragma unroll
      for (int i = 4 * SPL; i < 168; i++) wg_ss160_01(o, mkdesc(DB + hid_at(i / 4 - 33, 0) + (i & 2) * 256 + (i & 1) * 32, 16, 1024, 2), mkdesc(DB + w2_at(i / 4 - 30) + (i & 3) * 2048, UNIT, bo, 1), 1);
      wg_commit();
      const int row = (8 * role & ~63) + 16 * w;
      auto merge = [&](int e0, int e1) {
#pragma unroll
        for (int e = e0; e < e1; e++) {
          if (e % 4 == 0) mbar_wait_cluster(BAR(B_FULL + 1 + e / 2));
          const uint4 p = lds128(xb + 16 * lane + 512 * e);
          x1[4 * e] = bfma2(gb[2 * e], p.x, x1[4 * e]); x1[4 * e + 1] = bfma2(gb[2 * e], p.y, x1[4 * e + 1]);
          x1[4 * e + 2] = bfma2(gb[2 * e + 1], p.z, x1[4 * e + 2]); x1[4 * e + 3] = bfma2(gb[2 * e + 1], p.w, x1[4 * e + 3]);
        }
        __syncwarp();
      };
      merge(0, MG);
      wg_wait<0>();
      fence_regs(o);
#pragma unroll
      for (int k = 0; k < 10; k++) {
        if (k >= MG && k % 4 == 0) merge(k, k < 8 ? k + 4 : 10);
        uint32_t y[4];
#pragma unroll
        for (int e = 0; e < 4; e++) y[e] = bfma2(gb[2 * k + e / 2], pack_bf16(o[8 * k + 2 * e], o[8 * k + 2 * e + 1]), x1[4 * k + e]);
        stmatrix_x4(k < 8 ? xb + 2048 * (k >> 2) + (lane & 15) * 128 + (((2 * (k & 3) + (lane >> 4)) ^ (lane & 7) ^ 4 * (j & 1)) << 4)
                          : xb + 4096 + (lane & 15) * 64 + (((2 * (k & 1) + (lane >> 4)) ^ (lane >> 1 & 3)) << 4), y[0], y[1], y[2], y[3]);
        if ((SG >> k & 1) || k == 9) {
          fence_async_smem();
          __syncwarp();
#pragma unroll
          for (int b = 0; b < 3; b++) {
            const int e = b < 2 ? 4 * b + 3 : 9;
            if (e <= k && !(SG & ((1 << k) - 1) & ~((1 << e) - 1)) && lane == 0) tma2d_store(b < 2 ? &maps.outa : &maps.outb, b < 2 ? 128 * j + 64 * b : 512 + 32 * j, row, xb + 2048 * b);
          }
        }
      }
      if (lane == 0) { bulk_commit(); bulk_wait_read(); }
    }
  } else if (wg == 2) {
    asm volatile("setmaxnreg.dec.sync.aligned.u32 40;");
    mbar_init<15>(BAR(B_FULL + 15 * w), 1);
    mbar_init<11>(BAR(B_EMPTY - 1 + 11 * w), 8);
    mbar_init<1>(BAR(B_LAST + w), 1);
    asm volatile("fence.mbarrier_init.release.cluster;" ::: "memory");
    LAUNCHES;
    silu_vector(P.c + 80 * (blockIdx.x & 7) - 512, 296, base - 1024);
    const uint32_t epoch = EPOCH;
    if (w == 2) rank_pair(G, base, epoch, true);
    cluster_wait();
    {
      REGION_IDS;
      const uint32_t tag = opaque(~lane & 1);
      auto q_t = [&]() {
        const int tr = 4 * (lane & 1) + (lane >> 1 & 3);
        uint32_t a = base + OFF_Q + 128 * ((lane & 24) + tr) + ((w ^ tr) << 4);
        uint4* dst = G->qt + (64 * (bid & 1) + 8 * w + (lane >> 2)) * 256 + 4 * (bid >> 1) + (lane & 3);
#pragma unroll 1
        for (int c = 0; c < 5; c++) {
          mbar_wait(BAR(B_Q + c));
#pragma unroll
          for (int k = 0; k < 2; k++) {
            uint32_t x[4];
            ldmatrix_x4_t(x, a ^ (64 * k));
            st_relaxed128(dst + 8192 * k, set_tag(x[0], tag, epoch), x[1], x[2], x[3]);
          }
          a += 4096;
          dst += 32768;
        }
        arrive1(BAR(B_QTD));
      };
      q_t();
      if (w == 3) {
        mbar_wait_cluster(BAR(B_ST1));
        if (lane < 8) red_hint(G->hint[5][lane]);
        const uint2 x = lds64(base + OFF_ST + 8 * (lane & 15)), y = lds64(base + OFF_ST + 128 + 8 * (lane & 15));
        float m, sd;
        ln_final(__uint_as_float(x.x) + __uint_as_float(y.x), __uint_as_float(x.y) + __uint_as_float(y.y), m, sd);
        sd = rbf(rcpf(sd));
        const uint32_t mr = pack_bf16(sd, -rbf(m) * sd), tg = lane & 7 ? 0 : lane & 8 ? 1 : 0x8000;
        const uint32_t o = __byte_perm(__shfl_sync(~0u, mr, 2 * lane & 14), __shfl_sync(~0u, mr, (2 * lane & 14) + 1), (lane & 8) ? 0x7632 : 0x5410);
        if (lane < 16) st_relaxed32(&G->st1[lane >> 3][8 * bid + (lane & 7)], (o & ~tg) | ((epoch & 1) * tg));
      }
      if (w == 2) rank_pair(G, base, epoch, false);
      if (w == 1) mod_fetch(G, base, epoch, M8, 0, 1);
    }
    {
      REGION_IDS;
      const uint32_t tag = opaque(~lane & 1), sa = opaque(base + 16 * i0);
      uint4 q[2];
      mbar_wait(BAR(B_PFULL));
#pragma unroll 1
      for (uint32_t a = sa + tab(T_P, 0); a < sa + tab(T_P, 0) + 4096; a += 2048) {
        uint4 y = lds128(a), z = lds128(a + 4096), u = lds128(a + 8192);
        const uint4 v = lds128(a + 12288);
        add4(y, z); add4(u, v); add4(y, u);
        sts128(a, y.x, y.y, y.z, y.w);
      }
      uint4* gp = G->xs + 256 * bid + (sa - base >> 4);
      q[0] = ld_relaxed128(gp - D_ * 256);
      q[1] = ld_relaxed128(gp - D_ * 256 + 128);
      mbar_wait(BAR(B_MR));
      e_round<true>(G, base, sa, gp, q, 0, w, tag, epoch);
#pragma unroll 1
      for (int c = 1; c < 5; c++) e_round<false>(G, base, sa, gp, q, c, w, tag, epoch);
    }
    int h, j, r;
    ffn_role(h, j, r);
    arrive1(BAR(B_ED));
    {
      REGION_IDS;
      float s0 = 0.f, q0 = 0.f, s1 = 0.f, q1 = 0.f;
#pragma unroll 1
      for (int c = 2; c < 5; c++) {
        const uint32_t buf = base + OFF_SX + 4096 * (c - 2), b = BAR(B_SX + c);
        uint32_t x[8];
#pragma unroll 1
        for (int it = 0; it < SPIN_LIMIT; it++) {
          mbar_wait(b, it & 1);
#pragma unroll
          for (int i = 0; i < 8; i++) x[i] = lds32(buf + 1024 * w + 4 * lane + 128 * i);
          if (bar_all(3, (lane & 7) || min(min(min(x[0], x[1]), min(x[2], x[3])), min(min(x[4], x[5]), min(x[6], x[7]))))) break;
          if (w == 0 && elect()) { mbar_expect_tx(b, 4096); tma2d(buf, &maps.x1s, 128 * r + 64 * h, D_ * (epoch & 1) + 128 * c + 32 * j, b); }
        }
#pragma unroll
        for (int i = 0; i < 8; i++) { const float lo = bf_lo(x[i]), hi = bf_hi(x[i]); s0 += lo; q0 = fmaf(lo, lo, q0); s1 += hi; q1 = fmaf(hi, hi, q1); }
      }
      sts128(base + OFF_MR + 1024 * w + 16 * lane, __float_as_uint(s0), __float_as_uint(q0), __float_as_uint(s1), __float_as_uint(q1));
      arrive1(BAR(B_S2));
    }
    {
      REGION_IDS;
      const uint32_t* sp = &G->st2[2 * r + (h ^ (w >> 1))][0][2 * (i0 & 63)];
      uint2 x[4];
      int it;
#pragma unroll 1
      for (it = 0; it < SPIN_LIMIT; it++) {
        mbar_wait(BAR(B_BX), it & 1);
        uint32_t y = 0;
#pragma unroll
        for (int k = 0; k < 3; k++) y |= lds32(base + OFF_BX + 32 * i0 + 4096 * k) ^ epoch;
        if (bar_all(3, !(y & 1))) break;
        if (w == 0 && elect()) { mbar_expect_tx(BAR(B_BX), 12288); bulk_load(base + OFF_BX, G->uv[4 * h + j], 12288, BAR(B_BX)); }
      }
      it = 0;
#pragma unroll 1
      do {
#pragma unroll
        for (int k = 0; k < 4; k++) x[k] = ld_relaxed64(sp + 128 * k);
      } while (__any_sync(~0u, ((x[0].x ^ epoch) | (x[1].x ^ epoch) | (x[2].x ^ epoch) | (x[3].x ^ epoch)) & 1) && ++it < SPIN_LIMIT);
      float m, sd;
      ln_final((__uint_as_float(x[0].x) + __uint_as_float(x[1].x)) + (__uint_as_float(x[2].x) + __uint_as_float(x[3].x)),
               (__uint_as_float(x[0].y) + __uint_as_float(x[1].y)) + (__uint_as_float(x[2].y) + __uint_as_float(x[3].y)), m, sd);
      const uint32_t e = pack_bf16(-m, sd);
      sts128(base + OFF_AX + 16 * i0, e, e, e, e);
      sts32(base + OFF_RT + 4 * i0, __float_as_uint(rcpf(sd)));
      fence_async_smem();
      arrive1(BAR(B_EXT));
      {
        uint2 g0, g1;
        int it = 0;
#pragma unroll 1
        do {
          g0 = ld_relaxed64(&G->modv[1][128 * j + i0]);
          g1 = ld_relaxed64(&G->modv[1][512 + 32 * j + lane]);
        } while (__any_sync(~0u, ((g0.x ^ epoch) | (g0.y ^ epoch) | (g1.x ^ epoch) | (g1.y ^ epoch)) & 1) && ++it < SPIN_LIMIT);
        const uint32_t a = base + OFF_GB + 40 * (lane & 6) + 2 * (lane & 1) + (lane >> 3) * 4;
        asm volatile("st.shared.u16 [%0], %1; st.shared.u16 [%2], %3;" ::"r"(a + 16 * (w ^ (j & 1))), "h"((uint16_t)(mod_sum(g0) >> 16)), "r"(a + 64), "h"((uint16_t)(mod_sum(g1) >> 16)) : "memory");
        arrive1(BAR(B_GB));
      }
#pragma unroll 1
      for (int m = w < 3 ? w : 5; m < 9; m += w < 3 ? 3 : 1) {
        const int x = P.hid[0][m], id = 16 * r + 4 * h + ((j + x) & 3), q = x >> 2 & 3;
        const uint4* src = G->hh + id * 1536 + 512 * q;
        it = 0;
#pragma unroll 1
        while (w < 3 && __any_sync(~0u, ld_relaxed32(&G->hhf[8 * id + 64 * (lane & 1) + q]) != 4 * epoch) && ++it < SPIN_LIMIT);
        mbar_wait(BAR(w < 3 ? P.hid[2][m] : P.hid[3][m]));
        if (elect()) {
          if (w < 3) bulk_load(base + (P.hid[1][m] & ~15), src + 8 * 1536 * (h ^ 1), UNIT, BAR(B_FULL + 33 + m));
          else mbar_expect_tx(BAR(B_LAST + m - 5), UNIT);
          if (w == 3 || m < 5) bulk_load(base + (x & ~15), src + 8 * 1536 * h, UNIT, BAR(w < 3 ? B_FULL + 33 + m : B_LAST + m - 5));
        }
      }
    }
  } else {
    asm volatile("setmaxnreg.dec.sync.aligned.u32 24;");
    if (w >= 2) {
      LAUNCHES;
      uint32_t epoch;
      {
        REGION_IDS;
        uint32_t dv;
        asm volatile("ld.global.nc.u16 %0, [%1];" : "=r"(dv) : "l"(P.ssmd + 128 * (lane & 7) % D_ + bid));
        if (lane < 5) sts128(base + tab(T_F, lane) + (w & 1) * (F_O - F_E) + F_E - 16, 0, 0, 0, 0);
        epoch = EPOCH;
        __syncwarp();
#pragma unroll 1
        for (int c = 0; c < 5; c++) {
          const float d = i0 == 64 ? bf_lo(dv) : 0.f;
          dv = __shfl_down_sync(~0u, dv, 1);
          const uint32_t a = base + tab(T_F, c) + 16 * (i0 - 64);
          mbar_wait(BAR(B_FRAW + c));
#pragma unroll
          for (int k = 0; k < 4; k++) {
            uint4 x = lds128(a + F_E + 1024 * k);
            const uint32_t pv = lds32(a + F_E - 4 + 1024 * k);
            if (k == 0) { x.x = pack_bf16(bf_lo(x.x) + d, bf_hi(x.x)); sts32(a + F_E, x.x); }
            sts128(a + F_O + 1024 * k, __byte_perm(pv, x.x, 0x5432), __byte_perm(x.x, x.y, 0x5432), __byte_perm(x.y, x.z, 0x5432), __byte_perm(x.z, x.w, 0x5432));
          }
          __syncwarp();
          if (elect()) mbar_arrive2(BAR(B_FRDY + c));
          if (c == 0 && w == 3) {
#pragma unroll 1
            for (int k = 0; k < 13; k++) prefetch_map(&maps.w1a + k);
          }
        }
      }
      REGION_IDS;
      int h, j, r;
      ffn_role(h, j, r);
      cluster_wait();
      if (w == 2) {
        const unsigned* fp = G->xsh[lane < 10 ? lane >> 1 : 0][(r & 6) + (lane & 1)];
        uint32_t rdy = 0;
        mbar_wait(BAR(B_SC + 4));
#pragma unroll 1
        for (int e = 0; e < 14; e++) {
          const uint32_t x = P.adep[e], n = x >> 21 & 15, s = base + (x >> 25 << 13), b = BAR(B_FULL + (x >> 16 & 31));
          mbar_wait(BAR(opaque(x & 255)));
          mbar_wait(BAR(opaque(x >> 8 & 255)));
          const uint32_t f = BAR(B_FULL + 7 + 2 * (e < 7 ? e : e - 7));
          if (elect()) mbar_arrive_remote(mapa(f, h ^ 1));
#pragma unroll 1
          for (int it = 0; !(rdy >> n & 1) && it < SPIN_LIMIT; it++) rdy = __ballot_sync(~0u, ld_relaxed32(fp) == 64 * epoch);
          mbar_wait(f, e >= 7);
          if (elect()) asm volatile("cp.async.bulk.tensor.2d.shared::cluster.global.mbarrier::complete_tx::bytes.multicast::cluster [%0], [%1, {%3,%4}], [%2], %5;"
                                    ::"r"(s + UNIT * h), "l"(&maps.xs), "r"(b), "r"(128 * r + 64 * h), "r"(64 * n), "h"((uint16_t)3) : "memory");
        }
#pragma unroll 1
        for (int v = 0; v < 12; v++) {
          const int q = v * 11 >> 5, e = v - 3 * q, k32 = 24 * h + (q ? 6 * ((j + 1 + e) & 3) + 2 * q - 2 : 6 * j + 2 * e);
          const uint2 x = P.w2t[v];
          mbar_wait(BAR(x.y));
          if (elect()) {
            mbar_expect_tx(BAR(B_FULL + 30 + v), W2TILE + (v >= 8 ? UNIT : q ? 2 * UNIT : 0));
#pragma unroll
            for (int k = 0; k < 3; k++) tma5d(base - DB + 16 * (x.x & 0xFFFF) + UNIT * k, &maps.w2a + (q > 0), k < 2 ? 128 * j + 64 * k : 512 + 32 * (j & 2), k32, BAR(B_FULL + 30 + v));
          }
        }
      } else {
        float s0 = 0.f, q0 = 0.f, s1 = 0.f, q1 = 0.f;
        uint32_t nl = 0, np = 0, ph = 0;
#pragma unroll 1
        for (uint32_t seq = 0x94; seq > 1; seq >>= 1) {
          const uint32_t c = seq & 1 ? np : nl, buf = base + OFF_SX + 4096 * (c < 4 ? c & 1 : 2), b = BAR(opaque(B_SX + c));
          int it = 0;
          if (seq & 1) {
            mbar_wait(b, ph >> c & 1);
            ph ^= 1 << c;
            const uint32_t a = buf + 32 * lane;
            if (__all_sync(~0u, min(min(lds32(a), lds32(a + 1024)), min(lds32(a + 2048), lds32(a + 3072)))) || ph > SPIN_LIMIT) {
#pragma unroll 1
              for (uint32_t o = buf + 4 * lane; o < buf + 4096; o += 1024) {
                uint32_t x[8];
#pragma unroll
                for (int i = 0; i < 8; i++) x[i] = lds32(o + 128 * i);
#pragma unroll
                for (int i = 0; i < 8; i++) { const float lo = bf_lo(x[i]), hi = bf_hi(x[i]); s0 += lo; q0 = fmaf(lo, lo, q0); s1 += hi; q1 = fmaf(hi, hi, q1); }
              }
              np++;
              continue;
            }
            ph += 4;
            seq = 2 * seq + 1;
          } else {
#pragma unroll 1
            while (__any_sync(~0u, ld_relaxed32(G->xsh[c][(r & 6) + (j >> 1)]) != 64 * epoch) && ++it < SPIN_LIMIT);
            if (++nl == 5) mbar_wait(BAR(B_PEMPTY + 4));
          }
          if (elect()) { mbar_expect_tx(b, 4096); tma2d(buf, &maps.x1s, 128 * r + 64 * h, D_ * (epoch & 1) + 128 * c + 32 * j, b); }
        }
        mbar_wait(BAR(B_S2));
#pragma unroll
        for (int k = 0; k < 4; k++) {
          const uint4 x = lds128(base + OFF_MR + 1024 * k + 16 * lane);
          s0 += __uint_as_float(x.x); q0 += __uint_as_float(x.y); s1 += __uint_as_float(x.z); q1 += __uint_as_float(x.w);
        }
        asm volatile("{.reg .b128 t, x; .reg .b64 a, b; mov.b64 a, {%1,%2}; mov.b64 b, {%3,%4}; mov.b128 x, {a,b}; atom.relaxed.gpu.global.exch.b128 t, [%0], x;}"
                     ::"l"(&G->st2[2 * r + h][j][4 * lane]), "r"((__float_as_uint(s0) & ~1u) | (epoch & 1)), "f"(q0), "r"((__float_as_uint(s1) & ~1u) | (epoch & 1)), "f"(q1) : "memory");
        mbar_wait(BAR(B_EMPTY + 2 * UVS + 1));
        sts128(base + OFF_CO + 16 * lane, 0, 0, 0, 0);
        fence_async_smem();
        __syncwarp();
        if (elect()) {
#pragma unroll 1
          for (int k = 0; k < 40; k++) asm volatile("cp.async.bulk.global.shared::cta.bulk_group [%0], [%1], 512;" ::"l"(G->x1[~epoch & 1] + 1280 * blockIdx.x + 32 * k), "r"(base + OFF_CO) : "memory");
          bulk_commit();
          bulk_wait_read();
        }
      }
    } else if (w == 0) {
      LAUNCHES;
      uint32_t epoch;
      {
        REGION_IDS;
        const unsigned* hp = G->hint[0][4 * (bid >> 6) + (bid >> 3 & 3)];
        uint32_t v = ld_relaxed32(hp + 256 * min(lane, 5));
        if (lane < 3) sts128(base + tab(T_X, lane) + 4096, 0, 0, 0, 0);
        if (lane && lane <= B_WM) mbar_expect_tx(BAR(lane), lane < B_FRAW ? 9728 : lane == B_WM ? 10240 : 4096);
        epoch = EPOCH;
        fence_async_smem();
        const uint32_t rdy = __ballot_sync(~0u, v == epoch << 6) & 31;
        uint32_t nx = 0, mr = 1;
#pragma unroll 1
        for (int it = 0; (nx < 5 || mr) && it < SPIN_LIMIT; it++) {
          const bool second = nx == 5 || (lane && mr && nx >= K(mq));
          if (!(rdy >> nx & 1)) v = ld_relaxed32(hp + 256 * (second ? 5 : nx));
          const uint32_t ok = __ballot_sync(~0u, v == epoch << (second ? 7 : 6)) | (rdy >> nx & 1);
          if (nx < 5 && (ok & 1)) {
            if (nx >= 3) mbar_wait(BAR(B_PFULL - 3 + nx));
            if (elect()) { mbar_expect_tx(BAR(B_XR + nx), 4096); bulk_load(base + tab(T_X, nx), G->xr + (128 * nx + bid) * 256, 4096, BAR(B_XR + nx)); }
          }
          if (mr && (nx == 5 || nx >= K(mq)) && (ok & 2) && !(rdy >> nx & 1)) {
            if (elect()) { mbar_expect_tx(BAR(B_MR), 8192); bulk_load(base + OFF_MR, G->st1, 8192, BAR(B_MR)); mbar_arrive(BAR(B_QTOK)); }
            mr = 0;
          }
          if (nx < 5) nx += ok & 1;
        }
        mod_fetch(G, base, epoch, M8, 2, 5);
      }
      REGION_IDS;
      int h, j, r;
      ffn_role(h, j, r);
      cluster_wait();
      if (elect()) mbar_expect_tx(BAR(B_UVB), 30720);
#pragma unroll 1
      for (int k = 0; k < 5; k++) {
        mbar_wait(BAR(opaque(B_EMPTY + nib(K(uvd), k))));
        if (elect()) tma3d(base + OFF_UV + 6144 * k, &maps.w1u + (r & 1), 0, 40 * (r & 14) + 16 * k, 3 * (4 * h + j), BAR(B_UVB));
      }
      mbar_wait(BAR(B_G));
      {
        const uint2* mp = &G->modv[lane & 4 ? 0 : 2][40 * (r & 14) + (lane & 24) + 2 * (lane & 3)];
        uint4 v[3];
        int it = 0;
#pragma unroll 1
        do {
          v[0] = ld_relaxed128(mp); v[1] = ld_relaxed128(mp + 32); v[2] = ld_relaxed128(mp + 64 - (lane & 16));
        } while (__any_sync(~0u, ((v[0].x ^ epoch) | (v[0].y ^ epoch) | (v[0].z ^ epoch) | (v[0].w ^ epoch) | (v[1].x ^ epoch) | (v[1].y ^ epoch) | (v[1].z ^ epoch) | (v[1].w ^ epoch) |
                                  (v[2].x ^ epoch) | (v[2].y ^ epoch) | (v[2].z ^ epoch) | (v[2].w ^ epoch)) & 1) && ++it < SPIN_LIMIT);
#pragma unroll
        for (int i = 0; i < 3; i++)
          sts32(base + OFF_CO + 128 * i + 4 * lane, badd2(pack_bf16(__uint_as_float(v[i].x) + __uint_as_float(v[i].y), __uint_as_float(v[i].z) + __uint_as_float(v[i].w)), lane & 4 ? 0 : 0x3F803F80u));
      }
      fence_async_smem();
      arrive1(BAR(B_CO));
      ffn_role(h, j, r);
      mbar_wait(BAR(B_ED));
      int it = 0;
#pragma unroll 1
      while (__any_sync(~0u, ld_relaxed32(G->hint[8][4 * h + j]) != 128 * epoch) && ++it < SPIN_LIMIT);
      if (elect()) { mbar_expect_tx(BAR(B_BX), 12288); bulk_load(base + OFF_BX, G->uv[4 * h + j], 12288, BAR(B_BX)); }
      asm volatile("fence.acq_rel.gpu;" ::: "memory");
      if (lane < 8) red_hint(G->hint[7][lane]);
      unsigned x;
      it = 0;
#pragma unroll 1
      do { asm volatile("ld.acquire.gpu.global.u32 %0, [%1];" : "=r"(x) : "l"(G->hint[7][bid >> 4]) : "memory"); } while (__any_sync(~0u, x != 128 * epoch) && ++it < SPIN_LIMIT);
      fence_async_all();
      const int ch = D_ * (epoch & 1);
      mbar_wait(BAR(K(xdep)));
      if (elect()) {
        mbar_expect_tx(BAR(B_FULL + 42), 20480);
#pragma unroll
        for (int k = 0; k < 4; k++) tma2d(base + x1_at(k), &maps.x1b, 128 * r + 64 * h, ch + 128 * j + 32 * (k ^ (j & 1)), BAR(B_FULL + 42));
        tma2d(base + x1_at(4), &maps.x1b, 128 * r + 64 * h, ch + 512 + 32 * j, BAR(B_FULL + 42));
        mbar_expect_tx(BAR(B_FULL + 1), 8192); mbar_expect_tx(BAR(B_FULL + 3), 8192); mbar_expect_tx(BAR(B_FULL + 5), 4096);
      }
      mbar_wait(BAR(B_EMPTY + 37));
      if (elect()) mbar_arrive_remote(mapa(BAR(B_XFREE), h ^ 1));
    } else {
      LAUNCHES;
      {
        REGION_IDS;
        loads<0>(P, maps, base);
      }
      cluster_wait();
      int h, j, r;
      ffn_role(h, j, r);
      mbar_wait(BAR(B_QTD));
      mbar_wait(BAR(B_STD));
      mbar_wait(BAR(B_SC));
      mbar_wait(BAR(B_SC + 2));
      mbar_wait(BAR(B_FL));
#pragma unroll 1
      for (int u = 0; u < 30; u++) {
        if (u == K(mpos)) mod_fetch(G, base, EPOCH, M8, 1, 2);
        if (u < 6) wait_clock(t_start + K(wt0) + u * K(wpace));
        const uint32_t x = P.wdep[u], b = x >> 8 & 1;
        uint32_t s = base + OFF_R + WSLOT * (x >> 9 & 7), f = BAR(B_FULL + (b ? u : u & ~1)), n = x & 0xC000, y = x >> 16, z = 3 * (4 * h + j) + 2 * b;
        const CUtensorMap* m = &maps.w1a + 5 * b;
        asm volatile("{.reg .pred p, q; .reg .b32 i, t; .reg .b64 m; mov.u32 i, 0; add.u32 t, %0, 8192; add.u64 m, %1, 128; elect.sync _|q, 0xffffffff;"
                     "W: mbarrier.try_wait.parity.shared::cta.b64 p, [%6], 0; @p bra.uni D; add.u32 i, i, 1; setp.lt.u32 p, i, %7; @p bra.uni W; D:"
                     "setp.ne.and.u32 p, %3, 0, q; @p mbarrier.arrive.expect_tx.shared::cta.b64 _, [%2], %3;"
                     "@q cp.async.bulk.tensor.3d.shared::cluster.global.mbarrier::complete_tx::bytes [%0], [%1, {0,%4,%5}], [%2];"
                     "@q cp.async.bulk.tensor.3d.shared::cluster.global.mbarrier::complete_tx::bytes [t], [m, {0,%4,%5}], [%2];}"
                     ::"r"(s), "l"(m), "r"(f), "r"(n), "r"(y), "r"(z), "r"(BAR(opaque(x & 255))), "n"(SPIN_LIMIT) : "memory");
      }
    }
  }
}

typedef CUresult (*EncFn)(CUtensorMap*, CUtensorMapDataType, cuuint32_t, void*, const cuuint64_t*, const cuuint64_t*, const cuuint32_t*,
                          const cuuint32_t*, CUtensorMapInterleave, CUtensorMapSwizzle, CUtensorMapL2promotion, CUtensorMapFloatOOBfill);
static int enc_err = 0;
static void enc(EncFn fn, CUtensorMap* m, const void* p, int rank, const cuuint64_t* gd, const cuuint64_t* gs, const cuuint32_t* bd, CUtensorMapSwizzle sw) {
  cuuint32_t es[5] = {1, 1, 1, 1, 1};
  enc_err = 2 * enc_err + (fn(m, CU_TENSOR_MAP_DATA_TYPE_BFLOAT16, rank, (void*)p, gd, gs, bd, es, CU_TENSOR_MAP_INTERLEAVE_NONE, sw,
                              CU_TENSOR_MAP_L2_PROMOTION_L2_128B, CU_TENSOR_MAP_FLOAT_OOB_FILL_NONE) != CUDA_SUCCESS);
}

extern "C" void kernel_launch(void* const* d_in, const int* in_sizes, int n_in, void* d_out, int out_size) {
  const bf16 *q = (const bf16*)d_in[0], *k = (const bf16*)d_in[1], *v = (const bf16*)d_in[2], *shift = (const bf16*)d_in[3],
             *ssmk = (const bf16*)d_in[4], *ssmd = (const bf16*)d_in[5], *w1 = (const bf16*)d_in[7], *w3 = (const bf16*)d_in[8],
             *w2 = (const bf16*)d_in[9], *c = (const bf16*)d_in[10], *wmod = (const bf16*)d_in[11];
  EncFn fn = nullptr;
  cudaDriverEntryPointQueryResult qr;
  cudaGetDriverEntryPoint("cuTensorMapEncodeTiled", (void**)&fn, cudaEnableDefault, &qr);
  Scratch* pg;
  cudaGetSymbolAddress((void**)&pg, g_s);
  Maps maps;
  enc_err = 0;
  const CUtensorMapSwizzle S128 = CU_TENSOR_MAP_SWIZZLE_128B;
  { cuuint64_t gd[3] = {D_, S_ / 8, 8}, gs[2] = {D_ * 16, D_ * 2}; cuuint32_t b[3] = {64, 4, 8};
    enc(fn, &maps.km, k, 3, gd, gs, b, S128);
    enc(fn, &maps.v, v, 3, gd, gs, b, S128);
    enc(fn, &maps.q, q, 3, gd, gs, b, S128);
    b[2] = 3;
    enc(fn, &maps.kh, k, 3, gd, gs, b, S128); }
  { cuuint64_t gd[3] = {256, 8, D_}, gs[2] = {512, 4096}; cuuint32_t b[3] = {256, 8, 1};
    enc(fn, &maps.fm, ssmk, 3, gd, gs, b, CU_TENSOR_MAP_SWIZZLE_NONE); }
  { cuuint64_t gd[3] = {256, 2, 5}, gs[2] = {512, 1024}; cuuint32_t b[3] = {256, 1, 5};
    enc(fn, &maps.tap, shift, 3, gd, gs, b, CU_TENSOR_MAP_SWIZZLE_NONE); }
  { cuuint64_t gd[3] = {6 * D_, D_, 1}, gs[2] = {6 * D_ * 2, 6 * D_ * 2 * D_}; cuuint32_t b[3] = {64, 64, 1};
    enc(fn, &maps.wm, wmod, 3, gd, gs, b, S128);
    b[1] = 80;
    enc(fn, &maps.wmp, wmod, 3, gd, gs, b, S128); }
  { cuuint64_t gd[3] = {64, D_, F_ / 64}, gs[2] = {F_ * 2, 128}; cuuint32_t b[3] = {64, 16, 3};
    enc(fn, &maps.w1u, w1, 3, gd, gs, b, S128);
    enc(fn, &maps.w3u, w3, 3, gd, gs, b, S128);
    b[1] = 32; b[2] = 2;
    enc(fn, &maps.w1a, w1, 3, gd, gs, b, S128);
    enc(fn, &maps.w3a, w3, 3, gd, gs, b, S128);
    b[1] = 64; b[2] = 1;
    enc(fn, &maps.w1b, w1, 3, gd, gs, b, S128);
    enc(fn, &maps.w3b, w3, 3, gd, gs, b, S128); }
  { cuuint64_t gd[2] = {S_, D_}, gs[1] = {S_ * 2}; cuuint32_t b1[2] = {64, 64}, b2[2] = {64, 32};
    enc(fn, &maps.xs, pg->xs, 2, gd, gs, b1, S128);
    gd[1] = 2 * D_;
    enc(fn, &maps.x1b, pg->x1, 2, gd, gs, b2, S128);
    enc(fn, &maps.x1s, pg->x1, 2, gd, gs, b2, CU_TENSOR_MAP_SWIZZLE_NONE); }
  { cuuint64_t gd[5] = {D_, 2, 4, 4, 48}, gs[4] = {D_ * 2, D_ * 4, D_ * 16, D_ * 64}; cuuint32_t b[5] = {64, 2, 4, 4, 2};
    enc(fn, &maps.w2a, w2, 5, gd, gs, b, S128);
    gs[1] = D_ * 16; gs[2] = D_ * 4;
    enc(fn, &maps.w2b, w2, 5, gd, gs, b, S128); }
  { cuuint64_t gd[2] = {D_, S_}, gs[1] = {D_ * 2}; cuuint32_t b1[2] = {64, 16}, b2[2] = {32, 16};
    enc(fn, &maps.outa, d_out, 2, gd, gs, b1, S128);
    enc(fn, &maps.outb, d_out, 2, gd, gs, b2, CU_TENSOR_MAP_SWIZZLE_64B); }
  if (enc_err) return;
  cudaFuncSetAttribute(k_fused<0>, cudaFuncAttributeMaxDynamicSharedMemorySize, SMEM_BYTES);
  cudaFuncSetAttribute(k_fused<128>, cudaFuncAttributeMaxDynamicSharedMemorySize, SMEM_BYTES);
  cudaLaunchConfig_t cfg = {132, 512, SMEM_BYTES};
  cudaLaunchAttribute at = {cudaLaunchAttributeClusterDimension};
  at.val.clusterDim.x = 2; at.val.clusterDim.y = at.val.clusterDim.z = 1;
  cfg.attrs = &at; cfg.numAttrs = 1;
  int nc = 0;
  cudaOccupancyMaxActiveClusters(&nc, k_fused<0>, &cfg);
  Ptrs P = {c, ssmd, pg, 32, 1.f};
  const char* ho = "abcdefghijklmnopqrstuvwxyz{|}~";
  memset(P.hl, 255, sizeof(P.hl));
  for (int k = 0, n = 0; k < 30; k++) {
    const int i = ho[k] - 'a';
    if (i >= 20 || !(M8 >> i / 4 & 1)) ((uint8_t*)P.hl)[n++] = i;
  }
  for (int u = 0; u < 30; u++) P.wdep[u] = (u < 4 ? B_FL + 1 + u / 3 : u < 6 ? B_G : B_EMPTY + (u < 26 ? (u - 6) | 1 : u - 6)) | (u >= 20) << 8 | u % 6 << 9 | (u < 20 ? 3 * (~u & 1) : 1 + (u >= 26)) << 14 | (u < 20 ? 32 * u : 64 * (second(u - 20) % 10)) << 16;
  const int adep[14] = {B_PEMPTY, B_PEMPTY, B_PFULL + 4, B_PEMPTY + 1, B_PEMPTY + 2, B_EMPTY + 5, B_EMPTY + 7, B_PEMPTY + 3, B_EMPTY + 2 * UVS + 1, B_EMPTY + 2 * UVS + 1, B_EMPTY + 20, B_EMPTY + 21, B_EMPTY + 22, B_EMPTY + 23};
  const char *ad = "--*--d----uvwx", *wd = "255679:<=>?@", *hd = "789;;>?@A";
  for (int n = 0; n < 14; n++) P.adep[n] = adep[n] | (ad[n] == '-' ? adep[n] : ad[n] == '*' ? B_PFULL + 3 : B_EMPTY + ad[n] - 'a') << 8 | (n < 10 ? 2 * n : n + 16) << 16 | n % 10 << 21 | a_at(n) / UNIT << 25;
  const char* ld = "abcd";
  for (int v = 0; v < 12; v++) P.w2t[v] = make_uint2(w2_desc(v), B_EMPTY + 20 + wd[v] - '0');
  for (int m = 0; m < 9; m++) { P.hid[0][m] = hid_at(m, 0) | m / 3 * 4 | (m % 3 + 1); P.hid[1][m] = hid_at(m, 1) | m / 3 * 4 | (m % 3 + 1); P.hid[2][m] = B_EMPTY + 20 + hd[m] - '0'; P.hid[3][m] = m < 5 ? 0 : ld[m - 5] < 'a' ? B_EMPTY + 20 + ld[m - 5] - '0' : B_FULL + 38 + ld[m - 5] - 'a'; }
  if (nc < 66) k_fused<128><<<4, 512, SMEM_BYTES, cudaStreamPerThread>>>(P, maps);
  k_fused<0><<<nc < 66 ? 128 : 132, 512, SMEM_BYTES, cudaStreamPerThread>>>(P, maps);
}
```
